```python
import torch

def _softmax(x, axis=-1):
    return torch.softmax(x, dim=axis)

def _gelu(x):
    return torch.nn.functional.gelu(x, approximate='tanh')

def _silu(x):
    return torch.nn.functional.silu(x)

def _sigmoid(x):
    return torch.sigmoid(x)

def _layernorm(x, axis=-1, eps=1e-05):
    m = x.mean(dim=axis, keepdim=True)
    v = x.var(dim=axis, keepdim=True, unbiased=False)
    return (x - m) / torch.sqrt(v + eps)

def _scatter_add(tgt, idx, src, axis=0):
    return tgt.clone().index_add_(axis, idx, src)

def _segment_sum(src, seg, n):
    out = torch.zeros((n,) + src.shape[1:], dtype=src.dtype)
    return out.index_add_(0, seg, src)

def _pad(x, pw):
    flat = tuple((v for pair in reversed(pw) for v in pair))
    return torch.nn.functional.pad(x, flat)
kernel_name = 'adaLN_cond__linear_kernel_hedgehog__moe_arch_mod__prompt'

def setup_inputs():

    _w = lambda a: (lambda t: t.to(torch.bfloat16) if t.is_floating_point() else t)(torch.as_tensor(a))

    def _A_setup():
        B, S, D, H = (1, 2048, 1024, 32)
        Dh = D // H
        return {'x': _w((lambda *s: torch.randn(*s, dtype=torch.bfloat16) * 0.05)(B, S, D)), 'wqkv': _w((lambda *s: torch.randn(*s, dtype=torch.bfloat16) * 0.4)(D, 3 * D)), 'w_phi': _w((lambda *s: torch.randn(*s, dtype=torch.bfloat16) * 0.4)(H, Dh, Dh) * Dh ** (-0.5)), 'wo': _w((lambda *s: torch.randn(*s, dtype=torch.bfloat16) * 0.05)(D, D))}
    _A_in = _A_setup()

    def _B_setup():
        B, S, D, F, C = (1, 2048, 1024, 3584, 2)
        return {'x': _w((lambda *s: torch.randn(*s, dtype=torch.bfloat16) * 0.05)(B, S, D)), 'w_r': _w((lambda *s: torch.randn(*s, dtype=torch.bfloat16) * 0.1)(D)), 'w_gate': _w((lambda *s: torch.randn(*s, dtype=torch.bfloat16) * 0.05)(D, F)), 'w_up': _w((lambda *s: torch.randn(*s, dtype=torch.bfloat16) * 0.05)(D, F)), 'w_down': _w((lambda *s: torch.randn(*s, dtype=torch.bfloat16) * 0.05)(F, D))}
    _B_in = _B_setup()
    return {'A_x': _A_in['x'], 'A_wqkv': _A_in['wqkv'], 'A_w_phi': _A_in['w_phi'], 'A_wo': _A_in['wo'], 'B_x': _B_in['x'], 'B_w_r': _B_in['w_r'], 'B_w_gate': _B_in['w_gate'], 'B_w_up': _B_in['w_up'], 'B_w_down': _B_in['w_down'], 'c': _w((lambda *s: torch.randn(*s, dtype=torch.bfloat16) * 0.2)(1, 1024) * 8.0), 'w_mod': _w((lambda *s: torch.randn(*s, dtype=torch.bfloat16) * 0.2)(1024, 6 * 1024) * 1024 ** (-0.5) * 8.0)}

def reference(A_x, A_wqkv, A_w_phi, A_wo, B_x, B_w_r, B_w_gate, B_w_up, B_w_down, c, w_mod):

    def _A_ref(x, wqkv, w_phi, wo):
        B, S, D = x.shape
        H = 32
        Dh = D // H
        qkv = (lambda x, *d: x.permute(*d))((x @ wqkv).reshape(B, S, 3, H, Dh), 2, 0, 3, 1, 4)
        q, k, v = (qkv[0], qkv[1], qkv[2])
        pq = torch.einsum('bhsd,hdf->bhsf', q, w_phi)
        pk = torch.einsum('bhsd,hdf->bhsf', k, w_phi)
        phi_q = torch.concatenate([_softmax(pq, axis=-1), _softmax(-pq, axis=-1)], axis=-1)
        phi_k = torch.concatenate([_softmax(pk, axis=-1), _softmax(-pk, axis=-1)], axis=-1)
        kv = torch.einsum('bhsf,bhsd->bhfd', phi_k, v)
        z = torch.einsum('bhsf->bhf', phi_k)
        num = torch.einsum('bhqf,bhfd->bhqd', phi_q, kv)
        den = torch.einsum('bhqf,bhf->bhq', phi_q, z)[..., None] + 1e-06
        o = num / den
        return (lambda x, *d: x.permute(*d))(o, 0, 2, 1, 3).reshape(B, S, D) @ wo

    def _B_ref(x, w_r, w_gate, w_up, w_down):
        B, S, D = x.shape
        C = 2
        r = x @ w_r
        idx = torch.argsort(-r, axis=-1)[:, :C]
        idx_e = (lambda x, n, axis: torch.repeat_interleave(x, n, dim=axis))(idx.reshape(B, C, 1), D, axis=2)
        x_sel = (lambda x, i, axis: torch.take_along_dim(x, i, dim=axis))(x, idx_e, axis=1)
        g = _silu(x_sel @ w_gate)
        u = x_sel @ w_up
        y = g * u @ w_down
        r_sel = _sigmoid((lambda x, i, axis: torch.take_along_dim(x, i, dim=axis))(r, idx, axis=1))
        y = y * r_sel.reshape(B, C, 1)
        b_off = (torch.arange(B) * S).reshape(B, 1)
        flat_idx = (idx + b_off).reshape(B * C)
        zero = (x * 0.0).reshape(B * S, D)
        upd = _scatter_add(zero, flat_idx, y.reshape(B * C, D), axis=0)
        return x + upd.reshape(B, S, D)
    x = A_x
    mod = (_silu(c) @ w_mod).reshape(c.shape[0], 6, 1, -1)
    sa, ca, ga, sb, cb, gb = (mod[:, 0].clone(), mod[:, 1].clone(), mod[:, 2].clone(), mod[:, 3].clone(), mod[:, 4].clone(), mod[:, 5].clone())
    h = _layernorm(x, axis=-1) * (1 + ca) + sa
    x = x + ga * _A_ref(h, A_wqkv, A_w_phi, A_wo)
    h = _layernorm(x, axis=-1) * (1 + cb) + sb
    x = x + gb * _B_ref(h, B_w_r, B_w_gate, B_w_up, B_w_down)
    return x
```

```cpp
#include <cuda_runtime.h>
#include <cuda.h>
#include <cuda_bf16.h>
#include <stdint.h>

namespace {

typedef __nv_bfloat16 bf16;

constexpr int NTHREADS = 384;
constexpr int POLL_MAX = 400000;
constexpr uint32_t EMPTY = 0xffffffffu;

constexpr uint32_t OFF_RING = 0;
constexpr uint32_t OFF_XS   = 131072;
constexpr uint32_t OFF_WST  = 163840;
constexpr uint32_t OFF_XT   = 0;
constexpr uint32_t OFF_GA   = 32768;
constexpr uint32_t OFF_UP   = 0;
constexpr uint32_t OFF_DB   = 65536;
constexpr uint32_t OFF_V    = 131072;
constexpr uint32_t OFF_PHI  = 163840;
constexpr uint32_t OFF_DA   = 131072;
constexpr uint32_t OFF_OUT  = 163840;
constexpr uint32_t OFF_WPHI = 196608;
constexpr uint32_t OFF_SP   = 204800;
constexpr uint32_t OFF_Z    = 221184;
constexpr uint32_t OFF_ONES = 225280;
constexpr uint32_t OFF_MODS = 226304;
constexpr uint32_t OFF_GB   = 196608;
constexpr uint32_t OFF_BQ   = 229376;
constexpr uint32_t OFF_BAR  = 230400;
constexpr uint32_t OFF_ATOT = OFF_BAR + 632;
constexpr uint32_t OFF_PAR  = OFF_BAR + 640;
constexpr uint32_t SMEM_BYTES = 232448;
constexpr uint32_t OFF_SILU = OFF_Z;
constexpr uint32_t OFF_RED0 = OFF_Z + 2048;
constexpr uint32_t OFF_ST2  = OFF_DB + 32768;
constexpr uint32_t OFF_KEYS = OFF_ST2 + 1024;
constexpr uint32_t OFF_SEL  = OFF_KEYS + 512;
constexpr uint32_t OFF_ROWS = OFF_ST2 + 2048;
constexpr uint32_t OFF_PX   = OFF_ROWS + 2560;
constexpr uint32_t OFF_HID  = OFF_PX + 1024;

enum {
    B_F1 = 0, B_E1 = 3, B_MOD = 6, B_WPHI = 10, B_RF = 11, B_PHI = 15, B_PHIFREE = 17, B_KVF = 19, B_OWN = 21, B_PAR = 23,
    B_FA = 24, B_FB = 28, B_ED = 32, B_S0 = 36, B_STFREE = 37, B_MP = 38, B_GU = 39, B_WD = 40, B_PX = 41, B_X2 = 42, B_ST2 = 43,
    B_RD = 44, B_ROWS = 45, B_OUTW = 46, B_PUB = 47, B_COUNT = 49, B_XS = 50, B_WS = 58
};

struct Scratch {
    uint4 os[256 * 1024];
    uint4 kvp[32 * 256 * 32];
    uint4 kvf[32 * 288];
    uint4 st1[2048];
    uint4 mp[128 * 16];
    uint4 rest[1024];
    uint4 flo[256 * 2];
    uint4 st2[2048];
    uint4 cand[64 * 2];
    uint4 rowh[64 * 128];
    uint4 rowx[64 * 128];
    uint4 rsc[64 * 8 * 2];
    uint4 yp[56 * 512];
    unsigned done[4];
};
__device__ __align__(1024) Scratch g_scratch;
#define TS(i) do {} while (0)
#define WT0()
#define WTJ(j)

__device__ __forceinline__ uint32_t smem_u32(const void* p) { return (uint32_t)__cvta_generic_to_shared(p); }
__device__ __forceinline__ uint32_t clk32() { uint32_t c; asm volatile("mov.u32 %0, %%clock;" : "=r"(c) :: "memory"); return c; }
__device__ __forceinline__ void arrive_one(uint32_t bar) {
    asm volatile("{\n.reg .pred p;\nelect.sync _|p, 0xffffffff;\n@p mbarrier.arrive.shared::cta.b64 _, [%0];\n}" :: "r"(bar) : "memory");
}
__device__ __forceinline__ void arrive_if(uint32_t bar, uint32_t on) {
    asm volatile("{\n.reg .pred q, p;\nelect.sync _|q, 0xffffffff;\nsetp.ne.and.u32 p, %1, 0, q;\n@p mbarrier.arrive.shared::cta.b64 _, [%0];\n}" :: "r"(bar), "r"(on) : "memory");
}
__device__ __forceinline__ void st_partner128(uint32_t a, uint32_t bar, uint32_t cta, float x, float y, float z, float w) {
    asm volatile("{\n.reg .b32 ra, rb;\nmapa.shared::cluster.u32 ra, %0, %2;\nmapa.shared::cluster.u32 rb, %1, %2;\n"
        "st.async.weak.shared::cluster.mbarrier::complete_tx::bytes.v4.f32 [ra], {%3, %4, %5, %6}, [rb];\n}" :: "r"(a), "r"(bar), "r"(cta), "f"(x), "f"(y), "f"(z), "f"(w) : "memory");
}
__device__ __forceinline__ void mbar_wait(uint32_t bar, uint32_t parity) {
    asm volatile("{\n.reg .pred P1;\n.reg .u32 cnt;\nmov.u32 cnt, 0;\nLAB_WAIT:\n"
        "mbarrier.try_wait.parity.shared::cta.b64 P1, [%0], %1;\n@P1 bra DONE;\n"
        "add.u32 cnt, cnt, 1;\nsetp.lt.u32 P1, cnt, 1000000;\n@P1 bra LAB_WAIT;\ntrap;\nDONE:\n}" :: "r"(bar), "r"(parity) : "memory");
}
__device__ __forceinline__ uint64_t policy_evict_first() { uint64_t p; asm("createpolicy.fractional.L2::evict_first.b64 %0, 1.0;" : "=l"(p)); return p; }
__device__ __forceinline__ void bulk_commit() { asm volatile("cp.async.bulk.commit_group;" ::: "memory"); }
__device__ __forceinline__ void bulk_wait() { asm volatile("cp.async.bulk.wait_group 0;" ::: "memory"); }
__device__ __forceinline__ void tmap_prefetch(const CUtensorMap* tm) { asm volatile("prefetch.tensormap [%0];" :: "l"(tm) : "memory"); }
#define EL "{\n.reg .pred e;\nelect.sync _|e, 0xffffffff;\n@e "
__device__ __forceinline__ void expect_tx_e(uint32_t bar, uint32_t bytes) { asm volatile(EL "mbarrier.arrive.expect_tx.shared::cta.b64 _, [%0], %1;\n}" :: "r"(bar), "r"(bytes) : "memory"); }
__device__ __forceinline__ void tma2_e(uint32_t dst, const CUtensorMap* tm, int c0, int c1, uint32_t bar) {
    asm volatile(EL "cp.async.bulk.tensor.2d.shared::cluster.global.mbarrier::complete_tx::bytes [%0], [%1, {%3, %4}], [%2];\n}"
        :: "r"(dst), "l"(tm), "r"(bar), "r"(c0), "r"(c1) : "memory");
}
__device__ __forceinline__ void tma2_ef_e(uint32_t dst, const CUtensorMap* tm, int c0, int c1, uint32_t bar) {
    asm volatile(EL "cp.async.bulk.tensor.2d.shared::cluster.global.mbarrier::complete_tx::bytes.L2::cache_hint [%0], [%1, {%3, %4}], [%2], %5;\n}"
        :: "r"(dst), "l"(tm), "r"(bar), "r"(c0), "r"(c1), "l"(policy_evict_first()) : "memory");
}
__device__ __forceinline__ void tma3_ef_e(uint32_t dst, const CUtensorMap* tm, int row, int blk, uint32_t bar) {
    asm volatile(EL "cp.async.bulk.tensor.3d.shared::cluster.global.mbarrier::complete_tx::bytes.L2::cache_hint [%0], [%1, {0, %3, %4}], [%2], %5;\n}"
        :: "r"(dst), "l"(tm), "r"(bar), "r"(row), "r"(blk), "l"(policy_evict_first()) : "memory");
}
__device__ __forceinline__ void tma4_ef_e(uint32_t dst, const CUtensorMap* tm, int row, int blk, uint32_t bar) {
    asm volatile(EL "cp.async.bulk.tensor.4d.shared::cluster.global.mbarrier::complete_tx::bytes.L2::cache_hint [%0], [%1, {0, %3, %4, 0}], [%2], %5;\n}"
        :: "r"(dst), "l"(tm), "r"(bar), "r"(row), "r"(blk), "l"(policy_evict_first()) : "memory");
}
__device__ __forceinline__ void bulk_load_e(uint32_t dst, const void* src, uint32_t bytes, uint32_t bar) {
    asm volatile(EL "cp.async.bulk.shared::cluster.global.mbarrier::complete_tx::bytes [%0], [%1], %2, [%3];\n}" :: "r"(dst), "l"(src), "r"(bytes), "r"(bar) : "memory");
}
__device__ __forceinline__ void bulk_store_e(void* dst, uint32_t src, uint32_t bytes) {
    asm volatile(EL "cp.async.bulk.global.shared::cta.bulk_group [%0], [%1], %2;\n}" :: "l"(dst), "r"(src), "r"(bytes) : "memory");
}
__device__ __forceinline__ void st_flag_e(void* p, unsigned v) { asm volatile(EL "st.relaxed.gpu.global.u32 [%0], %1;\n}" :: "l"(p), "r"(v) : "memory"); }
__device__ __forceinline__ void mbar_init(uint32_t bar, uint32_t cnt) { asm volatile("mbarrier.init.shared::cta.b64 [%0], %1;" :: "r"(bar), "r"(cnt) : "memory"); }
__device__ __forceinline__ void mbar_init_e(uint32_t bar, uint32_t cnt) { asm volatile(EL "mbarrier.init.shared::cta.b64 [%0], %1;\n}" :: "r"(bar), "r"(cnt) : "memory"); }
__device__ __forceinline__ bool elect_one() {
    uint32_t p;
    asm volatile("{\n.reg .pred P;\nelect.sync _|P, 0xffffffff;\nselp.u32 %0, 1, 0, P;\n}" : "=r"(p));
    return p;
}
__device__ __forceinline__ void wg_fence() { asm volatile("wgmma.fence.sync.aligned;" ::: "memory"); }
__device__ __forceinline__ void wg_commit() { asm volatile("wgmma.commit_group.sync.aligned;" ::: "memory"); }
template<int N> __device__ __forceinline__ void wg_wait() { asm volatile("wgmma.wait_group.sync.aligned %0;" :: "n"(N) : "memory"); }
template<int N> __device__ __forceinline__ void acc_fence(float (&d)[N]) {
    #pragma unroll
    for (int i = 0; i < N; i++) asm volatile("" : "+f"(d[i]) :: "memory");
}
__device__ __forceinline__ uint64_t mk_desc(uint32_t addr, uint32_t lbo, uint32_t sbo, uint32_t swz) {
    uint32_t lo = ((addr & 0x3FFFF) >> 4) | (((lbo & 0x3FFFF) >> 4) << 16);
    uint32_t hi = (sbo >> 4) | (swz << 30);
    return ((uint64_t)hi << 32) | lo;
}
__device__ __forceinline__ uint64_t desc_add(uint64_t d, uint32_t bytes) { return (d & 0xffffffff00000000ull) | (uint32_t)((uint32_t)d + (bytes >> 4)); }
__device__ __forceinline__ uint64_t desc_raw(uint64_t d, uint32_t inc) { return (d & 0xffffffff00000000ull) | (uint32_t)((uint32_t)d + inc); }
__device__ __forceinline__ void fence_async_smem() { asm volatile("fence.proxy.async.shared::cta;" ::: "memory"); }
__device__ __forceinline__ void bar_sync(int id, int n) { asm volatile("bar.sync %0, %1;" :: "r"(id), "r"(n) : "memory"); }
__device__ __forceinline__ void bar_arrive(int id, int n) { asm volatile("bar.arrive %0, %1;" :: "r"(id), "r"(n) : "memory"); }
template<int R> __device__ __forceinline__ void reg_inc() { asm volatile("setmaxnreg.inc.sync.aligned.u32 %0;" :: "n"(R)); }
template<int R> __device__ __forceinline__ void reg_dec() { asm volatile("setmaxnreg.dec.sync.aligned.u32 %0;" :: "n"(R)); }
__device__ __forceinline__ void cluster_arrive() { asm volatile("barrier.cluster.arrive.relaxed.aligned;" ::: "memory"); }
__device__ __forceinline__ void cluster_wait() { asm volatile("barrier.cluster.wait.acquire.aligned;" ::: "memory"); }

__device__ __forceinline__ void stsm4(uint32_t addr, uint32_t r0, uint32_t r1, uint32_t r2, uint32_t r3) {
    asm volatile("stmatrix.sync.aligned.m8n8.x4.shared.b16 [%0], {%1,%2,%3,%4};" :: "r"(addr), "r"(r0), "r"(r1), "r"(r2), "r"(r3) : "memory");
}
__device__ __forceinline__ void ldsm4(uint32_t& r0, uint32_t& r1, uint32_t& r2, uint32_t& r3, uint32_t addr) {
    asm volatile("ldmatrix.sync.aligned.m8n8.x4.shared.b16 {%0,%1,%2,%3}, [%4];" : "=r"(r0), "=r"(r1), "=r"(r2), "=r"(r3) : "r"(addr) : "memory");
}
__device__ __forceinline__ void ldsm4t(uint32_t& r0, uint32_t& r1, uint32_t& r2, uint32_t& r3, uint32_t addr) {
    asm volatile("ldmatrix.sync.aligned.m8n8.x4.trans.shared.b16 {%0,%1,%2,%3}, [%4];" : "=r"(r0), "=r"(r1), "=r"(r2), "=r"(r3) : "r"(addr) : "memory");
}
__device__ __forceinline__ void mma16816(float (&d)[4], uint32_t a0, uint32_t a1, uint32_t a2, uint32_t a3, uint32_t b0, uint32_t b1) {
    asm("mma.sync.aligned.m16n8k16.row.col.f32.bf16.bf16.f32 {%0,%1,%2,%3}, {%4,%5,%6,%7}, {%8,%9}, {%0,%1,%2,%3};"
        : "+f"(d[0]), "+f"(d[1]), "+f"(d[2]), "+f"(d[3]) : "r"(a0), "r"(a1), "r"(a2), "r"(a3), "r"(b0), "r"(b1));
}
__device__ __forceinline__ uint4 lds128(uint32_t a) { uint4 v; asm volatile("ld.shared.v4.b32 {%0,%1,%2,%3}, [%4];" : "=r"(v.x), "=r"(v.y), "=r"(v.z), "=r"(v.w) : "r"(a) : "memory"); return v; }
__device__ __forceinline__ uint2 lds64(uint32_t a) { uint2 v; asm volatile("ld.shared.v2.b32 {%0,%1}, [%2];" : "=r"(v.x), "=r"(v.y) : "r"(a) : "memory"); return v; }
__device__ __forceinline__ uint32_t lds32(uint32_t a) { uint32_t v; asm volatile("ld.shared.b32 %0, [%1];" : "=r"(v) : "r"(a) : "memory"); return v; }
__device__ __forceinline__ float ldsf(uint32_t a) { float v; asm volatile("ld.shared.f32 %0, [%1];" : "=f"(v) : "r"(a) : "memory"); return v; }
__device__ __forceinline__ uint32_t lds16(uint32_t a) { uint16_t v; asm volatile("ld.shared.b16 %0, [%1];" : "=h"(v) : "r"(a) : "memory"); return v; }
__device__ __forceinline__ void sts128(uint32_t a, uint4 v) { asm volatile("st.shared.v4.b32 [%0], {%1,%2,%3,%4};" :: "r"(a), "r"(v.x), "r"(v.y), "r"(v.z), "r"(v.w) : "memory"); }
__device__ __forceinline__ void sts64(uint32_t a, uint32_t x, uint32_t y) { asm volatile("st.shared.v2.b32 [%0], {%1,%2};" :: "r"(a), "r"(x), "r"(y) : "memory"); }
__device__ __forceinline__ void sts32(uint32_t a, uint32_t x) { asm volatile("st.shared.b32 [%0], %1;" :: "r"(a), "r"(x) : "memory"); }
__device__ __forceinline__ void stsf(uint32_t a, float x) { asm volatile("st.shared.f32 [%0], %1;" :: "r"(a), "f"(x) : "memory"); }
__device__ __forceinline__ void sts16(uint32_t a, uint32_t x) { asm volatile("st.shared.b16 [%0], %1;" :: "r"(a), "h"((uint16_t)x) : "memory"); }

__device__ __forceinline__ uint4 ldg128(const void* p) { uint4 v; asm volatile("ld.global.nc.L1::no_allocate.v4.b32 {%0,%1,%2,%3}, [%4];" : "=r"(v.x), "=r"(v.y), "=r"(v.z), "=r"(v.w) : "l"(p)); return v; }
__device__ __forceinline__ uint2 ldg64(const void* p) { uint2 v; asm volatile("ld.global.nc.v2.b32 {%0,%1}, [%2];" : "=r"(v.x), "=r"(v.y) : "l"(p)); return v; }
__device__ __forceinline__ uint32_t ldg32(const void* p) { uint32_t v; asm volatile("ld.global.nc.b32 %0, [%1];" : "=r"(v) : "l"(p)); return v; }
__device__ __forceinline__ void stg128(void* p, uint4 v) { asm volatile("st.global.v4.b32 [%0], {%1,%2,%3,%4};" :: "l"(p), "r"(v.x), "r"(v.y), "r"(v.z), "r"(v.w) : "memory"); }
__device__ __forceinline__ void stg_fill(void* p, uint32_t v) { asm volatile("st.global.v4.b32 [%0], {%1,%1,%1,%1};" :: "l"(p), "r"(v) : "memory"); }
__device__ __forceinline__ void st_ll(void* p, uint32_t x, uint32_t y, uint32_t z, uint32_t w) {
    asm volatile("{\n.reg .b128 t;\n.reg .b64 a, b;\nmov.b64 a, {%1, %2};\nmov.b64 b, {%3, %4};\nmov.b128 t, {a, b};\nst.relaxed.gpu.global.b128 [%0], t;\n}"
        :: "l"(p), "r"(x), "r"(y), "r"(z), "r"(w) : "memory");
}
__device__ __forceinline__ uint4 ld_ll(const void* p) {
    uint4 v;
    asm volatile("{\n.reg .b128 t;\n.reg .b64 a, b;\nld.relaxed.gpu.global.b128 t, [%4];\nmov.b128 {a, b}, t;\nmov.b64 {%0, %1}, a;\nmov.b64 {%2, %3}, b;\n}"
        : "=r"(v.x), "=r"(v.y), "=r"(v.z), "=r"(v.w) : "l"(p) : "memory");
    return v;
}
__device__ __forceinline__ void ld_ll_if(uint4& v, const void* p, bool go) {
    asm volatile("{\n.reg .b128 t;\n.reg .b64 a, b;\n.reg .pred q;\nsetp.ne.u32 q, %5, 0;\nmov.b64 a, {%0, %1};\nmov.b64 b, {%2, %3};\nmov.b128 t, {a, b};\n"
        "@q ld.relaxed.gpu.global.b128 t, [%4];\nmov.b128 {a, b}, t;\nmov.b64 {%0, %1}, a;\nmov.b64 {%2, %3}, b;\n}"
        : "+r"(v.x), "+r"(v.y), "+r"(v.z), "+r"(v.w) : "l"(p), "r"((uint32_t)go) : "memory");
}
__device__ __forceinline__ void st_ll8(void* p, uint32_t x, uint32_t y) {
    asm volatile("{\n.reg .b64 a;\nmov.b64 a, {%1, %2};\nst.relaxed.gpu.global.b64 [%0], a;\n}" :: "l"(p), "r"(x), "r"(y) : "memory");
}
__device__ __forceinline__ void st_ll4(void* p, uint32_t x) { asm volatile("st.relaxed.gpu.global.b32 [%0], %1;" :: "l"(p), "r"(x) : "memory"); }
__device__ __forceinline__ unsigned ld_rlx(const void* p) { unsigned v; asm volatile("ld.relaxed.gpu.global.u32 %0, [%1];" : "=r"(v) : "l"(p) : "memory"); return v; }
__device__ __forceinline__ void red_add4(void* p, float x, float y, float z, float w) {
    asm volatile("red.relaxed.gpu.global.add.v4.f32 [%0], {%1, %2, %3, %4};" :: "l"(p), "f"(x), "f"(y), "f"(z), "f"(w) : "memory");
}
__device__ __forceinline__ void fence_rel_gpu() { asm volatile("fence.proxy.async.global;\nfence.release.gpu;" ::: "memory"); }
__device__ __forceinline__ void fence_acq_gpu() { asm volatile("fence.acquire.gpu;" ::: "memory"); }
template<int N> __device__ __forceinline__ void poll_words(uint4 (&v)[N], const uint4* p, int stride, uint32_t tag) {
    #pragma unroll 1
    for (int it = 0; it < POLL_MAX; it++) {
        bool ok = true;
        #pragma unroll
        for (int i = 0; i < N; i++) v[i] = ld_ll(p + i * stride);
        #pragma unroll
        for (int i = 0; i < N; i++) ok = ok && (v[i].w == tag);
        if (ok) break;
    }
}
template<int B> __device__ __forceinline__ uint32_t low_byte(float v, uint32_t src) { return __byte_perm(__float_as_uint(v), src, 0x3214 + B); }
__device__ __forceinline__ uint32_t low_bits(float v, uint32_t tag2) { return (__float_as_uint(v) & ~3u) | tag2; }
__device__ __forceinline__ bool tagged2(uint32_t w, uint32_t tag2) { return (w & 3u) == tag2; }
__device__ __forceinline__ uint32_t umax4(uint4 v) { return max(max(v.x, v.y), max(v.z, v.w)); }
constexpr uint32_t ONE2 = 0x3F803F80u;
__device__ __forceinline__ uint32_t pack2(float lo, float hi) { uint32_t d; asm("cvt.rn.bf16x2.f32 %0, %1, %2;" : "=r"(d) : "f"(hi), "f"(lo)); return d; }
__device__ __forceinline__ float bf_lo(uint32_t v) { return __uint_as_float(v << 16); }
__device__ __forceinline__ float bf_lo_alu(uint32_t v) { uint32_t d; asm("prmt.b32 %0, %1, 0, 0x1044;" : "=r"(d) : "r"(v)); return __uint_as_float(d); }
__device__ __forceinline__ float bf_hi(uint32_t v) { return __uint_as_float(v & 0xffff0000u); }
__device__ __forceinline__ float rbf(float x) { return bf_lo(pack2(x, 0.f)); }
__device__ __forceinline__ uint32_t hsub2(uint32_t a, uint32_t b) { uint32_t d; asm("sub.rn.bf16x2 %0, %1, %2;" : "=r"(d) : "r"(a), "r"(b)); return d; }
__device__ __forceinline__ uint32_t hadd2(uint32_t a, uint32_t b) { uint32_t d; asm("add.rn.bf16x2 %0, %1, %2;" : "=r"(d) : "r"(a), "r"(b)); return d; }
__device__ __forceinline__ uint32_t hmul2(uint32_t a, uint32_t b) { uint32_t d; asm("mul.rn.bf16x2 %0, %1, %2;" : "=r"(d) : "r"(a), "r"(b)); return d; }
__device__ __forceinline__ uint32_t hmax2(uint32_t a, uint32_t b) { uint32_t d; asm("max.bf16x2 %0, %1, %2;" : "=r"(d) : "r"(a), "r"(b)); return d; }
__device__ __forceinline__ uint32_t hmin2(uint32_t a, uint32_t b) { uint32_t d; asm("min.bf16x2 %0, %1, %2;" : "=r"(d) : "r"(a), "r"(b)); return d; }
__device__ __forceinline__ float ex2(float x) { float y; asm("ex2.approx.ftz.f32 %0, %1;" : "=f"(y) : "f"(x)); return y; }
__device__ __forceinline__ float rcp(float x) { float y; asm("rcp.approx.ftz.f32 %0, %1;" : "=f"(y) : "f"(x)); return y; }
__device__ __forceinline__ float shfl_x(float v, int m) { return __shfl_xor_sync(0xffffffffu, v, m); }
constexpr float LOG2E = 1.4426950408889634f;
__device__ __forceinline__ float sigmoidf(float x) { return rcp(1.0f + ex2(-LOG2E * x)); }
__device__ __forceinline__ uint32_t ln_pair(uint32_t x, uint32_t m2, float rinv, uint32_t a, uint32_t s) {
    uint32_t d = hsub2(x, m2);
    uint32_t n = pack2(bf_lo(d) * rinv, bf_hi(d) * rinv);
    return hadd2(hmul2(n, a), s);
}
__device__ __forceinline__ void ln_final(float s1, float s2, uint32_t& m2, float& rinv) {
    const float mean = s1 * (1.0f / 1024.0f), var = fmaf(-mean, mean, s2 * (1.0f / 1024.0f));
    m2 = pack2(mean, mean);
    float sd;
    asm("sqrt.approx.ftz.f32 %0, %1;" : "=f"(sd) : "f"(rbf(rbf(fmaxf(var, 0.f)) + 1e-5f)));
    rinv = rcp(rbf(sd));
}
__device__ __forceinline__ uint32_t f2key(float f) { uint32_t u = __float_as_uint(f); return (u & 0x80000000u) ? ~u : (u | 0x80000000u); }

struct FmState { float cp, cn, sp, sn; };
__device__ __forceinline__ uint32_t fm_extrema(const uint32_t* p) {
    const uint32_t mx = hmax2(hmax2(p[0], p[2]), hmax2(p[4], p[6]));
    const uint32_t mn = hmin2(hmin2(p[0], p[2]), hmin2(p[4], p[6])) ^ 0x80008000u;
    return hmax2(__byte_perm(mx, mn, 0x5410), __byte_perm(mx, mn, 0x7632));
}
template<bool PREV, bool CUR, bool NEXT>
__device__ __forceinline__ void fm_slot(FmState& s, const float (&ep)[16], uint32_t* o, const uint32_t* p, float (&e)[16], const uint32_t* pn) {
    float psp = s.sp, psn = s.sn, rp = 0.f, rn = 0.f, sp = 0.f, sn = 0.f;
    uint32_t mm = 0;
    #pragma unroll
    for (int j = 0; j < 4; j++) {
        float a0 = 0.f, a1 = 0.f, b0 = 0.f, b1 = 0.f;
        if (CUR) {
            const float f0 = bf_lo_alu(p[2 * j]), f1 = bf_hi(p[2 * j]);
            a0 = fmaf(f0, LOG2E, s.cp); a1 = fmaf(f1, LOG2E, s.cp); b0 = fmaf(f0, -LOG2E, s.cn); b1 = fmaf(f1, -LOG2E, s.cn);
            e[2 * j] = ex2(a0);
        }
        if (PREV && j == 0) { psp += shfl_x(psp, 1); psn += shfl_x(psn, 1); }
        if (NEXT && j == 0) mm = fm_extrema(pn);
        if (PREV && j >= 2) { const float r = j == 2 ? rp : rn; o[8 * (j - 2)] = pack2(ep[8 * (j - 2)] * r, ep[8 * (j - 2) + 1] * r); }
        if (CUR) e[2 * j + 1] = ex2(a1);
        if (NEXT && j == 0) mm = hmax2(mm, __shfl_xor_sync(0xffffffffu, mm, 1));
        if (PREV && j == 1) { const float r = rcp(psp * psn); rp = r * psn; rn = r * psp; }
        if (PREV && j >= 2) { const float r = j == 2 ? rp : rn; o[8 * (j - 2) + 2] = pack2(ep[8 * (j - 2) + 2] * r, ep[8 * (j - 2) + 3] * r); }
        if (CUR && j >= 1) sp = j == 1 ? e[0] + e[1] : (sp + e[2 * j - 2]) + e[2 * j - 1];
        if (CUR) e[8 + 2 * j] = ex2(b0);
        if (PREV && j == 0) { psp += shfl_x(psp, 2); psn += shfl_x(psn, 2); }
        if (NEXT && j == 1) mm = hmax2(mm, __shfl_xor_sync(0xffffffffu, mm, 2));
        if (PREV && j >= 2) { const float r = j == 2 ? rp : rn; o[8 * (j - 2) + 4] = pack2(ep[8 * (j - 2) + 4] * r, ep[8 * (j - 2) + 5] * r); }
        if (CUR) e[9 + 2 * j] = ex2(b1);
        if (PREV && j >= 2) { const float r = j == 2 ? rp : rn; o[8 * (j - 2) + 6] = pack2(ep[8 * (j - 2) + 6] * r, ep[8 * (j - 2) + 7] * r); }
        if (CUR && j >= 1) sn = j == 1 ? e[8] + e[9] : (sn + e[6 + 2 * j]) + e[7 + 2 * j];
    }
    if (NEXT) { s.cp = -bf_lo(mm) * LOG2E; s.cn = -bf_hi(mm) * LOG2E; }
    if (CUR) { s.sp = (sp + e[6]) + e[7]; s.sn = (sn + e[14]) + e[15]; }
}
__device__ __forceinline__ float reduce8(const float (&v)[8], int lane) {
    const bool b3 = lane & 16, b2 = lane & 8, b1 = lane & 4;
    float a[4], b[2];
    #pragma unroll
    for (int i = 0; i < 4; i++) { float keep = b3 ? v[4 + i] : v[i], send = b3 ? v[i] : v[4 + i]; a[i] = keep + shfl_x(send, 16); }
    #pragma unroll
    for (int i = 0; i < 2; i++) { float keep = b2 ? a[2 + i] : a[i], send = b2 ? a[i] : a[2 + i]; b[i] = keep + shfl_x(send, 8); }
    float keep = b1 ? b[1] : b[0], send = b1 ? b[0] : b[1];
    return keep + shfl_x(send, 4);
}
template<int TB> __device__ __forceinline__ void wgmma_n32_rs(float (&d)[16], uint32_t a0, uint32_t a1, uint32_t a2, uint32_t a3, uint64_t db, int sc) {
  asm volatile("{\n.reg .pred p;\nsetp.ne.b32 p, %21, 0;\n"
    "wgmma.mma_async.sync.aligned.m64n32k16.f32.bf16.bf16 {%0, %1, %2, %3, %4, %5, %6, %7, %8, %9, %10, %11, %12, %13, %14, %15}, {%16,%17,%18,%19}, %20, p, 1, 1, %22;\n}\n"
    : "+f"(d[0]), "+f"(d[1]), "+f"(d[2]), "+f"(d[3]), "+f"(d[4]), "+f"(d[5]), "+f"(d[6]), "+f"(d[7]), "+f"(d[8]), "+f"(d[9]), "+f"(d[10]), "+f"(d[11]), "+f"(d[12]), "+f"(d[13]), "+f"(d[14]), "+f"(d[15])
    : "r"(a0), "r"(a1), "r"(a2), "r"(a3), "l"(db), "r"(sc), "n"(TB));
}
template<int TA, int TB> __device__ __forceinline__ void wgmma_n40_ss(float (&d)[20], uint64_t da, uint64_t db, int sc) {
  asm volatile("{\n.reg .pred p;\nsetp.ne.b32 p, %22, 0;\n"
    "wgmma.mma_async.sync.aligned.m64n40k16.f32.bf16.bf16 {%0, %1, %2, %3, %4, %5, %6, %7, %8, %9, %10, %11, %12, %13, %14, %15, %16, %17, %18, %19}, %20, %21, p, 1, 1, %23, %24;\n}\n"
    : "+f"(d[0]), "+f"(d[1]), "+f"(d[2]), "+f"(d[3]), "+f"(d[4]), "+f"(d[5]), "+f"(d[6]), "+f"(d[7]), "+f"(d[8]), "+f"(d[9]), "+f"(d[10]), "+f"(d[11]), "+f"(d[12]), "+f"(d[13]), "+f"(d[14]), "+f"(d[15]), "+f"(d[16]), "+f"(d[17]), "+f"(d[18]), "+f"(d[19])
    : "l"(da), "l"(db), "r"(sc), "n"(TA), "n"(TB));
}
template<int TB> __device__ __forceinline__ void wgmma_n40_rs(float (&d)[20], uint32_t a0, uint32_t a1, uint32_t a2, uint32_t a3, uint64_t db, int sc) {
  asm volatile("{\n.reg .pred p;\nsetp.ne.b32 p, %25, 0;\n"
    "wgmma.mma_async.sync.aligned.m64n40k16.f32.bf16.bf16 {%0, %1, %2, %3, %4, %5, %6, %7, %8, %9, %10, %11, %12, %13, %14, %15, %16, %17, %18, %19}, {%20,%21,%22,%23}, %24, p, 1, 1, %26;\n}\n"
    : "+f"(d[0]), "+f"(d[1]), "+f"(d[2]), "+f"(d[3]), "+f"(d[4]), "+f"(d[5]), "+f"(d[6]), "+f"(d[7]), "+f"(d[8]), "+f"(d[9]), "+f"(d[10]), "+f"(d[11]), "+f"(d[12]), "+f"(d[13]), "+f"(d[14]), "+f"(d[15]), "+f"(d[16]), "+f"(d[17]), "+f"(d[18]), "+f"(d[19])
    : "r"(a0), "r"(a1), "r"(a2), "r"(a3), "l"(db), "r"(sc), "n"(TB));
}
template<int TA, int TB> __device__ __forceinline__ void wgmma_n128_ss(float (&d)[64], uint64_t da, uint64_t db, int sc) {
  asm volatile("{\n.reg .pred p;\nsetp.ne.b32 p, %66, 0;\n"
    "wgmma.mma_async.sync.aligned.m64n128k16.f32.bf16.bf16 {%0, %1, %2, %3, %4, %5, %6, %7, %8, %9, %10, %11, %12, %13, %14, %15, %16, %17, %18, %19, %20, %21, %22, %23, %24, %25, %26, %27, %28, %29, %30, %31, %32, %33, %34, %35, %36, %37, %38, %39, %40, %41, %42, %43, %44, %45, %46, %47, %48, %49, %50, %51, %52, %53, %54, %55, %56, %57, %58, %59, %60, %61, %62, %63}, %64, %65, p, 1, 1, %67, %68;\n}\n"
    : "+f"(d[0]), "+f"(d[1]), "+f"(d[2]), "+f"(d[3]), "+f"(d[4]), "+f"(d[5]), "+f"(d[6]), "+f"(d[7]), "+f"(d[8]), "+f"(d[9]), "+f"(d[10]), "+f"(d[11]), "+f"(d[12]), "+f"(d[13]), "+f"(d[14]), "+f"(d[15]), "+f"(d[16]), "+f"(d[17]), "+f"(d[18]), "+f"(d[19]), "+f"(d[20]), "+f"(d[21]), "+f"(d[22]), "+f"(d[23]), "+f"(d[24]), "+f"(d[25]), "+f"(d[26]), "+f"(d[27]), "+f"(d[28]), "+f"(d[29]), "+f"(d[30]), "+f"(d[31]), "+f"(d[32]), "+f"(d[33]), "+f"(d[34]), "+f"(d[35]), "+f"(d[36]), "+f"(d[37]), "+f"(d[38]), "+f"(d[39]), "+f"(d[40]), "+f"(d[41]), "+f"(d[42]), "+f"(d[43]), "+f"(d[44]), "+f"(d[45]), "+f"(d[46]), "+f"(d[47]), "+f"(d[48]), "+f"(d[49]), "+f"(d[50]), "+f"(d[51]), "+f"(d[52]), "+f"(d[53]), "+f"(d[54]), "+f"(d[55]), "+f"(d[56]), "+f"(d[57]), "+f"(d[58]), "+f"(d[59]), "+f"(d[60]), "+f"(d[61]), "+f"(d[62]), "+f"(d[63])
    : "l"(da), "l"(db), "r"(sc), "n"(TA), "n"(TB));
}
template<int TB> __device__ __forceinline__ void wgmma_n128_rs(float (&d)[64], uint32_t a0, uint32_t a1, uint32_t a2, uint32_t a3, uint64_t db, int sc) {
  asm volatile("{\n.reg .pred p;\nsetp.ne.b32 p, %69, 0;\n"
    "wgmma.mma_async.sync.aligned.m64n128k16.f32.bf16.bf16 {%0, %1, %2, %3, %4, %5, %6, %7, %8, %9, %10, %11, %12, %13, %14, %15, %16, %17, %18, %19, %20, %21, %22, %23, %24, %25, %26, %27, %28, %29, %30, %31, %32, %33, %34, %35, %36, %37, %38, %39, %40, %41, %42, %43, %44, %45, %46, %47, %48, %49, %50, %51, %52, %53, %54, %55, %56, %57, %58, %59, %60, %61, %62, %63}, {%64,%65,%66,%67}, %68, p, 1, 1, %70;\n}\n"
    : "+f"(d[0]), "+f"(d[1]), "+f"(d[2]), "+f"(d[3]), "+f"(d[4]), "+f"(d[5]), "+f"(d[6]), "+f"(d[7]), "+f"(d[8]), "+f"(d[9]), "+f"(d[10]), "+f"(d[11]), "+f"(d[12]), "+f"(d[13]), "+f"(d[14]), "+f"(d[15]), "+f"(d[16]), "+f"(d[17]), "+f"(d[18]), "+f"(d[19]), "+f"(d[20]), "+f"(d[21]), "+f"(d[22]), "+f"(d[23]), "+f"(d[24]), "+f"(d[25]), "+f"(d[26]), "+f"(d[27]), "+f"(d[28]), "+f"(d[29]), "+f"(d[30]), "+f"(d[31]), "+f"(d[32]), "+f"(d[33]), "+f"(d[34]), "+f"(d[35]), "+f"(d[36]), "+f"(d[37]), "+f"(d[38]), "+f"(d[39]), "+f"(d[40]), "+f"(d[41]), "+f"(d[42]), "+f"(d[43]), "+f"(d[44]), "+f"(d[45]), "+f"(d[46]), "+f"(d[47]), "+f"(d[48]), "+f"(d[49]), "+f"(d[50]), "+f"(d[51]), "+f"(d[52]), "+f"(d[53]), "+f"(d[54]), "+f"(d[55]), "+f"(d[56]), "+f"(d[57]), "+f"(d[58]), "+f"(d[59]), "+f"(d[60]), "+f"(d[61]), "+f"(d[62]), "+f"(d[63])
    : "r"(a0), "r"(a1), "r"(a2), "r"(a3), "l"(db), "r"(sc), "n"(TB));
}
template<int TB> __device__ __forceinline__ void wgmma_n256_rs(float (&d)[128], uint32_t a0, uint32_t a1, uint32_t a2, uint32_t a3, uint64_t db, int sc) {
  asm volatile("{\n.reg .pred p;\nsetp.ne.b32 p, %133, 0;\n"
    "wgmma.mma_async.sync.aligned.m64n256k16.f32.bf16.bf16 {%0, %1, %2, %3, %4, %5, %6, %7, %8, %9, %10, %11, %12, %13, %14, %15, %16, %17, %18, %19, %20, %21, %22, %23, %24, %25, %26, %27, %28, %29, %30, %31, %32, %33, %34, %35, %36, %37, %38, %39, %40, %41, %42, %43, %44, %45, %46, %47, %48, %49, %50, %51, %52, %53, %54, %55, %56, %57, %58, %59, %60, %61, %62, %63, %64, %65, %66, %67, %68, %69, %70, %71, %72, %73, %74, %75, %76, %77, %78, %79, %80, %81, %82, %83, %84, %85, %86, %87, %88, %89, %90, %91, %92, %93, %94, %95, %96, %97, %98, %99, %100, %101, %102, %103, %104, %105, %106, %107, %108, %109, %110, %111, %112, %113, %114, %115, %116, %117, %118, %119, %120, %121, %122, %123, %124, %125, %126, %127}, {%128,%129,%130,%131}, %132, p, 1, 1, %134;\n}\n"
    : "+f"(d[0]), "+f"(d[1]), "+f"(d[2]), "+f"(d[3]), "+f"(d[4]), "+f"(d[5]), "+f"(d[6]), "+f"(d[7]), "+f"(d[8]), "+f"(d[9]), "+f"(d[10]), "+f"(d[11]), "+f"(d[12]), "+f"(d[13]), "+f"(d[14]), "+f"(d[15]), "+f"(d[16]), "+f"(d[17]), "+f"(d[18]), "+f"(d[19]), "+f"(d[20]), "+f"(d[21]), "+f"(d[22]), "+f"(d[23]), "+f"(d[24]), "+f"(d[25]), "+f"(d[26]), "+f"(d[27]), "+f"(d[28]), "+f"(d[29]), "+f"(d[30]), "+f"(d[31]), "+f"(d[32]), "+f"(d[33]), "+f"(d[34]), "+f"(d[35]), "+f"(d[36]), "+f"(d[37]), "+f"(d[38]), "+f"(d[39]), "+f"(d[40]), "+f"(d[41]), "+f"(d[42]), "+f"(d[43]), "+f"(d[44]), "+f"(d[45]), "+f"(d[46]), "+f"(d[47]), "+f"(d[48]), "+f"(d[49]), "+f"(d[50]), "+f"(d[51]), "+f"(d[52]), "+f"(d[53]), "+f"(d[54]), "+f"(d[55]), "+f"(d[56]), "+f"(d[57]), "+f"(d[58]), "+f"(d[59]), "+f"(d[60]), "+f"(d[61]), "+f"(d[62]), "+f"(d[63]), "+f"(d[64]), "+f"(d[65]), "+f"(d[66]), "+f"(d[67]), "+f"(d[68]), "+f"(d[69]), "+f"(d[70]), "+f"(d[71]), "+f"(d[72]), "+f"(d[73]), "+f"(d[74]), "+f"(d[75]), "+f"(d[76]), "+f"(d[77]), "+f"(d[78]), "+f"(d[79]), "+f"(d[80]), "+f"(d[81]), "+f"(d[82]), "+f"(d[83]), "+f"(d[84]), "+f"(d[85]), "+f"(d[86]), "+f"(d[87]), "+f"(d[88]), "+f"(d[89]), "+f"(d[90]), "+f"(d[91]), "+f"(d[92]), "+f"(d[93]), "+f"(d[94]), "+f"(d[95]), "+f"(d[96]), "+f"(d[97]), "+f"(d[98]), "+f"(d[99]), "+f"(d[100]), "+f"(d[101]), "+f"(d[102]), "+f"(d[103]), "+f"(d[104]), "+f"(d[105]), "+f"(d[106]), "+f"(d[107]), "+f"(d[108]), "+f"(d[109]), "+f"(d[110]), "+f"(d[111]), "+f"(d[112]), "+f"(d[113]), "+f"(d[114]), "+f"(d[115]), "+f"(d[116]), "+f"(d[117]), "+f"(d[118]), "+f"(d[119]), "+f"(d[120]), "+f"(d[121]), "+f"(d[122]), "+f"(d[123]), "+f"(d[124]), "+f"(d[125]), "+f"(d[126]), "+f"(d[127])
    : "r"(a0), "r"(a1), "r"(a2), "r"(a3), "l"(db), "r"(sc), "n"(TB));
}

#define T_S0 1000
#define S_AFTER_MOD 1
#define NC 2
#define T_W1 1500
#define T_WLATE 4000
#define T_REST 8000
#define T_COL1 7500
#define T_COL2 12000
#define PF_START 6000
#define PF_FIRST 0
#define PFP 75
#define CREG 200
constexpr uint32_t PF_PERIOD = PFP;
struct Ptrs { const bf16 *x, *c, *wmod, *wr, *wg, *wu, *wd, *wqkv, *wo; bf16* out; Scratch* s; };

#define BAR(i) (sb + OFF_BAR + 8u * (i))

__device__ __forceinline__ int d_block(int hg, int n) {
    const int m = n - (n >= 9 ? 9 : 2);
    return n < 2 ? 2 * hg + n : 2 * (m + (m >= hg)) + (n >= 9);
}
constexpr int PF_COUNT = 80;
__device__ __forceinline__ void bg_step(const Ptrs& p, int b, int lane, int& piece, uint32_t& due, uint32_t now) {
    #pragma unroll 1
    while (piece < PF_COUNT && (int)(now - due) >= 0) {
        const int i = piece;
        const char* a;
        if (i < 12) a = (const char*)p.wqkv + ((size_t)(i * 128 + b) * 32 + lane) * 128;
        else if (i < 28) a = (const char*)p.wmod + (size_t)((b & 1) * 512 + (i - 12) * 32 + lane) * 12288 + 4096 + (b >> 1) * 128;
        else if (i < 32) a = (const char*)p.wo + ((size_t)((i - 28) * 128 + b) * 32 + lane) * 128;
        else if (i < 64) a = (const char*)(i < 48 ? p.wg : p.wu) + (size_t)((b & 1) * 512 + ((i - 32) & 15) * 32 + lane) * 7168 + (b >> 1) * 128;
        else a = (const char*)p.wd + (size_t)((b >> 1) * 64 + (i - 64) * 4 + (lane >> 3)) * 2048 + (b & 1) * 1024 + (lane & 7) * 128;
        asm volatile("prefetch.global.L2 [%0];" :: "l"(a));
        piece++; due += 4 * PF_PERIOD;
        if (i == 31 && b >= 112) piece = PF_COUNT;
    }
}
__host__ __device__ constexpr uint32_t bar_count(int i) {
    return ((i >= B_E1 && i < B_E1 + 3) || i == B_MOD || i == B_PHI || i == B_PHI + 1 || i == B_OWN || i == B_OWN + 1 || (i >= B_ED && i < B_ED + 4)
            || i == B_STFREE || i == B_X2 || i == B_OUTW) ? 8
         : (i == B_PHIFREE || i == B_PHIFREE + 1 || i == B_WD || i == B_ST2 || i == B_RD) ? 4 : (i == B_KVF || i == B_KVF + 1) ? 2 : 1;
}
template<int I0, int I1> __device__ __forceinline__ void init_barriers(uint32_t sb) {
    #pragma unroll
    for (int i = I0; i < I1; i++) mbar_init(BAR(i), bar_count(i));
}
template<int N> __device__ __forceinline__ uint32_t pop_max(uint32_t (&k)[N]) {
    uint32_t m = k[0];
    #pragma unroll
    for (int i = 1; i < N; i++) m = max(m, k[i]);
    m = __reduce_max_sync(0xffffffffu, m);
    #pragma unroll
    for (int i = 0; i < N; i++) k[i] = (k[i] == m) ? 0u : k[i];
    return m;
}
__device__ __forceinline__ void fma8(float (&a)[8], uint4 w, float s) {
    a[0] = fmaf(bf_lo(w.x), s, a[0]); a[1] = fmaf(bf_hi(w.x), s, a[1]); a[2] = fmaf(bf_lo(w.y), s, a[2]); a[3] = fmaf(bf_hi(w.y), s, a[3]);
    a[4] = fmaf(bf_lo(w.z), s, a[4]); a[5] = fmaf(bf_hi(w.z), s, a[5]); a[6] = fmaf(bf_lo(w.w), s, a[6]); a[7] = fmaf(bf_hi(w.w), s, a[7]);
}
__device__ __forceinline__ void mod_scatter(const float (&m)[8], uint32_t red, int lane) {
    const bool b4 = lane & 16, b3 = lane & 8;
    float a[4];
    #pragma unroll
    for (int i = 0; i < 4; i++) { const float keep = b4 ? m[4 + i] : m[i], send = b4 ? m[i] : m[4 + i]; a[i] = keep + shfl_x(send, 16); }
    const float k0 = b3 ? a[2] : a[0], k1 = b3 ? a[3] : a[1], s0 = b3 ? a[0] : a[2], s1 = b3 ? a[1] : a[3];
    sts64(red + (((lane & 7) >> 1) * 4 + (lane >> 3)) * 16 + (lane & 1) * 8, __float_as_uint(k0 + shfl_x(s0, 8)), __float_as_uint(k1 + shfl_x(s1, 8)));
}
__device__ __forceinline__ bool mod_collect(uint4 w0, uint4 w1, uint4 w2, uint4 w3, uint32_t sb, int jb, int lane, uint32_t tag2) {
    const uint32_t add = lane < 16 ? ONE2 : 0u;
    const uint32_t lo = pack2((__uint_as_float(w0.x) + __uint_as_float(w1.x)) + (__uint_as_float(w2.x) + __uint_as_float(w3.x)),
                              (__uint_as_float(w0.y) + __uint_as_float(w1.y)) + (__uint_as_float(w2.y) + __uint_as_float(w3.y)));
    const uint32_t hi = pack2((__uint_as_float(w0.z) + __uint_as_float(w1.z)) + (__uint_as_float(w2.z) + __uint_as_float(w3.z)),
                              (__uint_as_float(w0.w) + __uint_as_float(w1.w)) + (__uint_as_float(w2.w) + __uint_as_float(w3.w)));
    sts64(sb + OFF_MODS + jb * 256 + (lane & 15) * 16 + (lane >> 4) * 8, hadd2(lo, add), hadd2(hi, add));
    return tagged2(w0.w, tag2) && tagged2(w1.w, tag2) && tagged2(w2.w, tag2) && tagged2(w3.w, tag2);
}
__device__ __forceinline__ void phi_issue(float (&pp)[4][16], const uint32_t (&a)[32], uint32_t sb) {
    const uint64_t dw = mk_desc(sb + OFF_WPHI, 16, 512, 2);
    wg_fence();
    #pragma unroll
    for (int ks = 0; ks < 2; ks++)
        #pragma unroll
        for (int h = 0; h < 4; h++) wgmma_n32_rs<1>(pp[h], a[8 * h + 4 * ks], a[8 * h + 4 * ks + 1], a[8 * h + 4 * ks + 2], a[8 * h + 4 * ks + 3], desc_add(dw, h * 2048 + ks * 1024), ks);
    wg_commit();
}
__device__ __forceinline__ void phi_finish(float (&pp)[4][16], uint32_t (&a)[32]) {
    wg_wait<0>();
    #pragma unroll
    for (int h = 0; h < 4; h++) {
        acc_fence(pp[h]);
        #pragma unroll
        for (int i = 0; i < 8; i++) a[8 * h + i] = pack2(pp[h][2 * i], pp[h][2 * i + 1]);
    }
}

__global__ void __cluster_dims__(2, 1, 1) __launch_bounds__(NTHREADS, 1)
fused_kernel(const Ptrs p, const __grid_constant__ CUtensorMap tmW, const __grid_constant__ CUtensorMap tmWo, const __grid_constant__ CUtensorMap tmPhi,
             const __grid_constant__ CUtensorMap tmG, const __grid_constant__ CUtensorMap tmU, const __grid_constant__ CUtensorMap tmD,
             const __grid_constant__ CUtensorMap tmX, const __grid_constant__ CUtensorMap tmO, const __grid_constant__ CUtensorMap tmM,
             const __grid_constant__ CUtensorMap tmR)
{
    extern __shared__ __align__(1024) uint8_t smem_raw[];
    const uint32_t sb = smem_u32(smem_raw);
    const int tid = threadIdx.x, lane = tid & 31, warp = __shfl_sync(0xffffffffu, tid >> 5, 0);
    const int b = blockIdx.x;
    const int pr = b >> 1, rank = b & 1;
    const int cls = pr < 4 ? 15 : pr < 36 ? 2 * ((pr - 4) & 7) : 2 * ((pr - 36) % 7) + 1, mem = pr < 4 ? pr : pr < 36 ? (pr - 4) >> 3 : (pr - 36) / 7;
    const int hg = ((cls & 4) ? 3 - (cls & 3) : (cls & 3)) * 2 + rank, rb = (cls >> 2) * 4 + mem;
    const bool ffn = b < 112;
    const uint32_t cstart = clk32();

    if (warp >= 8) {
        const int t = tid & 127, w4 = warp & 3, g = lane >> 2, c = lane & 3;
        if (w4 == 0) TS(40);
        reg_dec<40>();
        if (w4 < 2) {
            if (w4 == 0) { tmap_prefetch(&tmX); tmap_prefetch(&tmW); }
            if (elect_one()) {
                if (w4 == 0) init_barriers<0, 24>(sb); else init_barriers<24, B_COUNT>(sb);
                asm volatile("fence.mbarrier_init.release.cluster;" ::: "memory");
            }
            __syncwarp();
            fence_async_smem();
            if (w4 == 1) expect_tx_e(BAR(B_PX), 1024);
        }
        if (w4 == 0) TS(42);
        bar_arrive(0, 384);
        cluster_arrive();
        bar_sync(2, 128);
        const uint32_t tag = ldg32(p.s->done) + 1, tag2 = tag % 3u + 1;
        if (w4 == 0) {
            int s = 0;
            #pragma unroll 1
            for (int j = 0; j < 16; j++) {
                if (j >= 3) mbar_wait(BAR(B_E1 + s), ((j / 3) - 1) & 1);
                else if (j == 2) mbar_wait(BAR(B_STFREE), 0);
                else while (clk32() - cstart < T_S0) {}
                if (j == S_AFTER_MOD) mbar_wait(BAR(B_MOD), 0);
                expect_tx_e(BAR(B_F1 + s), 65536);
                const uint32_t st = sb + OFF_RING + s * 65536u;
                tma4_ef_e(st + 16384u, &tmW, j * 64, hg * 2, BAR(B_F1 + s));
                tma2_e(st, &tmX, j * 64, rb * 128, BAR(B_F1 + s));
                if (j == 1) TS(50);
                s = s == 2 ? 0 : s + 1;
            }
            mbar_wait(BAR(B_MOD + 3), 0);
            expect_tx_e(BAR(B_WPHI), 8192);
            tma2_e(sb + OFF_WPHI, &tmPhi, 0, hg * 128, BAR(B_WPHI));
            mbar_wait(BAR(B_E1 + 1), 0);
            #pragma unroll 1
            for (int n = 0; n < 4; n++) {
                expect_tx_e(BAR(B_FB + n), 16384);
                tma3_ef_e(sb + OFF_DB + n * 16384u, &tmWo, d_block(hg, n) * 64, hg * 2, BAR(B_FB + n));
            }
            mbar_wait(BAR(B_E1 + 0), 1);
            expect_tx_e(BAR(B_S0), ffn ? 65536 : 32768);
            tma2_e(sb + OFF_XT, &tmX, hg * 128, rb * 128, BAR(B_S0)); tma2_e(sb + OFF_XT + 16384u, &tmX, hg * 128 + 64, rb * 128, BAR(B_S0));
            #pragma unroll 1
            for (int i = 0; i < (ffn ? 4 : 0); i++) tma2_ef_e(sb + OFF_GA + i * 8192u, &tmG, pr * 64, rank * 512 + i * 64, BAR(B_S0));
        } else if (w4 == 1) {
            int piece = PF_FIRST, jg = 1, ph = 0;
            uint32_t due = cstart + PF_START;
            #pragma unroll 1
            for (int it = 0; it < 4 * POLL_MAX && (jg < 4 || piece < PF_COUNT); it++) {
                const uint32_t now = __shfl_sync(0xffffffffu, clk32(), 0);
                bg_step(p, b, lane, piece, due, now);
                if (jg < 4 && now - cstart >= (jg < NC ? T_COL1 : T_COL2)) {
                    expect_tx_e(BAR(B_MP), 8192);
                    bulk_load_e(sb + OFF_WPHI, p.s->mp + jg * 512, 8192, BAR(B_MP));
                    mbar_wait(BAR(B_MP), ph);
                    ph ^= 1;
                    bool ok = true;
                    #pragma unroll 1
                    for (int q = 0; q < 4; q++) {
                        const uint32_t a = sb + OFF_WPHI + q * 2048 + (lane >> 4) * 1024 + (lane & 15) * 16;
                        ok &= mod_collect(lds128(a), lds128(a + 256), lds128(a + 512), lds128(a + 768), sb, jg * 4 + q, lane, tag2);
                    }
                    if (__all_sync(0xffffffffu, ok)) {
                        arrive_one(BAR(B_MOD + jg));
                        if (jg == 1) TS(51);
                        if (jg == 2) TS(5);
                        if (jg == 3) TS(8);
                        jg++;
                        continue;
                    }
                }
                __nanosleep(100);
            }
        } else {
            const int hw = w4 & 1;
            const uint32_t fb = BAR(B_RF + 2 * hw);
            float macc[8];
            if (w4 == 2) {
                if (lane < 8) stg_fill(p.s->rest + b * 8 + lane, 0);
                else if (lane < 24 && b >= 32 * NC) stg_fill(p.s->mp + b * 16 + lane - 8, 0);
            }
            bar_sync(3, 320);
            #pragma unroll 1
            for (int job = b < 32 * NC; job < 2; job++) {
                const int nr = job ? 8 : 4;
                const uint32_t buf = sb + OFF_SP + hw * 8192u;
                const CUtensorMap* tm = job ? &tmR : &tmM;
                const int c0 = job ? 2048 + b * 32 : (((b >> 2) & 1) ? 0 : 1024) + (b >> 3) * 64;
                const int row0 = job ? hw * 512 : (b & 3) * 256 + hw * 128, rows = job ? 64 : 32;
                while (clk32() - cstart < (job ? T_REST : T_WLATE)) __nanosleep(100);
                #pragma unroll
                for (int i = 0; i < 8; i++) macc[i] = 0.f;
                #pragma unroll 1
                for (int q = -2; q < nr; q++) {
                    if (q >= 0) {
                        mbar_wait(fb + (q & 1) * 8, (q >> 1) & 1);
                        const uint32_t sv0 = sb + OFF_SILU + (row0 + q * rows + (job ? lane >> 2 : lane >> 3)) * 2, svs = job ? 16 : 8;
                        const uint32_t wa = buf + (q & 1) * 4096u + lane * 16u;
                        #pragma unroll 1
                        for (int i = 0; i < 8; i += 2) {
                            const uint32_t s0 = lds16(sv0 + i * svs), s1 = lds16(sv0 + (i + 1) * svs);
                            const uint4 w = lds128(wa + i * 512u), w1 = lds128(wa + (i + 1) * 512u);
                            fma8(macc, w, bf_lo(s0)); fma8(macc, w1, bf_lo(s1));
                        }
                    }
                    __syncwarp();
                    if (q + 2 < nr) {
                        const uint32_t bar = fb + (q & 1) * 8 + (q >= 0 && __float_as_uint(macc[0]) == 0x7fc12345u) * 512;
                        expect_tx_e(bar, 4096);
                        tma2_ef_e(buf + (q & 1) * 4096u, tm, c0, row0 + (q + 2) * rows, bar);
                    }
                }
                const uint32_t red = sb + OFF_RED0 + hw * 256;
                if (job == 0) mod_scatter(macc, red, lane);
                else stsf(red + (c * 8 + g) * 4, reduce8(macc, lane));
                bar_sync(4, 64);
                if (w4 == 2) {
                    const uint4 u0 = lds128(sb + OFF_RED0 + (lane & 15) * 16), u1 = lds128(sb + OFF_RED0 + 256 + (lane & 15) * 16);
                    const float v0 = __uint_as_float(u0.x) + __uint_as_float(u1.x), v1 = __uint_as_float(u0.y) + __uint_as_float(u1.y);
                    const float v2 = __uint_as_float(u0.z) + __uint_as_float(u1.z), v3 = __uint_as_float(u0.w) + __uint_as_float(u1.w);
                    const uint32_t add = (b >> 5) == 2 ? ONE2 : 0u;
                    if (job == 0) { if (lane < 16) st_ll(p.s->mp + b * 16 + lane, __float_as_uint(v0), __float_as_uint(v1), __float_as_uint(v2), low_bits(v3, tag2)); TS(13); }
                    else { if (lane < 8) st_ll(p.s->rest + b * 8 + lane, hadd2(pack2(v0, v1), add), hadd2(pack2(v2, v3), add), 0, tag); TS(33); }
                }
                bar_sync(4, 64);
            }
            tmap_prefetch(hw ? &tmWo : &tmG); tmap_prefetch(hw ? &tmU : &tmD); tmap_prefetch(hw ? &tmPhi : &tmO);
            #pragma unroll 1
            for (int i = 0; i < 4; i++) {
                #pragma unroll 1
                for (int d = 0; d < 8; d++) stg_fill(p.s->kvp + ((hg * 64 + i * 16 + hw * 8 + d) * 16 + rb) * 32 + lane, 0);
                if (ffn) stg_fill(p.s->yp + pr * 512 + hw * 256 + rank * 128 + i * 32 + lane, 0);
                if (hw) stg_fill(p.s->rowh + (lane >> 4) * 8192 + (rb * 4 + i) * 128 + hg * 16 + (lane & 15), EMPTY);
                else if (lane < 18) stg_fill(p.s->kvf + (hg * 4 + i) * 288 + (lane < 16 ? (rb >> 2) * 64 + (rb & 3) * 8 + (lane >> 3) * 32 + (lane & 7) : 240 + rb * 2 + lane), EMPTY);
            }
            if (hw) { if (hg == 0 && lane < 8) stg_fill(p.s->cand + rb * 8 + lane, 0); }
            else if (lane < 28) stg_fill(lane < 16 ? p.s->st2 + rb * 128 + hg * 16 + lane : lane < 20 ? p.s->flo + (rb * 16 + hg * 2) * 2 + lane - 16
                                         : p.s->rsc + ((rb * 4 + ((lane - 20) >> 1)) * 8 + hg) * 2 + (lane & 1), 0);
            __threadfence();
            if (w4 == 2) TS(36);
        }
        __syncwarp();
        cluster_wait();
        bar_sync(2, 128);
        reg_inc<504 - 2 * CREG>();
        if (w4 == 0) TS(6);
        #pragma unroll 1
        for (int h = 0; h < 4; h++) {
            mbar_wait(BAR(B_PHI + (h & 1)), h >> 1);
            float o[20];
            const uint32_t vb = OFF_V + h * 8192u;
            const uint64_t dp = mk_desc(sb + OFF_PHI + (h & 1) * 16384u, 16, 1024, 1), dv = mk_desc(sb + vb, OFF_ONES - vb, 512, 2);
            wg_fence();
            #pragma unroll
            for (int ks = 0; ks < 8; ks++)
                wgmma_n40_ss<1, 1>(o, desc_add(dp, ks * 2048), desc_raw(dv, ks * (64 - (64 << 16))), ks);
            wg_commit();
            wg_wait<0>();
            acc_fence(o);
            arrive_one(BAR(B_PHIFREE + (h & 1)));
            uint4* dst = p.s->kvp + (((hg * 4 + h) * 16 + (t >> 3)) * 16 + rb) * 32 + (t & 7);
            #pragma unroll
            for (int k = 0; k < 2; k++) {
                const uint32_t z = __float_as_uint(o[16 + 2 * k]) + 0x80u;
                st_ll(dst + k * 8, low_byte<1>(o[4 * k], z), low_byte<2>(o[4 * k + 1], z), low_byte<3>(o[4 * k + 2], z), low_bits(o[4 * k + 3], tag2));
                st_ll(dst + 16 + k * 8, __float_as_uint(o[8 + 4 * k]), __float_as_uint(o[9 + 4 * k]), __float_as_uint(o[10 + 4 * k]), low_bits(o[11 + 4 * k], tag2));
            }
        }
        if (w4 == 0) TS(17);
        bar_sync(2, 128);
        {
            uint4* const fin = p.s->kvf + (hg * 4 + w4) * 288;
            {
                const uint4* src = p.s->kvp + ((hg * 4 + w4) * 16 + rb) * 512 + lane;
                uint4 w[16];
                #pragma unroll
                for (int i = 0; i < 16; i++) w[i] = make_uint4(0, 0, 0, 0);
                #pragma unroll 1
                for (int it = 0; it < POLL_MAX; it++) {
                    bool ok = true;
                    #pragma unroll
                    for (int i = 0; i < 16; i++) ld_ll_if(w[i], src + i * 32, !tagged2(w[i].w, tag2));
                    #pragma unroll
                    for (int i = 0; i < 16; i++) ok = ok && tagged2(w[i].w, tag2);
                    if (__all_sync(0xffffffffu, ok)) break;
                }
                if (w4 == 0) TS(18);
                if (w4 == 3) TS(10);
                float s[2][5];
                #pragma unroll
                for (int i = 0; i < 16; i++) {
                    const float z = __uint_as_float(__byte_perm(__byte_perm(w[i].x, w[i].y, 0x0400), w[i].z, 0x4210) & 0xffffff00u);
                    float (&a)[5] = s[i & 1];
                    if (i < 2) { a[0] = __uint_as_float(w[i].x); a[1] = __uint_as_float(w[i].y); a[2] = __uint_as_float(w[i].z); a[3] = __uint_as_float(w[i].w); a[4] = z; }
                    else { a[0] += __uint_as_float(w[i].x); a[1] += __uint_as_float(w[i].y); a[2] += __uint_as_float(w[i].z); a[3] += __uint_as_float(w[i].w); a[4] += z; }
                }
                char* d = (char*)fin + ((rb >> 2) * 16 + (rb & 3) * 2 + (g & 1)) * 64 + (((lane >> 3) ^ (rb & 3)) << 4) + c * 4;
                st_ll4(d, pack2(s[0][0] + s[1][0], s[0][1] + s[1][1]));
                st_ll4(d + 512, pack2(s[0][2] + s[1][2], s[0][3] + s[1][3]));
                if (lane < 16 && c < 2) st_ll4((char*)fin + 4096 + rb * 32 + (g * 2 + c) * 4, pack2(s[0][4] + s[1][4], 0.f));
            }
            fence_acq_gpu();
            uint4 v[9];
            #pragma unroll 1
            for (int it = 0; it < POLL_MAX; it++) {
                uint32_t m = 0;
                #pragma unroll
                for (int k = 0; k < 9; k++) v[k] = ld_ll(fin + k * 32 + lane);
                #pragma unroll
                for (int k = 0; k < 9; k++) m = max(m, umax4(v[k]));
                if (__all_sync(0xffffffffu, m != EMPTY)) break;
            }
            #pragma unroll
            for (int k = 0; k < 8; k++) sts128(sb + OFF_SP + w4 * 4096u + k * 512u + lane * 16u, v[k]);
            const uint32_t za = sb + OFF_Z + ((lane >> 3) * 16 + ((lane >> 1) & 3) * 2 + (lane & 1) * 8) * 64u + ((w4 ^ ((lane >> 1) & 3)) << 4);
            sts16(za, v[8].x); sts16(za + 64, v[8].z);
            fence_async_smem();
            __syncwarp();
            arrive_one(BAR(B_KVF + (w4 >> 1)));
            if (w4 == 0) TS(19);
            if (w4 == 3) TS(1);
        }
        if (w4 == 0) {
            const unsigned* f = (const unsigned*)(p.s->flo + (rb * 16 + d_block(hg, lane & 15)) * 2);
            uint32_t seen = 0;
            #pragma unroll 1
            for (int n = 2; n < 18; n++) {
                const uint32_t s = n & 3;
                if (n < 16 && !((seen >> n) & 1)) {
                    #pragma unroll 1
                    for (int it = 0; it < POLL_MAX && !((seen >> n) & 1); it++) seen = __ballot_sync(0xffffffffu, ld_rlx(f) == tag);
                    fence_acq_gpu();
                }
                if (n >= 4) mbar_wait(BAR(B_ED + s), ((n >> 2) - 1) & 1);
                if (n == 4 || n == 5) mbar_wait(BAR(B_PUB + s), 0);
                if (n < 16) {
                    expect_tx_e(BAR(B_FA + s), 16384);
                    bulk_load_e(sb + OFF_DA + s * 16384u, p.s->os + (rb * 16 + d_block(hg, n)) * 1024, 16384, BAR(B_FA + s));
                } else if (ffn) {
                    expect_tx_e(BAR(B_WD), 16384);
                    tma3_ef_e(sb + OFF_DA + s * 16384u, &tmD, pr * 64, rank * 8 + s * 2, BAR(B_WD));
                }
                if (n == 2) TS(2);
            }
        } else if (w4 == 1) {
            if (ffn) expect_tx_e(BAR(B_GU), 98304);
            #pragma unroll 1
            for (int n = 4; n < (ffn ? 18 : 16); n++) {
                const uint32_t s = n & 3, bar = BAR(n < 16 ? B_FB + s : B_WD);
                mbar_wait(BAR(B_ED + s), ((n >> 2) - 1) & 1);
                expect_tx_e(bar, 16384);
                tma3_ef_e(sb + OFF_DB + s * 16384u, n < 16 ? &tmWo : &tmD, n < 16 ? d_block(hg, n) * 64 : pr * 64, n < 16 ? hg * 2 : rank * 8 + 4 + s * 2, bar);
                if (ffn && n < 16) tma2_ef_e(sb + (n < 8 ? OFF_GB - 32768u : OFF_UP - 65536u) + n * 8192u, n < 8 ? &tmG : &tmU, pr * 64, rank * 512 + (n & 7) * 64, BAR(B_GU));
            }
        } else if (w4 == 2) {
            #pragma unroll 1
            for (int q = 0; q < 2; q++) {
                mbar_wait(BAR(B_OWN + q), 0);
                bulk_store_e(p.s->os + (rb * 16 + 2 * hg + q) * 1024, sb + OFF_DA + q * 16384u, 16384);
                bulk_commit();
                bulk_wait();
                arrive_one(BAR(B_PUB + q));
                fence_rel_gpu();
                st_flag_e(p.s->flo + (rb * 16 + 2 * hg + q) * 2, tag);
                if (q == 0) TS(3);
            }
        } else {
            {
                uint4 w[4];
                poll_words<4>(w, p.s->rest + hg * 32 + lane, 256, tag);
                sts128(sb + OFF_PAR + lane * 32, make_uint4(w[2].x, w[1].x, w[3].x, w[0].x));
                sts128(sb + OFF_PAR + lane * 32 + 16, make_uint4(w[2].y, w[1].y, w[3].y, w[0].y));
                const uint2 wr = ldg64(p.wr + hg * 128 + lane * 4);
                sts64(sb + OFF_BQ + lane * 8, hmul2(w[2].x, wr.x), hmul2(w[2].y, wr.y));
            }
            float s = 0.f;
            #pragma unroll 1
            for (int i = 0; i < 8; i++) {
                uint4 w[1];
                const uint2 wr = ldg64(p.wr + (lane + 32 * i) * 4);
                poll_words<1>(w, p.s->rest + 512 + i * 32 + lane, 0, tag);
                const uint32_t r0 = hmul2(w[0].x, wr.x), r1 = hmul2(w[0].y, wr.y);
                s += (bf_lo(r0) + bf_hi(r0)) + (bf_lo(r1) + bf_hi(r1));
            }
            __syncwarp();
            #pragma unroll
            for (int m = 16; m >= 1; m >>= 1) s += shfl_x(s, m);
            if (lane == 0) stsf(sb + OFF_ATOT, s);
            __syncwarp();
            arrive_one(BAR(B_PAR));
        }
        __syncwarp();
        {
            mbar_wait(BAR(B_PAR), 0);
            const uint2 pa0 = lds64(sb + OFF_PAR + lane * 32), pa1 = lds64(sb + OFF_PAR + lane * 32 + 16), wr = ldg64(p.wr + hg * 128 + lane * 4);
            const float atot = ldsf(sb + OFF_ATOT);
            mbar_wait(BAR(B_X2), 0);
            uint4 w;
            #pragma unroll 1
            for (int it = 0; it < POLL_MAX; it++) {
                w = ld_ll(p.s->st2 + rb * 128 + t);
                if (__all_sync(0xffffffffu, __uint_as_float(w.w) == 8.0f)) break;
            }
            if (w4 == 0) TS(31);
            uint32_t m2; float rinv;
            ln_final(__uint_as_float(w.x), __uint_as_float(w.y), m2, rinv);
            sts32(sb + OFF_KEYS + t * 4, (f2key(fmaf(-bf_lo(m2), atot, __uint_as_float(w.z)) * rinv) & ~127u) | (127 - t));
            sts64(sb + OFF_ST2 + t * 8, m2, __float_as_uint(rinv));
            bar_sync(2, 128);
            arrive_one(BAR(B_ST2));
            const uint4 kk = lds128(sb + OFF_KEYS + lane * 16);
            uint32_t k[4] = {kk.x, kk.y, kk.z, kk.w}, best;
            #pragma unroll 1
            for (int r = 0; r <= w4; r++) best = pop_max(k);
            const uint32_t row = 127 - (best & 127u), slot = rb * 4 + w4;
            if (hg == 0 && lane < 2) st_ll(p.s->cand + slot * 2 + lane, best, rb * 128 + row, 0, tag);
            if (w4 == 3) TS(23);
            const uint2 xv = lds64(sb + OFF_OUT + (row >> 3) * 2048u + (lane >> 4) * 1024u + (row & 7) * 128u + ((((lane >> 1) ^ row) & 7) << 4) + (lane & 1) * 8);
            const uint2 sv = lds64(sb + OFF_ST2 + row * 8);
            const uint32_t h0 = ln_pair(xv.x, sv.x, __uint_as_float(sv.y), pa0.x, pa0.y), h1 = ln_pair(xv.y, sv.x, __uint_as_float(sv.y), pa1.x, pa1.y);
            char* d = (char*)(p.s->rowh + slot * 128 + hg * 16) + lane * 8;
            st_ll8(d, h0, h1);
            st_ll8(d + 131072, xv.x, xv.y);
            __syncwarp();
            arrive_one(BAR(B_RD));
            float r = fmaf(bf_lo(h0), bf_lo(wr.x), bf_hi(h0) * bf_hi(wr.x)) + fmaf(bf_lo(h1), bf_lo(wr.y), bf_hi(h1) * bf_hi(wr.y));
            #pragma unroll
            for (int m = 16; m >= 1; m >>= 1) r += shfl_x(r, m);
            if (lane < 2) st_ll(p.s->rsc + (slot * 8 + hg) * 2 + lane, __float_as_uint(r), 0, 0, tag);
            if (w4 == 3) TS(24);
        }
        if (w4 == 0) {
            uint4 cv[2];
            poll_words<2>(cv, p.s->cand + lane * 2, 64, tag);
            __syncwarp();
            TS(11);
            uint32_t k[2] = {(cv[0].x & ~127u) | (63 - lane), (cv[1].x & ~127u) | (31 - lane)}, slot[4];
            #pragma unroll
            for (int i = 0; i < 4; i++) slot[i] = 63 - (pop_max(k) & 127u);
            const uint32_t myslot = lane < 16 ? (lane < 8 ? slot[0] : slot[1]) : (lane < 24 ? slot[2] : slot[3]);
            uint4 hv[4][2], sc;
            #pragma unroll 1
            for (int it = 0; it < POLL_MAX; it++) {
                sc = ld_ll(p.s->rsc + (myslot * 8 + (lane & 7)) * 2);
                uint32_t m = 0;
                #pragma unroll
                for (int i = 0; i < 4; i++) { hv[i][0] = ld_ll(p.s->rowh + slot[i] * 128 + rank * 64 + lane); hv[i][1] = ld_ll(p.s->rowh + slot[i] * 128 + rank * 64 + 32 + lane); }
                #pragma unroll
                for (int i = 0; i < 4; i++) m = max(m, max(max(hv[i][0].x, hv[i][0].z), max(hv[i][1].x, hv[i][1].z)));
                if (__all_sync(0xffffffffu, m != EMPTY && sc.w == tag)) break;
            }
            TS(12);
            const uint32_t r0 = __shfl_sync(0xffffffffu, cv[0].y, myslot & 31), r1 = __shfl_sync(0xffffffffu, cv[1].y, myslot & 31), row = myslot < 32 ? r0 : r1;
            float r = __uint_as_float(sc.x);
            r += shfl_x(r, 1); r += shfl_x(r, 2); r += shfl_x(r, 4);
            r = rbf(r);
            const uint32_t key = (f2key(r) & 0xffff0000u) | (0xffffu - row);
            uint32_t kq[1] = {key};
            const uint32_t best0 = pop_max(kq), best1 = pop_max(kq);
            const uint32_t m0 = __ballot_sync(0xffffffffu, key == best0), m1 = __ballot_sync(0xffffffffu, key == best1);
            #pragma unroll
            for (int i = 0; i < 4; i++)
                if (((m0 | m1) >> (8 * i)) & 1) {
                    const uint32_t a = sb + OFF_ROWS + ((m1 >> (8 * i)) & 1) * 1040u + lane * 16u;
                    sts128(a, hv[i][0]); sts128(a + 512, hv[i][1]);
                }
            if (key == best0 || key == best1) sts128(sb + OFF_SEL + (key == best1) * 16, make_uint4(row, myslot, __float_as_uint(r), 0));
            __syncwarp();
            arrive_one(BAR(B_ROWS));
            TS(25);
        } else if (w4 == 1) {
            mbar_wait(BAR(B_ROWS), 0);
            const uint4 sel = lds128(sb + OFF_SEL + rank * 16);
            const int col = pr * 16 + c * 2 + (lane >> 4) + (lane & 8);
            uint32_t xs, hs; uint4 gw;
            #pragma unroll 1
            for (int it = 0; it < POLL_MAX; it++) {
                const char* a = (const char*)(p.s->rowh + sel.y * 128) + (col >> 1) * 4;
                hs = ld_rlx(a); xs = ld_rlx(a + 131072); gw = ld_ll(p.s->rest + 768 + (col >> 2));
                if (hs != EMPTY && xs != EMPTY && gw.w == tag) break;
            }
            const uint32_t gq = (col & 2) ? gw.y : gw.x;
            const float fx = (col & 1) ? bf_hi(xs) : bf_lo(xs), fh = (col & 1) ? bf_hi(hs) : bf_lo(hs), fg = (col & 1) ? bf_hi(gq) : bf_lo(gq);
            const float sg = rbf(sigmoidf(__uint_as_float(sel.z)));
            const uint4* src = p.s->yp + g * 512 + rank * 256 + pr * 4 + c;
            uint4 w[7];
            #pragma unroll
            for (int i = 0; i < 7; i++) w[i] = make_uint4(0, 0, 0, 0);
            if (ffn) mbar_wait(BAR(B_PX), 0);
            #pragma unroll 1
            for (int it = 0; it < POLL_MAX; it++) {
                bool ok = true;
                #pragma unroll
                for (int i = 0; i < 7; i++) ld_ll_if(w[i], src + i * 4096, !(tagged2(w[i].y, tag2) && tagged2(w[i].w, tag2)));
                #pragma unroll
                for (int i = 0; i < 7; i++) ok = ok && tagged2(w[i].y, tag2) && tagged2(w[i].w, tag2);
                if (__all_sync(0xffffffffu, ok)) break;
            }
            TS(29);
            float y0 = 0.f, y1 = 0.f, y2 = 0.f, y3 = 0.f;
            #pragma unroll
            for (int i = 0; i < 7; i++) { y0 += __uint_as_float(w[i].x); y1 += __uint_as_float(w[i].y); y2 += __uint_as_float(w[i].z); y3 += __uint_as_float(w[i].w); }
            const bool b4 = lane & 16, b3 = lane & 8;
            const float a0 = (b4 ? y2 : y0) + shfl_x(b4 ? y0 : y2, 16), a1 = (b4 ? y3 : y1) + shfl_x(b4 ? y1 : y3, 16);
            float y = (b3 ? a1 : a0) + shfl_x(b3 ? a0 : a1, 8);
            y += shfl_x(y, 4);
            const float upd = rbf(rbf(y) * sg);
            if (!(lane & 4)) p.out[(size_t)sel.x * 1024 + col] = __float2bfloat16(fx + rbf(fg * rbf(fh + upd)));
            if (b == 0 && lane == 0) p.s->done[0] = tag;
            TS(28);
        } else if (w4 == 2) {
            mbar_wait(BAR(B_ROWS), 0);
            const uint32_t row0 = lds32(sb + OFF_SEL) - rb * 128, row1 = lds32(sb + OFF_SEL + 16) - rb * 128;
            mbar_wait(BAR(B_OUTW), 0);
            #pragma unroll 1
            for (uint32_t i = 0; i < 16; i++) {
                if ((row0 >> 3) != i && (row1 >> 3) != i) {
                    asm volatile(EL "cp.async.bulk.tensor.3d.global.shared::cta.bulk_group [%0, {0, %2, %3}], [%1];\n}"
                        :: "l"(&tmO), "r"(sb + OFF_OUT + i * 2048u), "r"(rb * 128 + i * 8), "r"(hg * 2) : "memory");
                } else {
                    #pragma unroll 1
                    for (uint32_t q = 0; q < 4; q++) {
                        const uint32_t r = q * 2 + (lane >> 4), ch = lane & 15;
                        const uint4 v = lds128(sb + OFF_OUT + i * 2048u + (ch >> 3) * 1024u + r * 128u + (((ch ^ r) & 7) << 4));
                        if (i * 8 + r != row0 && i * 8 + r != row1) stg128(p.out + (size_t)(rb * 128 + i * 8 + r) * 1024 + hg * 128 + ch * 8, v);
                    }
                }
            }
            bulk_commit();
            bulk_wait();
            TS(35);
        }
    } else {
        const int w4 = warp & 3, wgi = warp >> 2, g = lane >> 2, c = lane & 3;
        uint32_t m2[2]; float rinv[2];
        uint32_t tag2;
        {
            const int xrow = b * 16 + warp * 2;
            mbar_init_e(BAR(B_XS + warp), 1); mbar_init_e(BAR(B_WS + warp), 1);
            fence_async_smem();
            expect_tx_e(BAR(B_XS + warp), 4096);
            bulk_load_e(sb + OFF_XS + warp * 4096u, p.x + (size_t)xrow * 1024, 4096, BAR(B_XS + warp));
            if (warp == 0) TS(43);
            const uint2 cv = ldg64(p.c + tid * 4);
            const uint32_t tag = ldg32(p.s->done) + 1;
            if (b < 32 * NC) {
                while (b >= 32 && clk32() - cstart < T_W1) {}
                expect_tx_e(BAR(B_WS + warp), 4096);
                tma2_ef_e(sb + OFF_WST + warp * 4096u, &tmM, (((b >> 2) & 1) ? 0 : 1024) + (b >> 3) * 64, (b & 3) * 256 + warp * 32, BAR(B_WS + warp));
            }
            if (lane < 2) stg_fill(p.s->st1 + xrow + lane, 0);
            if (warp == 0 && lane < 16 && b < 32 * NC) stg_fill(p.s->mp + b * 16 + lane, 0);
            if (tid < 64) { int s = tid >> 2; sts128(sb + OFF_ONES + tid * 16, make_uint4(((tid & 3) == ((s >> 1) & 3)) ? 0x3F80u : 0u, 0, 0, 0)); }
            cluster_arrive();
            reg_inc<232>();
            {
                const float c0 = bf_lo(cv.x), c1 = bf_hi(cv.x), c2 = bf_lo(cv.y), c3 = bf_hi(cv.y);
                sts64(sb + OFF_SILU + tid * 8, pack2(c0 * sigmoidf(c0), c1 * sigmoidf(c1)), pack2(c2 * sigmoidf(c2), c3 * sigmoidf(c3)));
            }
            tag2 = tag % 3u + 1;
            bar_arrive(3, 320);
            bar_sync(0, 384);
            if (warp == 0) TS(47);
            {
                float s[2], q[2];
                mbar_wait(BAR(B_XS + warp), 0);
                #pragma unroll
                for (int r = 0; r < 2; r++) s[r] = q[r] = 0.f;
                #pragma unroll 1
                for (int i = 0; i < 4; i++) {
                    #pragma unroll
                    for (int r = 0; r < 2; r++) {
                        const uint4 xv = lds128(sb + OFF_XS + warp * 4096u + r * 2048u + (i * 32 + lane) * 16u);
                        const uint32_t u[4] = {xv.x, xv.y, xv.z, xv.w};
                        float s0 = 0.f, q0 = 0.f;
                        #pragma unroll
                        for (int e = 0; e < 4; e++) {
                            const float lo = bf_lo(u[e]), hi = bf_hi(u[e]);
                            s0 += lo; s[r] += hi; q0 = fmaf(lo, lo, q0); q[r] = fmaf(hi, hi, q[r]);
                        }
                        s[r] += s0; q[r] += q0;
                    }
                }
                if (warp == 0) TS(30);
                float sk = (lane & 16) ? s[1] : s[0], qk = (lane & 16) ? q[1] : q[0];
                sk += shfl_x((lane & 16) ? s[0] : s[1], 16); qk += shfl_x((lane & 16) ? q[0] : q[1], 16);
                #pragma unroll
                for (int m = 8; m >= 1; m >>= 1) { sk += shfl_x(sk, m); qk += shfl_x(qk, m); }
                uint32_t mm; float ri;
                ln_final(sk, qk, mm, ri);
                if (!(lane & 15)) st_ll(p.s->st1 + xrow + (lane >> 4), mm, __float_as_uint(ri), 0, tag);
                if (warp == 0) TS(14);
            }
            if (b < 32 * NC) {
                float macc[8];
                #pragma unroll
                for (int i = 0; i < 8; i++) macc[i] = 0.f;
                mbar_wait(BAR(B_WS + warp), 0);
                #pragma unroll 2
                for (int i = 0; i < 8; i++)
                    fma8(macc, lds128(sb + OFF_WST + warp * 4096u + i * 512u + lane * 16u), bf_lo(lds16(sb + OFF_SILU + ((b & 3) * 256 + warp * 32 + i * 4 + (lane >> 3)) * 2)));
                if (warp == 0) TS(46);
                mod_scatter(macc, sb + OFF_RED0 + warp * 256, lane);
                if (warp != 7) bar_arrive(5, 256);
                else {
                    bar_sync(5, 256);
                    float v0 = 0.f, v1 = 0.f, v2 = 0.f, v3 = 0.f;
                    #pragma unroll
                    for (int w = 0; w < 4; w++) {
                        const uint4 u = lds128(sb + OFF_RED0 + w * 512 + lane * 16);
                        v0 += __uint_as_float(u.x); v1 += __uint_as_float(u.y); v2 += __uint_as_float(u.z); v3 += __uint_as_float(u.w);
                    }
                    v0 += shfl_x(v0, 16); v1 += shfl_x(v1, 16); v2 += shfl_x(v2, 16); v3 += shfl_x(v3, 16);
                    if (lane < 16) st_ll(p.s->mp + b * 16 + lane, __float_as_uint(v0), __float_as_uint(v1), __float_as_uint(v2), low_bits(v3, tag2));
                    TS(45);
                }
            }
            arrive_one(BAR(B_STFREE));
            cluster_wait();
            {
                const uint4* st_src = p.s->st1 + rb * 128 + warp * 16 + g;
                uint4 st0, st1;
                #pragma unroll 1
                for (int it = 0; it < POLL_MAX; it++) {
                    st0 = ld_ll(st_src); st1 = ld_ll(st_src + 8);
                    bool ok = true;
                    if (warp < 4) {
                        const uint4* src = p.s->mp + (warp * 8 + (lane >> 4) * 4) * 16 + (lane & 15);
                        const uint4 w0 = ld_ll(src), w1 = ld_ll(src + 16), w2 = ld_ll(src + 32), w3 = ld_ll(src + 48);
                        ok = mod_collect(w0, w1, w2, w3, sb, warp, lane, tag2);
                    }
                    if (__all_sync(0xffffffffu, ok && st0.w == tag && st1.w == tag)) break;
                }
                m2[0] = st0.x; rinv[0] = __uint_as_float(st0.y); m2[1] = st1.x; rinv[1] = __uint_as_float(st1.y);
            }
            if (warp == 0) TS(4);
            arrive_one(BAR(B_MOD));
        }
        const int srow = warp * 16 + (lane & 15);
        const uint32_t aoff = srow * 128u + ((((lane >> 4) ^ srow) & 7) << 4);
        uint32_t pk[32], qf[32];
        {
            float accKV[128], accQ[64];
            {
                uint32_t f[2][4], r[4];
                mbar_wait(BAR(B_F1), 0);
                ldsm4(r[0], r[1], r[2], r[3], sb + OFF_RING + aoff);
                mbar_wait(BAR(B_MOD), 0);
                if (warp == 0) TS(15);
                uint4 md = lds128(sb + OFF_MODS + c * 16);
                int s = 0, sp = 2, par = 0;
                #pragma unroll 1
                for (int j = 0; j < 16; j++) {
                    const int sn = s == 2 ? 0 : s + 1;
                    par ^= s == 2;
                    const uint64_t db = mk_desc(sb + OFF_RING + s * 65536u + 16384u, 8192, 1024, 1);
                    #pragma unroll
                    for (int ks = 0; ks < 4; ks++) {
                        uint32_t (&ff)[4] = f[ks & 1];
                        ff[0] = ln_pair(r[0], m2[0], rinv[0], md.x, md.z); ff[1] = ln_pair(r[1], m2[1], rinv[1], md.x, md.z);
                        ff[2] = ln_pair(r[2], m2[0], rinv[0], md.y, md.w); ff[3] = ln_pair(r[3], m2[1], rinv[1], md.y, md.w);
                        const int kn = (ks + 1) & 3;
                        ldsm4(r[0], r[1], r[2], r[3], sb + OFF_RING + (ks == 3 ? sn : s) * 65536u + (aoff ^ (kn << 5)));
                        md = lds128(sb + OFF_MODS + ((ks == 3 ? j + 1 : j) * 4 + kn) * 64 + c * 16);
                        wg_fence();
                        wgmma_n256_rs<1>(accKV, ff[0], ff[1], ff[2], ff[3], desc_add(db, 16384 + ks * 2048), ks ? 1 : j);
                        wgmma_n128_rs<1>(accQ, ff[0], ff[1], ff[2], ff[3], desc_add(db, ks * 2048), ks ? 1 : j);
                        wg_commit();
                        wg_wait<1>();
                        if (ks == 0) arrive_if(BAR(B_E1 + sp), j);
                        if (ks == 2) {
                            WT0();
                            mbar_wait(BAR(B_MOD + (j < 15 ? (j + 1) >> 2 : 3)), 0);
                            mbar_wait(BAR(j < 15 ? B_F1 + sn : B_WPHI), j < 15 ? par : 0);
                        }
                    }
                    sp = s; s = sn;
                }
            }
            mbar_wait(BAR(B_E1 + 2), 0);
            wg_wait<0>();
            acc_fence(accKV); acc_fence(accQ);
            arrive_one(BAR(B_E1));
            if (warp == 0) TS(16);
            #pragma unroll
            for (int h = 0; h < 4; h++)
                #pragma unroll
                for (int q = 0; q < 2; q++) {
                    const int o = 64 + 16 * h + 8 * q;
                    stsm4(sb + OFF_V + h * 8192u + srow * 64u + (((2 * q + (lane >> 4)) ^ ((srow >> 1) & 3)) << 4),
                          pack2(accKV[o], accKV[o + 1]), pack2(accKV[o + 2], accKV[o + 3]), pack2(accKV[o + 4], accKV[o + 5]), pack2(accKV[o + 6], accKV[o + 7]));
                }
            #pragma unroll
            for (int i = 0; i < 32; i++) pk[i] = pack2(accKV[2 * i], accKV[2 * i + 1]);
            float pp[4][16];
            phi_issue(pp, pk, sb);
            #pragma unroll
            for (int i = 0; i < 32; i++) qf[i] = pack2(accQ[2 * i], accQ[2 * i + 1]);
            phi_finish(pp, pk);
        }
        reg_dec<CREG>();
        if (warp == 0) TS(56);
        uint32_t ph[64];
        #pragma unroll 1
        for (int u = 0; ; u++) {
            FmState fs; float ea[16], eb[16];
            fm_slot<false, false, true>(fs, ea, ph, pk, ea, pk);
            fm_slot<false, true, true>(fs, eb, ph, pk, ea, pk + 1);
            #pragma unroll
            for (int h = 0; h < 4; h++) {
                if (h < 3) {
                    fm_slot<true, true, true>(fs, ea, ph + 16 * h, pk + 8 * h + 1, eb, pk + 8 * h + 8);
                    fm_slot<true, true, true>(fs, eb, ph + 16 * h + 1, pk + 8 * h + 8, ea, pk + 8 * h + 9);
                } else {
                    fm_slot<true, true, false>(fs, ea, ph + 16 * h, pk + 8 * h + 1, eb, pk);
                    fm_slot<true, false, false>(fs, eb, ph + 16 * h + 1, pk, ea, pk);
                }
                if (u == 0) {
                    if (h >= 2) mbar_wait(BAR(B_PHIFREE + (h & 1)), 0);
                    #pragma unroll
                    for (int q = 0; q < 4; q++)
                        stsm4(sb + OFF_PHI + (h & 1) * 16384u + (aoff ^ (q << 5)), ph[16 * h + 4 * q], ph[16 * h + 4 * q + 1], ph[16 * h + 4 * q + 2], ph[16 * h + 4 * q + 3]);
                    fence_async_smem();
                    __syncwarp();
                    arrive_one(BAR(B_PHI + (h & 1)));
                    if (warp == 0 && h == 0) TS(58);
                    if (warp == 0 && h == 1) TS(52);
                    if (warp == 0 && h == 3) TS(59);
                }
            }
            if (u) break;
            float pp[4][16];
            phi_issue(pp, qf, sb);
            phi_finish(pp, pk);
            if (warp == 0) TS(62);
        }
        if (warp == 0) TS(57);
        uint32_t x2[16][2], gf[64];
        const uint32_t woff = lane * 128u + (((warp ^ lane) & 7) << 4);
        mbar_wait(BAR(B_S0), 0);
        #pragma unroll
        for (int q = 0; q < 8; q++) {
            ldsm4(x2[2 * q][0], x2[2 * q][1], x2[2 * q + 1][0], x2[2 * q + 1][1], sb + OFF_XT + (q >> 2) * 16384u + (aoff ^ ((q & 3) << 5)));
            ldsm4t(gf[4 * q], gf[4 * q + 1], gf[4 * q + 2], gf[4 * q + 3], sb + OFF_GA + q * 4096u + woff);
        }
        #pragma unroll 1
        for (int pp = 0; pp < 2; pp++) {
            float o0[20], o1[20];
            const uint64_t dk = mk_desc(sb + OFF_SP + pp * 8192u, OFF_Z - OFF_SP - pp * 8160u, 512, 2);
            mbar_wait(BAR(B_KVF + pp), 0);
            wg_fence();
            #pragma unroll
            for (int ks = 0; ks < 4; ks++) {
                wgmma_n40_rs<1>(o0, ph[4 * ks], ph[4 * ks + 1], ph[4 * ks + 2], ph[4 * ks + 3], desc_add(dk, ks * 1024), ks);
                wgmma_n40_rs<1>(o1, ph[16 + 4 * ks], ph[17 + 4 * ks], ph[18 + 4 * ks], ph[19 + 4 * ks], desc_raw(dk, 256 + ks * 64 - (255 << 16)), ks);
            }
            wg_commit();
            wg_wait<0>();
            acc_fence(o0); acc_fence(o1);
            #pragma unroll
            for (int i = 0; i < 32; i++) ph[i] = ph[32 + i];
            #pragma unroll
            for (int hh = 0; hh < 2; hh++) {
                const float (&o)[20] = hh ? o1 : o0;
                const float rd0 = rcp(rbf(rbf(__shfl_sync(0xffffffffu, o[16], lane & ~3)) + 1e-6f));
                const float rd1 = rcp(rbf(rbf(__shfl_sync(0xffffffffu, o[18], lane & ~3)) + 1e-6f));
                uint32_t op[8];
                #pragma unroll
                for (int j = 0; j < 4; j++) {
                    uint32_t n0 = pack2(o[4 * j], o[4 * j + 1]), n1 = pack2(o[4 * j + 2], o[4 * j + 3]);
                    op[2 * j] = pack2(bf_lo(n0) * rd0, bf_hi(n0) * rd0);
                    op[2 * j + 1] = pack2(bf_lo(n1) * rd1, bf_hi(n1) * rd1);
                }
                #pragma unroll
                for (int q = 0; q < 2; q++) stsm4(sb + OFF_DA + pp * 16384u + (aoff ^ ((2 * hh + q) << 5)), op[4 * q], op[4 * q + 1], op[4 * q + 2], op[4 * q + 3]);
            }
            fence_async_smem();
            __syncwarp();
            arrive_one(BAR(B_OWN + pp));
            if (warp == 0) TS(20 + pp);
        }
        const uint32_t ooff = sb + OFF_OUT + (srow >> 3) * 1024u + aoff;
        {
            float acc[64];
            const uint64_t da0 = mk_desc(sb + OFF_DA + wgi * 8192u, 16, 1024, 1), db0 = mk_desc(sb + OFF_DB, 8192, 1024, 1);
            #pragma unroll 1
            for (int n = 0; n < 16; n++) {
                const int s = n & 3;
                WT0();
                mbar_wait(BAR(B_FB + s), (n >> 2) & 1);
                WTJ(16 + n);
                mbar_wait(BAR(n < 2 ? B_OWN + n : B_FA + s), n < 2 ? 0 : ((n >> 2) - (s < 2)) & 1);
                WTJ(n);
                const uint64_t da = desc_add(da0, s * 16384u), db = desc_add(db0, s * 16384u);
                wg_fence();
                #pragma unroll
                for (int ks = 0; ks < 4; ks++) wgmma_n128_ss<0, 1>(acc, desc_add(da, ks * 32), desc_add(db, ks * 2048), ks ? 1 : n);
                wg_commit();
                wg_wait<1>();
                arrive_if(BAR(B_ED + ((n - 1) & 3)), n);
            }
            mbar_wait(BAR(B_PAR), 0);
            uint32_t gar[16], bfr[16];
            #pragma unroll
            for (int j = 0; j < 16; j++) {
                gar[j] = lds32(sb + OFF_PAR + j * 64 + c * 16 + 12);
                const uint32_t bq = lds32(sb + OFF_BQ + j * 16 + c * 4);
                bfr[j] = (g & 1) ? bq : ONE2;
            }
            wg_wait<0>();
            acc_fence(acc);
            arrive_one(BAR(B_ED + 3));
            if (warp == 0) TS(9);
            float sd[2][4], q1[2][4], q2[2][4];
            #pragma unroll
            for (int e = 0; e < 4; e++) { sd[0][e] = sd[1][e] = q1[0][e] = q1[1][e] = q2[0][e] = q2[1][e] = 0.f; }
            #pragma unroll
            for (int s = 0; s < 8; s++) {
                #pragma unroll
                for (int e = 0; e < 4; e++) { const int j = 2 * s + (e >> 1), h = e & 1; x2[j][h] = hadd2(x2[j][h], hmul2(gar[j], pack2(acc[4 * j + 2 * h], acc[4 * j + 2 * h + 1]))); }
                mma16816(sd[s & 1], x2[2 * s][0], x2[2 * s][1], x2[2 * s + 1][0], x2[2 * s + 1][1], bfr[2 * s], bfr[2 * s + 1]);
                mma16816(q1[s & 1], x2[2 * s][0], x2[2 * s][1], x2[2 * s + 1][0], x2[2 * s + 1][1], x2[2 * s][0], x2[2 * s + 1][0]);
                mma16816(q2[s & 1], x2[2 * s][0], x2[2 * s][1], x2[2 * s + 1][0], x2[2 * s + 1][1], x2[2 * s][1], x2[2 * s + 1][1]);
            }
            if (c == (g >> 1)) {
                uint4* d = p.s->st2 + rb * 128 + warp * 16 + g;
                red_add4(d, sd[0][0] + sd[1][0], (g & 1) ? q1[0][1] + q1[1][1] : q1[0][0] + q1[1][0], sd[0][1] + sd[1][1], 1.0f);
                red_add4(d + 8, sd[0][2] + sd[1][2], (g & 1) ? q2[0][3] + q2[1][3] : q2[0][2] + q2[1][2], sd[0][3] + sd[1][3], 1.0f);
            }
            if (warp == 0) TS(22);
            mbar_wait(BAR(B_ED + 3), 1);
            #pragma unroll
            for (int q = 0; q < 8; q++) stsm4((ooff + (q >> 2) * 1024u) ^ ((q & 3) << 5), x2[2 * q][0], x2[2 * q][1], x2[2 * q + 1][0], x2[2 * q + 1][1]);
            __syncwarp();
            arrive_one(BAR(B_X2));
        }
        if (ffn) {
            mbar_wait(BAR(B_GU), 0);
            #pragma unroll
            for (int q = 8; q < 16; q++) ldsm4t(gf[4 * q], gf[4 * q + 1], gf[4 * q + 2], gf[4 * q + 3], sb + OFF_GB + (q - 8) * 4096u + woff);
        }
        {
            mbar_wait(BAR(B_ST2), 0);
            const uint2 s0 = lds64(sb + OFF_ST2 + (warp * 16 + g) * 8), s1 = lds64(sb + OFF_ST2 + (warp * 16 + g + 8) * 8);
            #pragma unroll
            for (int j = 0; j < 16; j++) {
                const uint4 pa = lds128(sb + OFF_PAR + j * 64 + c * 16);
                x2[j][0] = hadd2(x2[j][0], hmul2(pa.z, ln_pair(x2[j][0], s0.x, __uint_as_float(s0.y), pa.x, pa.y)));
                x2[j][1] = hadd2(x2[j][1], hmul2(pa.z, ln_pair(x2[j][1], s1.x, __uint_as_float(s1.y), pa.x, pa.y)));
            }
            mbar_wait(BAR(B_RD), 0);
            #pragma unroll
            for (int q = 0; q < 8; q++) stsm4((ooff + (q >> 2) * 1024u) ^ ((q & 3) << 5), x2[2 * q][0], x2[2 * q][1], x2[2 * q + 1][0], x2[2 * q + 1][1]);
            fence_async_smem();
            __syncwarp();
            arrive_one(BAR(B_OUTW));
            if (warp == 0) TS(32);
        }
        if (ffn) {
            float acc[4][4];
            {
                uint32_t uf[64];
                #pragma unroll
                for (int q = 0; q < 16; q++) ldsm4t(uf[4 * q], uf[4 * q + 1], uf[4 * q + 2], uf[4 * q + 3], sb + OFF_UP + q * 4096u + woff);
                #pragma unroll
                for (int i = 0; i < 4; i++) { acc[i][0] = acc[i][1] = acc[i][2] = acc[i][3] = 0.f; }
                mbar_wait(BAR(B_WD), 0);
                mbar_wait(BAR(B_ROWS), 0);
                #pragma unroll
                for (int q = 0; q < 16; q++) {
                    uint32_t b0, b1, b2, b3;
                    ldsm4(b0, b1, b2, b3, sb + OFF_ROWS + (lane & 1) * 1040u + (lane >> 3) * 16u + q * 64u);
                    mma16816(acc[(2 * q) & 3], gf[4 * q], uf[4 * q], gf[4 * q + 1], uf[4 * q + 1], b0, b1);
                    mma16816(acc[(2 * q + 1) & 3], gf[4 * q + 2], uf[4 * q + 2], gf[4 * q + 3], uf[4 * q + 3], b2, b3);
                }
            }
            float s[4];
            #pragma unroll
            for (int e = 0; e < 4; e++) s[e] = (acc[0][e] + acc[1][e]) + (acc[2][e] + acc[3][e]);
            const uint32_t pxa = sb + OFF_PX + (warp * 8 + g) * 16u;
            if (c == 0) st_partner128(pxa, BAR(B_PX), rank ^ 1, s[0], s[1], s[2], s[3]);
            if (warp == 0) TS(34);
            uint32_t df[4][4][4];
            {
                const uint32_t da = sb + (wgi ? OFF_DB : OFF_DA) + w4 * 8192u + ((lane & 7) + ((lane >> 4) << 3)) * 128u;
                #pragma unroll
                for (int tt = 0; tt < 4; tt++)
                    #pragma unroll
                    for (int ks = 0; ks < 4; ks++)
                        ldsm4t(df[tt][ks][0], df[tt][ks][1], df[tt][ks][2], df[tt][ks][3], da + ks * 2048u + (((2 * tt + ((lane >> 3) & 1)) ^ (lane & 7)) << 4));
            }
            mbar_wait(BAR(B_PX), 0);
            {
                const uint4 q = lds128(pxa);
                float gt = rbf((c & 1) ? s[1] + __uint_as_float(q.y) : s[0] + __uint_as_float(q.x));
                const float us = rbf((c & 1) ? s[3] + __uint_as_float(q.w) : s[2] + __uint_as_float(q.z));
                gt = rbf(gt * sigmoidf(gt));
                if (c < 2) sts16(sb + OFF_HID + c * 144 + (warp * 8 + g) * 2, pack2(gt * us, 0.f));
            }
            if (warp == 0) TS(26);
            bar_sync(1, 256);
            uint32_t bh[8];
            ldsm4(bh[0], bh[1], bh[2], bh[3], sb + OFF_HID + (lane & 1) * 144u + (lane >> 3) * 16u);
            ldsm4(bh[4], bh[5], bh[6], bh[7], sb + OFF_HID + (lane & 1) * 144u + (lane >> 3) * 16u + 64u);
            float y[4][4];
            #pragma unroll
            for (int tt = 0; tt < 4; tt++) { y[tt][0] = y[tt][1] = y[tt][2] = y[tt][3] = 0.f; }
            #pragma unroll
            for (int ks = 0; ks < 4; ks++)
                #pragma unroll
                for (int tt = 0; tt < 4; tt++) mma16816(y[tt], df[tt][ks][0], df[tt][ks][1], df[tt][ks][2], df[tt][ks][3], bh[2 * ks], bh[2 * ks + 1]);
            float e[4];
            #pragma unroll
            for (int i = 0; i < 4; i++) e[i] = (c & 2) ? ((c & 1) ? y[3][i] : y[2][i]) : ((c & 1) ? y[1][i] : y[0][i]);
            char* d = (char*)(p.s->yp + pr * 512 + rank * 128 + (warp * 4 + c) * 4) + g * 8;
            st_ll8(d, __float_as_uint(e[0]), low_bits(e[2], tag2));
            st_ll8(d + 4096, __float_as_uint(e[1]), low_bits(e[3], tag2));
            if (warp == 0) TS(27);
        }
    }
}

typedef CUresult (*EncodeFn)(CUtensorMap*, CUtensorMapDataType, cuuint32_t, void*, const cuuint64_t*, const cuuint64_t*, const cuuint32_t*,
                             const cuuint32_t*, CUtensorMapInterleave, CUtensorMapSwizzle, CUtensorMapL2promotion, CUtensorMapFloatOOBfill);

CUtensorMap make_map(EncodeFn enc, const void* ptr, uint64_t cols, uint64_t rows, uint32_t bc, uint32_t br, CUtensorMapSwizzle swz, CUtensorMapL2promotion promo) {
    CUtensorMap m;
    cuuint64_t dims[2] = {cols, rows}, strides[1] = {cols * 2};
    cuuint32_t box[2] = {bc, br}, es[2] = {1, 1};
    enc(&m, CU_TENSOR_MAP_DATA_TYPE_BFLOAT16, 2, const_cast<void*>(ptr), dims, strides, box, es, CU_TENSOR_MAP_INTERLEAVE_NONE, swz, promo,
        CU_TENSOR_MAP_FLOAT_OOB_FILL_NONE);
    return m;
}
CUtensorMap make_block_map(EncodeFn enc, const void* ptr, uint32_t sections, uint64_t rows, uint32_t br, CUtensorMapL2promotion promo) {
    CUtensorMap m;
    cuuint64_t dims[4] = {64, rows, 16, sections}, strides[3] = {sections * 2048ull, 128, 2048};
    cuuint32_t box[4] = {64, br, 2, sections}, es[4] = {1, 1, 1, 1};
    enc(&m, CU_TENSOR_MAP_DATA_TYPE_BFLOAT16, sections > 1 ? 4 : 3, const_cast<void*>(ptr), dims, strides, box, es, CU_TENSOR_MAP_INTERLEAVE_NONE,
        CU_TENSOR_MAP_SWIZZLE_128B, promo, CU_TENSOR_MAP_FLOAT_OOB_FILL_NONE);
    return m;
}

}

extern "C" void kernel_launch(void* const* d_in, const int* in_sizes, int n_in, void* d_out, int out_size) {
    (void)in_sizes; (void)n_in; (void)out_size;
    void* fn = nullptr; cudaDriverEntryPointQueryResult qr;
    cudaGetDriverEntryPoint("cuTensorMapEncodeTiled", &fn, cudaEnableDefault, &qr);
    EncodeFn enc = (EncodeFn)fn;
    void* hs = nullptr;
    cudaGetSymbolAddress(&hs, g_scratch);
    const CUtensorMapL2promotion P256 = CU_TENSOR_MAP_L2_PROMOTION_L2_256B, P128 = CU_TENSOR_MAP_L2_PROMOTION_L2_128B;
    CUtensorMap tmW = make_block_map(enc, d_in[1], 3, 1024, 64, P256);
    CUtensorMap tmWo = make_block_map(enc, d_in[3], 1, 1024, 64, P256);
    CUtensorMap tmPhi = make_map(enc, d_in[2], 32, 1024, 32, 128, CU_TENSOR_MAP_SWIZZLE_64B, P128);
    CUtensorMap tmG = make_map(enc, d_in[6], 3584, 1024, 64, 64, CU_TENSOR_MAP_SWIZZLE_128B, P128);
    CUtensorMap tmU = make_map(enc, d_in[7], 3584, 1024, 64, 64, CU_TENSOR_MAP_SWIZZLE_128B, P128);
    CUtensorMap tmD = make_block_map(enc, d_in[8], 1, 3584, 64, P128);
    CUtensorMap tmX = make_map(enc, d_in[0], 1024, 2048, 64, 128, CU_TENSOR_MAP_SWIZZLE_128B, P128);
    CUtensorMap tmO = make_block_map(enc, d_out, 1, 2048, 8, P128);
    CUtensorMap tmM = make_map(enc, d_in[10], 6144, 1024, 64, 32, CU_TENSOR_MAP_SWIZZLE_NONE, P128);
    CUtensorMap tmR = make_map(enc, d_in[10], 6144, 1024, 32, 64, CU_TENSOR_MAP_SWIZZLE_NONE, P128);
    Ptrs p;
    p.x = (const bf16*)d_in[0]; p.c = (const bf16*)d_in[9]; p.wmod = (const bf16*)d_in[10]; p.wr = (const bf16*)d_in[5];
    p.wg = (const bf16*)d_in[6]; p.wu = (const bf16*)d_in[7]; p.wd = (const bf16*)d_in[8]; p.out = (bf16*)d_out; p.s = (Scratch*)hs;
    p.wqkv = (const bf16*)d_in[1]; p.wo = (const bf16*)d_in[3];
    cudaFuncSetAttribute(fused_kernel, cudaFuncAttributeMaxDynamicSharedMemorySize, SMEM_BYTES);
    fused_kernel<<<128, NTHREADS, SMEM_BYTES, cudaStreamPerThread>>>(p, tmW, tmWo, tmPhi, tmG, tmU, tmD, tmX, tmO, tmM, tmR);
}
```

```cpp
#include <cuda_runtime.h>
#include <cuda.h>
#include <cuda_bf16.h>
#include <stdint.h>

namespace {

typedef __nv_bfloat16 bf16;

constexpr int NTHREADS = 384;
constexpr int POLL_MAX = 400000;
constexpr uint32_t EMPTY = 0xffffffffu;

constexpr uint32_t OFF_RING = 0;
constexpr uint32_t OFF_XS   = 131072;
constexpr uint32_t OFF_WST  = 163840;
constexpr uint32_t OFF_XT   = 0;
constexpr uint32_t OFF_GA   = 32768;
constexpr uint32_t OFF_KVS  = 98304;
constexpr uint32_t OFF_PHI  = 114688;
constexpr uint32_t OFF_V    = 131072;
constexpr uint32_t OFF_DB   = 0;
constexpr uint32_t OFF_DA   = 98304;
constexpr uint64_t SLOT_A   = 0x1032541032541032ull, SLOT_B = 0x1054321054321054ull;
constexpr uint32_t PAR_A    = 0x3f00, PAR_B = 0x0fc0;
constexpr uint32_t OFF_OWN  = OFF_DA + 32768;
constexpr uint32_t OFF_OUT  = OFF_DA;
constexpr uint32_t OFF_UP0  = OFF_DA + 65536, OFF_UP1 = OFF_DB + 32768, OFF_DN0 = OFF_DA + 32768, OFF_DN1 = OFF_DB + 65536;
constexpr uint32_t OFF_WPHI = 196608;
constexpr uint32_t OFF_SP   = 204800;
constexpr uint32_t OFF_Z    = 221184;
constexpr uint32_t OFF_ONES = 225280;
constexpr uint32_t OFF_MODS = 226304;
constexpr uint32_t OFF_GB   = 196608;
constexpr uint32_t OFF_BQ   = 229376;
constexpr uint32_t OFF_ATOT = OFF_BQ + 256;
constexpr uint32_t OFF_BAR  = 230400;
constexpr uint32_t OFF_SEEN = OFF_BAR + 632;
constexpr uint32_t OFF_PAR  = OFF_BAR + 640;
constexpr uint32_t SMEM_BYTES = 232448;
constexpr uint32_t OFF_SILU = OFF_Z;
constexpr uint32_t OFF_RED0 = OFF_Z + 2048;
constexpr uint32_t OFF_ST2  = OFF_DB;
constexpr uint32_t OFF_KEYS = OFF_ST2 + 1024;
constexpr uint32_t OFF_SEL  = OFF_KEYS + 512;
constexpr uint32_t OFF_ROWS = OFF_ST2 + 2048;
constexpr uint32_t OFF_PX   = OFF_ROWS + 2560;
constexpr uint32_t OFF_HID  = OFF_PX + 1024;

enum {
    B_F1 = 0, B_E1 = 3, B_STFREE = 6, B_WPHI = 7, B_FA = 8, B_FB = 14, B_RF = 20,
    B_MP = 24, B_MOD = 25, B_PX = 41, B_NONE = 42, B_PHI = 43,
    B_XS = 51,
    B_WS = 55, B_KVD = 59, B_PAR = 63, B_S0 = 64, B_GU = 65, B_WD = 66, B_X2 = 67, B_ST2 = 68,
    B_RD = 69, B_ROWS = 70, B_OUTW = 71, B_PUB = 72, B_KVF = 74, B_OWN = 76, B_COUNT = 78,
    B_ED = B_MOD, B_S0FREE = B_NONE, B_KVS = B_XS, B_OGO = B_XS + 2, B_PF = B_XS + 3
};

struct Scratch {
    uint4 os[256 * 1024];
    uint4 kvp[32 * 256 * 32];
    uint4 kvf[32 * 288];
    uint4 st1[2048];
    uint4 mp[128 * 16];
    uint4 rest[1024];
    uint4 flo[256 * 2];
    uint4 st2[2048];
    uint4 cand[64 * 2];
    uint4 rowh[64 * 128];
    uint4 rowx[64 * 128];
    uint4 rsc[64 * 8 * 2];
    uint4 yp[56 * 512];
    unsigned done[4];
};
__device__ __align__(1024) Scratch g_scratch;
#define TS(i) do {} while (0)
#define TR(i)
#define TRL(i)
#define WT0()
#define WTJ(j)

__device__ __forceinline__ uint32_t smem_u32(const void* p) { return (uint32_t)__cvta_generic_to_shared(p); }
__device__ __forceinline__ uint32_t clk32() { uint32_t c; asm volatile("mov.u32 %0, %%clock;" : "=r"(c) :: "memory"); return c; }
__device__ __forceinline__ void arrive_one(uint32_t bar) {
    asm volatile("{\n.reg .pred p;\nelect.sync _|p, 0xffffffff;\n@p mbarrier.arrive.shared::cta.b64 _, [%0];\n}" :: "r"(bar) : "memory");
}
__device__ __forceinline__ void arrive_many(uint32_t bar, uint32_t n) {
    asm volatile("{\n.reg .pred p;\nelect.sync _|p, 0xffffffff;\n@p mbarrier.arrive.shared::cta.b64 _, [%0], %1;\n}" :: "r"(bar), "r"(n) : "memory");
}
__device__ __forceinline__ void arrive_if(uint32_t bar, uint32_t on) {
    asm volatile("{\n.reg .pred q, p;\nelect.sync _|q, 0xffffffff;\nsetp.ne.and.u32 p, %1, 0, q;\n@p mbarrier.arrive.shared::cta.b64 _, [%0];\n}" :: "r"(bar), "r"(on) : "memory");
}
__device__ __forceinline__ void arrive_both_if(uint32_t bar, uint32_t on) {
    asm volatile("{\n.reg .pred q, p;\n.reg .b32 r0, r1;\nelect.sync _|q, 0xffffffff;\nsetp.ne.and.u32 p, %1, 0, q;\n"
        "mapa.shared::cluster.u32 r0, %0, 0;\nmapa.shared::cluster.u32 r1, %0, 1;\n"
        "@p mbarrier.arrive.shared::cluster.b64 _, [r0];\n@p mbarrier.arrive.shared::cluster.b64 _, [r1];\n}" :: "r"(bar), "r"(on) : "memory");
}
__device__ __forceinline__ void st_partner128(uint32_t a, uint32_t bar, uint32_t cta, float x, float y, float z, float w) {
    asm volatile("{\n.reg .b32 ra, rb;\nmapa.shared::cluster.u32 ra, %0, %2;\nmapa.shared::cluster.u32 rb, %1, %2;\n"
        "st.async.weak.shared::cluster.mbarrier::complete_tx::bytes.v4.f32 [ra], {%3, %4, %5, %6}, [rb];\n}" :: "r"(a), "r"(bar), "r"(cta), "f"(x), "f"(y), "f"(z), "f"(w) : "memory");
}
__device__ __forceinline__ void mbar_wait(uint32_t bar, uint32_t parity) {
    asm volatile("{\n.reg .pred P1;\n.reg .u32 cnt;\nmov.u32 cnt, 0;\nLAB_WAIT:\n"
        "mbarrier.try_wait.parity.shared::cta.b64 P1, [%0], %1;\n@P1 bra DONE;\n"
        "add.u32 cnt, cnt, 1;\nsetp.lt.u32 P1, cnt, 1000000;\n@P1 bra LAB_WAIT;\ntrap;\nDONE:\n}" :: "r"(bar), "r"(parity) : "memory");
}
__device__ __forceinline__ uint64_t policy_evict_first() { uint64_t p; asm("createpolicy.fractional.L2::evict_first.b64 %0, 1.0;" : "=l"(p)); return p; }
#define EF_W 1
#define EF_WO 1
#define EF_F 1
#define EF_M 1
__device__ __forceinline__ void bulk_commit() { asm volatile("cp.async.bulk.commit_group;" ::: "memory"); }
__device__ __forceinline__ void bulk_wait() { asm volatile("cp.async.bulk.wait_group 0;" ::: "memory"); }
__device__ __forceinline__ void tmap_prefetch(const CUtensorMap* tm) { asm volatile("prefetch.tensormap [%0];" :: "l"(tm) : "memory"); }
#define EL "{\n.reg .pred e;\nelect.sync _|e, 0xffffffff;\n@e "
__device__ __forceinline__ void expect_tx_e(uint32_t bar, uint32_t bytes) { asm volatile(EL "mbarrier.arrive.expect_tx.shared::cta.b64 _, [%0], %1;\n}" :: "r"(bar), "r"(bytes) : "memory"); }
__device__ __forceinline__ void tma2_e(uint32_t dst, const CUtensorMap* tm, int c0, int c1, uint32_t bar) {
    asm volatile(EL "cp.async.bulk.tensor.2d.shared::cluster.global.mbarrier::complete_tx::bytes [%0], [%1, {%3, %4}], [%2];\n}"
        :: "r"(dst), "l"(tm), "r"(bar), "r"(c0), "r"(c1) : "memory");
}
__device__ __forceinline__ void tma2_ef_e(uint32_t dst, const CUtensorMap* tm, int c0, int c1, uint32_t bar) {
    asm volatile(EL "cp.async.bulk.tensor.2d.shared::cluster.global.mbarrier::complete_tx::bytes.L2::cache_hint [%0], [%1, {%3, %4}], [%2], %5;\n}"
        :: "r"(dst), "l"(tm), "r"(bar), "r"(c0), "r"(c1), "l"(policy_evict_first()) : "memory");
}
__device__ __forceinline__ void tma2_mc_e(uint32_t dst, const CUtensorMap* tm, int c0, int c1, uint32_t bar) {
    if (!EF_WO) asm volatile(EL "cp.async.bulk.tensor.2d.shared::cluster.global.mbarrier::complete_tx::bytes.multicast::cluster [%0], [%1, {%3, %4}], [%2], %5;\n}"
        :: "r"(dst), "l"(tm), "r"(bar), "r"(c0), "r"(c1), "h"((uint16_t)3) : "memory");
    else
    asm volatile(EL "cp.async.bulk.tensor.2d.shared::cluster.global.mbarrier::complete_tx::bytes.multicast::cluster.L2::cache_hint [%0], [%1, {%3, %4}], [%2], %5, %6;\n}"
        :: "r"(dst), "l"(tm), "r"(bar), "r"(c0), "r"(c1), "h"((uint16_t)3), "l"(policy_evict_first()) : "memory");
}
__device__ __forceinline__ void tma3_ef_e(uint32_t dst, const CUtensorMap* tm, int row, int blk, uint32_t bar) {
    if (!EF_F) asm volatile(EL "cp.async.bulk.tensor.3d.shared::cluster.global.mbarrier::complete_tx::bytes [%0], [%1, {0, %3, %4}], [%2];\n}"
        :: "r"(dst), "l"(tm), "r"(bar), "r"(row), "r"(blk) : "memory");
    else
    asm volatile(EL "cp.async.bulk.tensor.3d.shared::cluster.global.mbarrier::complete_tx::bytes.L2::cache_hint [%0], [%1, {0, %3, %4}], [%2], %5;\n}"
        :: "r"(dst), "l"(tm), "r"(bar), "r"(row), "r"(blk), "l"(policy_evict_first()) : "memory");
}
__device__ __forceinline__ void tma4_ef_e(uint32_t dst, const CUtensorMap* tm, int row, int blk, uint32_t bar) {
    if (!EF_W) asm volatile(EL "cp.async.bulk.tensor.4d.shared::cluster.global.mbarrier::complete_tx::bytes [%0], [%1, {0, %3, %4, 0}], [%2];\n}"
        :: "r"(dst), "l"(tm), "r"(bar), "r"(row), "r"(blk) : "memory");
    else
    asm volatile(EL "cp.async.bulk.tensor.4d.shared::cluster.global.mbarrier::complete_tx::bytes.L2::cache_hint [%0], [%1, {0, %3, %4, 0}], [%2], %5;\n}"
        :: "r"(dst), "l"(tm), "r"(bar), "r"(row), "r"(blk), "l"(policy_evict_first()) : "memory");
}
__device__ __forceinline__ void bulk_load_e(uint32_t dst, const void* src, uint32_t bytes, uint32_t bar) {
    asm volatile(EL "cp.async.bulk.shared::cluster.global.mbarrier::complete_tx::bytes [%0], [%1], %2, [%3];\n}" :: "r"(dst), "l"(src), "r"(bytes), "r"(bar) : "memory");
}
__device__ __forceinline__ void bulk_store_e(void* dst, uint32_t src, uint32_t bytes) {
    asm volatile(EL "cp.async.bulk.global.shared::cta.bulk_group [%0], [%1], %2;\n}" :: "l"(dst), "r"(src), "r"(bytes) : "memory");
}
__device__ __forceinline__ void st_flag_e(void* p, unsigned v) { asm volatile(EL "st.relaxed.gpu.global.u32 [%0], %1;\n}" :: "l"(p), "r"(v) : "memory"); }
__device__ __forceinline__ void mbar_init(uint32_t bar, uint32_t cnt) { asm volatile("mbarrier.init.shared::cta.b64 [%0], %1;" :: "r"(bar), "r"(cnt) : "memory"); }
__device__ __forceinline__ bool elect_one() {
    uint32_t p;
    asm volatile("{\n.reg .pred P;\nelect.sync _|P, 0xffffffff;\nselp.u32 %0, 1, 0, P;\n}" : "=r"(p));
    return p;
}
__device__ __forceinline__ void wg_fence() { asm volatile("wgmma.fence.sync.aligned;" ::: "memory"); }
__device__ __forceinline__ void wg_commit() { asm volatile("wgmma.commit_group.sync.aligned;" ::: "memory"); }
template<int N> __device__ __forceinline__ void wg_wait() { asm volatile("wgmma.wait_group.sync.aligned %0;" :: "n"(N) : "memory"); }
template<int N> __device__ __forceinline__ void acc_fence(float (&d)[N]) {
    #pragma unroll
    for (int i = 0; i < N; i++) asm volatile("" : "+f"(d[i]) :: "memory");
}
__device__ __forceinline__ uint64_t mk_desc(uint32_t addr, uint32_t lbo, uint32_t sbo, uint32_t swz) {
    uint32_t lo = ((addr & 0x3FFFF) >> 4) | (((lbo & 0x3FFFF) >> 4) << 16);
    uint32_t hi = (sbo >> 4) | (swz << 30);
    return ((uint64_t)hi << 32) | lo;
}
__device__ __forceinline__ uint64_t desc_add(uint64_t d, uint32_t bytes) { return (d & 0xffffffff00000000ull) | (uint32_t)((uint32_t)d + (bytes >> 4)); }
__device__ __forceinline__ uint64_t desc_raw(uint64_t d, uint32_t inc) { return (d & 0xffffffff00000000ull) | (uint32_t)((uint32_t)d + inc); }
__device__ __forceinline__ void fence_async_smem() { asm volatile("fence.proxy.async.shared::cta;" ::: "memory"); }
__device__ __forceinline__ void bar_sync(int id, int n) { asm volatile("bar.sync %0, %1;" :: "r"(id), "r"(n) : "memory"); }
__device__ __forceinline__ void bar_arrive(int id, int n) { asm volatile("bar.arrive %0, %1;" :: "r"(id), "r"(n) : "memory"); }
template<int R> __device__ __forceinline__ void reg_inc() { asm volatile("setmaxnreg.inc.sync.aligned.u32 %0;" :: "n"(R)); }
template<int R> __device__ __forceinline__ void reg_dec() { asm volatile("setmaxnreg.dec.sync.aligned.u32 %0;" :: "n"(R)); }
__device__ __forceinline__ void cluster_arrive() { asm volatile("barrier.cluster.arrive.relaxed.aligned;" ::: "memory"); }
__device__ __forceinline__ void cluster_wait() { asm volatile("barrier.cluster.wait.acquire.aligned;" ::: "memory"); }

__device__ __forceinline__ void stsm4(uint32_t addr, uint32_t r0, uint32_t r1, uint32_t r2, uint32_t r3) {
    asm volatile("stmatrix.sync.aligned.m8n8.x4.shared.b16 [%0], {%1,%2,%3,%4};" :: "r"(addr), "r"(r0), "r"(r1), "r"(r2), "r"(r3) : "memory");
}
__device__ __forceinline__ void ldsm4(uint32_t& r0, uint32_t& r1, uint32_t& r2, uint32_t& r3, uint32_t addr) {
    asm volatile("ldmatrix.sync.aligned.m8n8.x4.shared.b16 {%0,%1,%2,%3}, [%4];" : "=r"(r0), "=r"(r1), "=r"(r2), "=r"(r3) : "r"(addr) : "memory");
}
__device__ __forceinline__ void ldsm4t(uint32_t& r0, uint32_t& r1, uint32_t& r2, uint32_t& r3, uint32_t addr) {
    asm volatile("ldmatrix.sync.aligned.m8n8.x4.trans.shared.b16 {%0,%1,%2,%3}, [%4];" : "=r"(r0), "=r"(r1), "=r"(r2), "=r"(r3) : "r"(addr) : "memory");
}
__device__ __forceinline__ void mma16816(float (&d)[4], uint32_t a0, uint32_t a1, uint32_t a2, uint32_t a3, uint32_t b0, uint32_t b1) {
    asm("mma.sync.aligned.m16n8k16.row.col.f32.bf16.bf16.f32 {%0,%1,%2,%3}, {%4,%5,%6,%7}, {%8,%9}, {%0,%1,%2,%3};"
        : "+f"(d[0]), "+f"(d[1]), "+f"(d[2]), "+f"(d[3]) : "r"(a0), "r"(a1), "r"(a2), "r"(a3), "r"(b0), "r"(b1));
}
__device__ __forceinline__ uint4 lds128(uint32_t a) { uint4 v; asm volatile("ld.shared.v4.b32 {%0,%1,%2,%3}, [%4];" : "=r"(v.x), "=r"(v.y), "=r"(v.z), "=r"(v.w) : "r"(a) : "memory"); return v; }
__device__ __forceinline__ uint2 lds64(uint32_t a) { uint2 v; asm volatile("ld.shared.v2.b32 {%0,%1}, [%2];" : "=r"(v.x), "=r"(v.y) : "r"(a) : "memory"); return v; }
__device__ __forceinline__ uint32_t lds32(uint32_t a) { uint32_t v; asm volatile("ld.shared.b32 %0, [%1];" : "=r"(v) : "r"(a) : "memory"); return v; }
__device__ __forceinline__ float ldsf(uint32_t a) { float v; asm volatile("ld.shared.f32 %0, [%1];" : "=f"(v) : "r"(a) : "memory"); return v; }
__device__ __forceinline__ uint32_t lds16(uint32_t a) { uint16_t v; asm volatile("ld.shared.b16 %0, [%1];" : "=h"(v) : "r"(a) : "memory"); return v; }
__device__ __forceinline__ void sts128(uint32_t a, uint4 v) { asm volatile("st.shared.v4.b32 [%0], {%1,%2,%3,%4};" :: "r"(a), "r"(v.x), "r"(v.y), "r"(v.z), "r"(v.w) : "memory"); }
__device__ __forceinline__ void sts64(uint32_t a, uint32_t x, uint32_t y) { asm volatile("st.shared.v2.b32 [%0], {%1,%2};" :: "r"(a), "r"(x), "r"(y) : "memory"); }
__device__ __forceinline__ void sts32(uint32_t a, uint32_t x) { asm volatile("st.shared.b32 [%0], %1;" :: "r"(a), "r"(x) : "memory"); }
__device__ __forceinline__ void stsf(uint32_t a, float x) { asm volatile("st.shared.f32 [%0], %1;" :: "r"(a), "f"(x) : "memory"); }
__device__ __forceinline__ void sts16(uint32_t a, uint32_t x) { asm volatile("st.shared.b16 [%0], %1;" :: "r"(a), "h"((uint16_t)x) : "memory"); }

__device__ __forceinline__ uint2 ldg64(const void* p) { uint2 v; asm volatile("ld.global.nc.v2.b32 {%0,%1}, [%2];" : "=r"(v.x), "=r"(v.y) : "l"(p)); return v; }
__device__ __forceinline__ void stg128(void* p, uint4 v) { asm volatile("st.global.v4.b32 [%0], {%1,%2,%3,%4};" :: "l"(p), "r"(v.x), "r"(v.y), "r"(v.z), "r"(v.w) : "memory"); }
__device__ __forceinline__ void stg_fill(void* p, uint32_t v) { asm volatile("st.global.v4.b32 [%0], {%1,%1,%1,%1};" :: "l"(p), "r"(v) : "memory"); }
__device__ __forceinline__ void st_ll(void* p, uint32_t x, uint32_t y, uint32_t z, uint32_t w) {
    asm volatile("{\n.reg .b128 t;\n.reg .b64 a, b;\nmov.b64 a, {%1, %2};\nmov.b64 b, {%3, %4};\nmov.b128 t, {a, b};\nst.relaxed.gpu.global.b128 [%0], t;\n}"
        :: "l"(p), "r"(x), "r"(y), "r"(z), "r"(w) : "memory");
}
__device__ __forceinline__ uint4 ld_ll(const void* p) {
    uint4 v;
    asm volatile("{\n.reg .b128 t;\n.reg .b64 a, b;\nld.relaxed.gpu.global.b128 t, [%4];\nmov.b128 {a, b}, t;\nmov.b64 {%0, %1}, a;\nmov.b64 {%2, %3}, b;\n}"
        : "=r"(v.x), "=r"(v.y), "=r"(v.z), "=r"(v.w) : "l"(p) : "memory");
    return v;
}
__device__ __forceinline__ void ld_ll_if(uint4& v, const void* p, bool go) {
    asm volatile("{\n.reg .b128 t;\n.reg .b64 a, b;\n.reg .pred q;\nsetp.ne.u32 q, %5, 0;\nmov.b64 a, {%0, %1};\nmov.b64 b, {%2, %3};\nmov.b128 t, {a, b};\n"
        "@q ld.relaxed.gpu.global.b128 t, [%4];\nmov.b128 {a, b}, t;\nmov.b64 {%0, %1}, a;\nmov.b64 {%2, %3}, b;\n}"
        : "+r"(v.x), "+r"(v.y), "+r"(v.z), "+r"(v.w) : "l"(p), "r"((uint32_t)go) : "memory");
}
__device__ __forceinline__ void st_ll8(void* p, uint32_t x, uint32_t y) {
    asm volatile("{\n.reg .b64 a;\nmov.b64 a, {%1, %2};\nst.relaxed.gpu.global.b64 [%0], a;\n}" :: "l"(p), "r"(x), "r"(y) : "memory");
}
__device__ __forceinline__ void st_ll4(void* p, uint32_t x) { asm volatile("st.relaxed.gpu.global.b32 [%0], %1;" :: "l"(p), "r"(x) : "memory"); }
__device__ __forceinline__ unsigned ld_rlx(const void* p) { unsigned v; asm volatile("ld.relaxed.gpu.global.u32 %0, [%1];" : "=r"(v) : "l"(p) : "memory"); return v; }
__device__ __forceinline__ void red_add4(void* p, float x, float y, float z, float w) {
    asm volatile("red.relaxed.gpu.global.add.v4.f32 [%0], {%1, %2, %3, %4};" :: "l"(p), "f"(x), "f"(y), "f"(z), "f"(w) : "memory");
}
__device__ __forceinline__ void fence_rel_gpu() { asm volatile("fence.proxy.async.global;\nfence.release.gpu;" ::: "memory"); }
__device__ __forceinline__ void fence_acq_gpu() { asm volatile("fence.acquire.gpu;" ::: "memory"); }
template<int N> __device__ __forceinline__ void poll_words(uint4 (&v)[N], const uint4* p, int stride, uint32_t tag) {
    #pragma unroll 1
    for (int it = 0; it < POLL_MAX; it++) {
        bool ok = true;
        #pragma unroll
        for (int i = 0; i < N; i++) v[i] = ld_ll(p + i * stride);
        #pragma unroll
        for (int i = 0; i < N; i++) ok = ok && (v[i].w == tag);
        if (ok) break;
    }
}
template<int B> __device__ __forceinline__ uint32_t low_byte(float v, uint32_t src) { return __byte_perm(__float_as_uint(v), src, 0x3214 + B); }
__device__ __forceinline__ uint32_t low_bits(float v, uint32_t tag2) { return (__float_as_uint(v) & ~3u) | tag2; }
__device__ __forceinline__ bool tagged2(uint32_t w, uint32_t tag2) { return (w & 3u) == tag2; }
__device__ __forceinline__ uint32_t umax4(uint4 v) { return max(max(v.x, v.y), max(v.z, v.w)); }
constexpr uint32_t ONE2 = 0x3F803F80u;
__device__ __forceinline__ uint32_t pack2(float lo, float hi) { uint32_t d; asm("cvt.rn.bf16x2.f32 %0, %1, %2;" : "=r"(d) : "f"(hi), "f"(lo)); return d; }
__device__ __forceinline__ float bf_lo(uint32_t v) { return __uint_as_float(v << 16); }
__device__ __forceinline__ float bf_lo_alu(uint32_t v) { uint32_t d; asm("prmt.b32 %0, %1, 0, 0x1044;" : "=r"(d) : "r"(v)); return __uint_as_float(d); }
__device__ __forceinline__ float bf_hi(uint32_t v) { return __uint_as_float(v & 0xffff0000u); }
__device__ __forceinline__ float rbf(float x) { return bf_lo(pack2(x, 0.f)); }
__device__ __forceinline__ uint32_t hsub2(uint32_t a, uint32_t b) { uint32_t d; asm("sub.rn.bf16x2 %0, %1, %2;" : "=r"(d) : "r"(a), "r"(b)); return d; }
__device__ __forceinline__ uint32_t hadd2(uint32_t a, uint32_t b) { uint32_t d; asm("add.rn.bf16x2 %0, %1, %2;" : "=r"(d) : "r"(a), "r"(b)); return d; }
__device__ __forceinline__ uint32_t hmul2(uint32_t a, uint32_t b) { uint32_t d; asm("mul.rn.bf16x2 %0, %1, %2;" : "=r"(d) : "r"(a), "r"(b)); return d; }
__device__ __forceinline__ uint32_t hmax2(uint32_t a, uint32_t b) { uint32_t d; asm("max.bf16x2 %0, %1, %2;" : "=r"(d) : "r"(a), "r"(b)); return d; }
__device__ __forceinline__ uint32_t hmin2(uint32_t a, uint32_t b) { uint32_t d; asm("min.bf16x2 %0, %1, %2;" : "=r"(d) : "r"(a), "r"(b)); return d; }
__device__ __forceinline__ float ex2(float x) { float y; asm("ex2.approx.ftz.f32 %0, %1;" : "=f"(y) : "f"(x)); return y; }
__device__ __forceinline__ float rcp(float x) { float y; asm("rcp.approx.ftz.f32 %0, %1;" : "=f"(y) : "f"(x)); return y; }
__device__ __forceinline__ float shfl_x(float v, int m) { return __shfl_xor_sync(0xffffffffu, v, m); }
constexpr float LOG2E = 1.4426950408889634f;
__device__ __forceinline__ float sigmoidf(float x) { return rcp(1.0f + ex2(-LOG2E * x)); }
__device__ __forceinline__ uint32_t ln_pair(uint32_t x, uint32_t m2, float rinv, uint32_t a, uint32_t s) {
    uint32_t d = hsub2(x, m2);
    uint32_t n = pack2(bf_lo(d) * rinv, bf_hi(d) * rinv);
    return hadd2(hmul2(n, a), s);
}
struct Recip { uint32_t hi, lo; };
__device__ __forceinline__ Recip split_recip(float r) { Recip q; q.hi = pack2(r, r); const float l = r - bf_hi(q.hi); q.lo = pack2(l, l); return q; }
__device__ __forceinline__ uint32_t hdiv2(uint32_t n, Recip r) { uint32_t d; asm("fma.rn.bf16x2 %0, %1, %2, %3;" : "=r"(d) : "r"(n), "r"(r.hi), "r"(hmul2(n, r.lo))); return d; }
__device__ __forceinline__ uint32_t ln_pair(uint32_t x, uint32_t m2, Recip r, uint32_t a, uint32_t s) { return hadd2(hmul2(hdiv2(hsub2(x, m2), r), a), s); }
__device__ __forceinline__ void ln_final(float s1, float s2, uint32_t& m2, float& rinv) {
    const float mean = s1 * (1.0f / 1024.0f), var = fmaf(-mean, mean, s2 * (1.0f / 1024.0f));
    m2 = pack2(mean, mean);
    float sd;
    asm("sqrt.approx.ftz.f32 %0, %1;" : "=f"(sd) : "f"(rbf(rbf(fmaxf(var, 0.f)) + 1e-5f)));
    rinv = rcp(rbf(sd));
}
__device__ __forceinline__ uint32_t f2key(float f) { uint32_t u = __float_as_uint(f); return (u & 0x80000000u) ? ~u : (u | 0x80000000u); }

struct FmState { float cp, cn, sp, sn; };
__device__ __forceinline__ uint32_t fm_extrema(const uint32_t* p) {
    const uint32_t mx = hmax2(hmax2(p[0], p[2]), hmax2(p[4], p[6]));
    const uint32_t mn = hmin2(hmin2(p[0], p[2]), hmin2(p[4], p[6])) ^ 0x80008000u;
    return hmax2(__byte_perm(mx, mn, 0x5410), __byte_perm(mx, mn, 0x7632));
}
template<bool PREV, bool CUR, bool NEXT>
__device__ __forceinline__ void fm_slot(FmState& s, const float (&ep)[16], uint32_t* o, const uint32_t* p, float (&e)[16], const uint32_t* pn) {
    float psp = s.sp, psn = s.sn, rp = 0.f, rn = 0.f, sp = 0.f, sn = 0.f;
    uint32_t mm = 0;
    #pragma unroll
    for (int j = 0; j < 4; j++) {
        float a0 = 0.f, a1 = 0.f, b0 = 0.f, b1 = 0.f;
        if (CUR) {
            const float f0 = bf_lo_alu(p[2 * j]), f1 = bf_hi(p[2 * j]);
            a0 = fmaf(f0, LOG2E, s.cp); a1 = fmaf(f1, LOG2E, s.cp); b0 = fmaf(f0, -LOG2E, s.cn); b1 = fmaf(f1, -LOG2E, s.cn);
            e[2 * j] = ex2(a0);
        }
        if (PREV && j == 0) { psp += shfl_x(psp, 1); psn += shfl_x(psn, 1); }
        if (NEXT && j == 0) mm = fm_extrema(pn);
        if (PREV && j >= 2) { const float r = j == 2 ? rp : rn; o[8 * (j - 2)] = pack2(ep[8 * (j - 2)] * r, ep[8 * (j - 2) + 1] * r); }
        if (CUR) e[2 * j + 1] = ex2(a1);
        if (NEXT && j == 0) mm = hmax2(mm, __shfl_xor_sync(0xffffffffu, mm, 1));
        if (PREV && j == 1) { const float r = rcp(psp * psn); rp = r * psn; rn = r * psp; }
        if (PREV && j >= 2) { const float r = j == 2 ? rp : rn; o[8 * (j - 2) + 2] = pack2(ep[8 * (j - 2) + 2] * r, ep[8 * (j - 2) + 3] * r); }
        if (CUR && j >= 1) sp = j == 1 ? e[0] + e[1] : (sp + e[2 * j - 2]) + e[2 * j - 1];
        if (CUR) e[8 + 2 * j] = ex2(b0);
        if (PREV && j == 0) { psp += shfl_x(psp, 2); psn += shfl_x(psn, 2); }
        if (NEXT && j == 1) mm = hmax2(mm, __shfl_xor_sync(0xffffffffu, mm, 2));
        if (PREV && j >= 2) { const float r = j == 2 ? rp : rn; o[8 * (j - 2) + 4] = pack2(ep[8 * (j - 2) + 4] * r, ep[8 * (j - 2) + 5] * r); }
        if (CUR) e[9 + 2 * j] = ex2(b1);
        if (PREV && j >= 2) { const float r = j == 2 ? rp : rn; o[8 * (j - 2) + 6] = pack2(ep[8 * (j - 2) + 6] * r, ep[8 * (j - 2) + 7] * r); }
        if (CUR && j >= 1) sn = j == 1 ? e[8] + e[9] : (sn + e[6 + 2 * j]) + e[7 + 2 * j];
    }
    if (NEXT) { s.cp = -bf_lo(mm) * LOG2E; s.cn = -bf_hi(mm) * LOG2E; }
    if (CUR) { s.sp = (sp + e[6]) + e[7]; s.sn = (sn + e[14]) + e[15]; }
}
__device__ __forceinline__ float reduce8(const float (&v)[8], int lane) {
    const bool b3 = lane & 16, b2 = lane & 8, b1 = lane & 4;
    float a[4], b[2];
    #pragma unroll
    for (int i = 0; i < 4; i++) { float keep = b3 ? v[4 + i] : v[i], send = b3 ? v[i] : v[4 + i]; a[i] = keep + shfl_x(send, 16); }
    #pragma unroll
    for (int i = 0; i < 2; i++) { float keep = b2 ? a[2 + i] : a[i], send = b2 ? a[i] : a[2 + i]; b[i] = keep + shfl_x(send, 8); }
    float keep = b1 ? b[1] : b[0], send = b1 ? b[0] : b[1];
    return keep + shfl_x(send, 4);
}
template<int TB> __device__ __forceinline__ void wgmma_n32_rs(float (&d)[16], uint32_t a0, uint32_t a1, uint32_t a2, uint32_t a3, uint64_t db, int sc) {
  asm volatile("{\n.reg .pred p;\nsetp.ne.b32 p, %21, 0;\n"
    "wgmma.mma_async.sync.aligned.m64n32k16.f32.bf16.bf16 {%0, %1, %2, %3, %4, %5, %6, %7, %8, %9, %10, %11, %12, %13, %14, %15}, {%16,%17,%18,%19}, %20, p, 1, 1, %22;\n}\n"
    : "+f"(d[0]), "+f"(d[1]), "+f"(d[2]), "+f"(d[3]), "+f"(d[4]), "+f"(d[5]), "+f"(d[6]), "+f"(d[7]), "+f"(d[8]), "+f"(d[9]), "+f"(d[10]), "+f"(d[11]), "+f"(d[12]), "+f"(d[13]), "+f"(d[14]), "+f"(d[15])
    : "r"(a0), "r"(a1), "r"(a2), "r"(a3), "l"(db), "r"(sc), "n"(TB));
}
template<int TA, int TB> __device__ __forceinline__ void wgmma_n40_ss(float (&d)[20], uint64_t da, uint64_t db, int sc) {
  asm volatile("{\n.reg .pred p;\nsetp.ne.b32 p, %22, 0;\n"
    "wgmma.mma_async.sync.aligned.m64n40k16.f32.bf16.bf16 {%0, %1, %2, %3, %4, %5, %6, %7, %8, %9, %10, %11, %12, %13, %14, %15, %16, %17, %18, %19}, %20, %21, p, 1, 1, %23, %24;\n}\n"
    : "+f"(d[0]), "+f"(d[1]), "+f"(d[2]), "+f"(d[3]), "+f"(d[4]), "+f"(d[5]), "+f"(d[6]), "+f"(d[7]), "+f"(d[8]), "+f"(d[9]), "+f"(d[10]), "+f"(d[11]), "+f"(d[12]), "+f"(d[13]), "+f"(d[14]), "+f"(d[15]), "+f"(d[16]), "+f"(d[17]), "+f"(d[18]), "+f"(d[19])
    : "l"(da), "l"(db), "r"(sc), "n"(TA), "n"(TB));
}
template<int TA, int TB> __device__ __forceinline__ void wgmma_n128_ss(float (&d)[64], uint64_t da, uint64_t db, int sc) {
  asm volatile("{\n.reg .pred p;\nsetp.ne.b32 p, %66, 0;\n"
    "wgmma.mma_async.sync.aligned.m64n128k16.f32.bf16.bf16 {%0, %1, %2, %3, %4, %5, %6, %7, %8, %9, %10, %11, %12, %13, %14, %15, %16, %17, %18, %19, %20, %21, %22, %23, %24, %25, %26, %27, %28, %29, %30, %31, %32, %33, %34, %35, %36, %37, %38, %39, %40, %41, %42, %43, %44, %45, %46, %47, %48, %49, %50, %51, %52, %53, %54, %55, %56, %57, %58, %59, %60, %61, %62, %63}, %64, %65, p, 1, 1, %67, %68;\n}\n"
    : "+f"(d[0]), "+f"(d[1]), "+f"(d[2]), "+f"(d[3]), "+f"(d[4]), "+f"(d[5]), "+f"(d[6]), "+f"(d[7]), "+f"(d[8]), "+f"(d[9]), "+f"(d[10]), "+f"(d[11]), "+f"(d[12]), "+f"(d[13]), "+f"(d[14]), "+f"(d[15]), "+f"(d[16]), "+f"(d[17]), "+f"(d[18]), "+f"(d[19]), "+f"(d[20]), "+f"(d[21]), "+f"(d[22]), "+f"(d[23]), "+f"(d[24]), "+f"(d[25]), "+f"(d[26]), "+f"(d[27]), "+f"(d[28]), "+f"(d[29]), "+f"(d[30]), "+f"(d[31]), "+f"(d[32]), "+f"(d[33]), "+f"(d[34]), "+f"(d[35]), "+f"(d[36]), "+f"(d[37]), "+f"(d[38]), "+f"(d[39]), "+f"(d[40]), "+f"(d[41]), "+f"(d[42]), "+f"(d[43]), "+f"(d[44]), "+f"(d[45]), "+f"(d[46]), "+f"(d[47]), "+f"(d[48]), "+f"(d[49]), "+f"(d[50]), "+f"(d[51]), "+f"(d[52]), "+f"(d[53]), "+f"(d[54]), "+f"(d[55]), "+f"(d[56]), "+f"(d[57]), "+f"(d[58]), "+f"(d[59]), "+f"(d[60]), "+f"(d[61]), "+f"(d[62]), "+f"(d[63])
    : "l"(da), "l"(db), "r"(sc), "n"(TA), "n"(TB));
}
template<int TB> __device__ __forceinline__ void wgmma_n128_rs(float (&d)[64], uint32_t a0, uint32_t a1, uint32_t a2, uint32_t a3, uint64_t db, int sc) {
  asm volatile("{\n.reg .pred p;\nsetp.ne.b32 p, %69, 0;\n"
    "wgmma.mma_async.sync.aligned.m64n128k16.f32.bf16.bf16 {%0, %1, %2, %3, %4, %5, %6, %7, %8, %9, %10, %11, %12, %13, %14, %15, %16, %17, %18, %19, %20, %21, %22, %23, %24, %25, %26, %27, %28, %29, %30, %31, %32, %33, %34, %35, %36, %37, %38, %39, %40, %41, %42, %43, %44, %45, %46, %47, %48, %49, %50, %51, %52, %53, %54, %55, %56, %57, %58, %59, %60, %61, %62, %63}, {%64,%65,%66,%67}, %68, p, 1, 1, %70;\n}\n"
    : "+f"(d[0]), "+f"(d[1]), "+f"(d[2]), "+f"(d[3]), "+f"(d[4]), "+f"(d[5]), "+f"(d[6]), "+f"(d[7]), "+f"(d[8]), "+f"(d[9]), "+f"(d[10]), "+f"(d[11]), "+f"(d[12]), "+f"(d[13]), "+f"(d[14]), "+f"(d[15]), "+f"(d[16]), "+f"(d[17]), "+f"(d[18]), "+f"(d[19]), "+f"(d[20]), "+f"(d[21]), "+f"(d[22]), "+f"(d[23]), "+f"(d[24]), "+f"(d[25]), "+f"(d[26]), "+f"(d[27]), "+f"(d[28]), "+f"(d[29]), "+f"(d[30]), "+f"(d[31]), "+f"(d[32]), "+f"(d[33]), "+f"(d[34]), "+f"(d[35]), "+f"(d[36]), "+f"(d[37]), "+f"(d[38]), "+f"(d[39]), "+f"(d[40]), "+f"(d[41]), "+f"(d[42]), "+f"(d[43]), "+f"(d[44]), "+f"(d[45]), "+f"(d[46]), "+f"(d[47]), "+f"(d[48]), "+f"(d[49]), "+f"(d[50]), "+f"(d[51]), "+f"(d[52]), "+f"(d[53]), "+f"(d[54]), "+f"(d[55]), "+f"(d[56]), "+f"(d[57]), "+f"(d[58]), "+f"(d[59]), "+f"(d[60]), "+f"(d[61]), "+f"(d[62]), "+f"(d[63])
    : "r"(a0), "r"(a1), "r"(a2), "r"(a3), "l"(db), "r"(sc), "n"(TB));
}
template<int TB> __device__ __forceinline__ void wgmma_n256_rs(float (&d)[128], uint32_t a0, uint32_t a1, uint32_t a2, uint32_t a3, uint64_t db, int sc) {
  asm volatile("{\n.reg .pred p;\nsetp.ne.b32 p, %133, 0;\n"
    "wgmma.mma_async.sync.aligned.m64n256k16.f32.bf16.bf16 {%0, %1, %2, %3, %4, %5, %6, %7, %8, %9, %10, %11, %12, %13, %14, %15, %16, %17, %18, %19, %20, %21, %22, %23, %24, %25, %26, %27, %28, %29, %30, %31, %32, %33, %34, %35, %36, %37, %38, %39, %40, %41, %42, %43, %44, %45, %46, %47, %48, %49, %50, %51, %52, %53, %54, %55, %56, %57, %58, %59, %60, %61, %62, %63, %64, %65, %66, %67, %68, %69, %70, %71, %72, %73, %74, %75, %76, %77, %78, %79, %80, %81, %82, %83, %84, %85, %86, %87, %88, %89, %90, %91, %92, %93, %94, %95, %96, %97, %98, %99, %100, %101, %102, %103, %104, %105, %106, %107, %108, %109, %110, %111, %112, %113, %114, %115, %116, %117, %118, %119, %120, %121, %122, %123, %124, %125, %126, %127}, {%128,%129,%130,%131}, %132, p, 1, 1, %134;\n}\n"
    : "+f"(d[0]), "+f"(d[1]), "+f"(d[2]), "+f"(d[3]), "+f"(d[4]), "+f"(d[5]), "+f"(d[6]), "+f"(d[7]), "+f"(d[8]), "+f"(d[9]), "+f"(d[10]), "+f"(d[11]), "+f"(d[12]), "+f"(d[13]), "+f"(d[14]), "+f"(d[15]), "+f"(d[16]), "+f"(d[17]), "+f"(d[18]), "+f"(d[19]), "+f"(d[20]), "+f"(d[21]), "+f"(d[22]), "+f"(d[23]), "+f"(d[24]), "+f"(d[25]), "+f"(d[26]), "+f"(d[27]), "+f"(d[28]), "+f"(d[29]), "+f"(d[30]), "+f"(d[31]), "+f"(d[32]), "+f"(d[33]), "+f"(d[34]), "+f"(d[35]), "+f"(d[36]), "+f"(d[37]), "+f"(d[38]), "+f"(d[39]), "+f"(d[40]), "+f"(d[41]), "+f"(d[42]), "+f"(d[43]), "+f"(d[44]), "+f"(d[45]), "+f"(d[46]), "+f"(d[47]), "+f"(d[48]), "+f"(d[49]), "+f"(d[50]), "+f"(d[51]), "+f"(d[52]), "+f"(d[53]), "+f"(d[54]), "+f"(d[55]), "+f"(d[56]), "+f"(d[57]), "+f"(d[58]), "+f"(d[59]), "+f"(d[60]), "+f"(d[61]), "+f"(d[62]), "+f"(d[63]), "+f"(d[64]), "+f"(d[65]), "+f"(d[66]), "+f"(d[67]), "+f"(d[68]), "+f"(d[69]), "+f"(d[70]), "+f"(d[71]), "+f"(d[72]), "+f"(d[73]), "+f"(d[74]), "+f"(d[75]), "+f"(d[76]), "+f"(d[77]), "+f"(d[78]), "+f"(d[79]), "+f"(d[80]), "+f"(d[81]), "+f"(d[82]), "+f"(d[83]), "+f"(d[84]), "+f"(d[85]), "+f"(d[86]), "+f"(d[87]), "+f"(d[88]), "+f"(d[89]), "+f"(d[90]), "+f"(d[91]), "+f"(d[92]), "+f"(d[93]), "+f"(d[94]), "+f"(d[95]), "+f"(d[96]), "+f"(d[97]), "+f"(d[98]), "+f"(d[99]), "+f"(d[100]), "+f"(d[101]), "+f"(d[102]), "+f"(d[103]), "+f"(d[104]), "+f"(d[105]), "+f"(d[106]), "+f"(d[107]), "+f"(d[108]), "+f"(d[109]), "+f"(d[110]), "+f"(d[111]), "+f"(d[112]), "+f"(d[113]), "+f"(d[114]), "+f"(d[115]), "+f"(d[116]), "+f"(d[117]), "+f"(d[118]), "+f"(d[119]), "+f"(d[120]), "+f"(d[121]), "+f"(d[122]), "+f"(d[123]), "+f"(d[124]), "+f"(d[125]), "+f"(d[126]), "+f"(d[127])
    : "r"(a0), "r"(a1), "r"(a2), "r"(a3), "l"(db), "r"(sc), "n"(TB));
}

#define T_S0 1000
#define T_S1 3500
#define NC 2
#define T_W1 1500
#define T_WD 0
#define NW0 32
#define PFN 3
#define PFJ 2
#define PFM 4
#define WOJ 10
#define WON 1
#define NLD 1
#define VFIRST 2
#define T_X0 300
#define T_XD 400
#define MCB 1
#define ORIENT 2
#define PFORDER 0x51634
#define PFORDER2 0x51
#define PFW0 2
#define CLRJ 3
#define CLRS 200
#define OGATE 5
#define PFD 0
#define GBN 6
#define BG1 99
#define BG2 99
#define BG3 99
#define BG4 99
#define BG5 99
#define SYNCQ 640
#define SYNCG 4
#define BSP 0
#define T_INI 450
#define T_WLATE 4000
#define T_REST 7000
#define T_COL 4000
#define PF_START 9000
#define PF_FIRST 2
#define PFP 400
#define CREG 208
#define TMA_WO tma2_ef_e
#define TMA_M tma2_ef_e
#define TMA_F tma2_ef_e
struct Ptrs { const bf16 *x, *c, *wmod, *wr, *wg, *wu, *wd, *wqkv, *wo; bf16* out; Scratch* s; };

#define BAR(i) (sb + OFF_BAR + 8u * (i))

__device__ __forceinline__ int d_block(int hg, int n) {
    const int m = n - (n >= 9 ? 9 : 2);
    return n < 2 ? 2 * hg + n : 2 * (m + (m >= hg)) + (n >= 9);
}
__host__ __device__ constexpr uint32_t bar_count(int i) {
    return (MCB && i >= B_ED && i < B_ED + 16) ? 16 : ((i >= B_E1 && i < B_E1 + 3) || (i >= B_NONE && i < B_PHI + 8) || i == B_OWN || i == B_OWN + 1 || (i >= B_ED && i < B_ED + 16)
            || i == B_STFREE || i == B_X2 || i == B_OUTW) ? 8
         : ((i >= B_KVD && i < B_KVD + 4) || i == B_ST2 || i == B_RD) ? 4 : (i == B_KVF || i == B_KVF + 1 ) ? 2 : 1;
}
template<int I0, int I1> __device__ __forceinline__ void init_barriers(uint32_t sb) {
    #pragma unroll
    for (int i = I0; i < I1; i++) mbar_init(BAR(i), bar_count(i));
}
template<int N> __device__ __forceinline__ uint32_t pop_max(uint32_t (&k)[N]) {
    uint32_t m = k[0];
    #pragma unroll
    for (int i = 1; i < N; i++) m = max(m, k[i]);
    m = __reduce_max_sync(0xffffffffu, m);
    #pragma unroll
    for (int i = 0; i < N; i++) k[i] = (k[i] == m) ? 0u : k[i];
    return m;
}
__device__ __forceinline__ void fma8(float (&a)[8], uint4 w, float s) {
    a[0] = fmaf(bf_lo(w.x), s, a[0]); a[1] = fmaf(bf_hi(w.x), s, a[1]); a[2] = fmaf(bf_lo(w.y), s, a[2]); a[3] = fmaf(bf_hi(w.y), s, a[3]);
    a[4] = fmaf(bf_lo(w.z), s, a[4]); a[5] = fmaf(bf_hi(w.z), s, a[5]); a[6] = fmaf(bf_lo(w.w), s, a[6]); a[7] = fmaf(bf_hi(w.w), s, a[7]);
}
__device__ __forceinline__ void mod_scatter(const float (&m)[8], uint32_t red, int lane) {
    const bool b4 = lane & 16, b3 = lane & 8;
    float a[4];
    #pragma unroll
    for (int i = 0; i < 4; i++) { const float keep = b4 ? m[4 + i] : m[i], send = b4 ? m[i] : m[4 + i]; a[i] = keep + shfl_x(send, 16); }
    const float k0 = b3 ? a[2] : a[0], k1 = b3 ? a[3] : a[1], s0 = b3 ? a[0] : a[2], s1 = b3 ? a[1] : a[3];
    sts64(red + (((lane & 7) >> 1) * 4 + (lane >> 3)) * 16 + (lane & 1) * 8, __float_as_uint(k0 + shfl_x(s0, 8)), __float_as_uint(k1 + shfl_x(s1, 8)));
}
__device__ __forceinline__ bool mod_collect(uint4 w0, uint4 w1, uint4 w2, uint4 w3, uint32_t sb, int jb, int lane, uint32_t tag2) {
    const uint32_t add = lane < 16 ? ONE2 : 0u;
    const uint32_t lo = pack2((__uint_as_float(w0.x) + __uint_as_float(w1.x)) + (__uint_as_float(w2.x) + __uint_as_float(w3.x)),
                              (__uint_as_float(w0.y) + __uint_as_float(w1.y)) + (__uint_as_float(w2.y) + __uint_as_float(w3.y)));
    const uint32_t hi = pack2((__uint_as_float(w0.z) + __uint_as_float(w1.z)) + (__uint_as_float(w2.z) + __uint_as_float(w3.z)),
                              (__uint_as_float(w0.w) + __uint_as_float(w1.w)) + (__uint_as_float(w2.w) + __uint_as_float(w3.w)));
    sts64(sb + OFF_MODS + jb * 256 + (lane & 15) * 16 + (lane >> 4) * 8, hadd2(lo, add), hadd2(hi, add));
    return tagged2(w0.w, tag2) && tagged2(w1.w, tag2) && tagged2(w2.w, tag2) && tagged2(w3.w, tag2);
}
__device__ __forceinline__ void phi_issue(float (&pp)[2][16], const uint32_t* a, uint32_t sb, int pair) {
    const uint64_t dw = mk_desc(sb + OFF_WPHI + pair * 4096, 16, 512, 2);
    wg_fence();
    #pragma unroll
    for (int ks = 0; ks < 2; ks++)
        #pragma unroll
        for (int h = 0; h < 2; h++) wgmma_n32_rs<1>(pp[h], a[8 * h + 4 * ks], a[8 * h + 4 * ks + 1], a[8 * h + 4 * ks + 2], a[8 * h + 4 * ks + 3], desc_add(dw, h * 2048 + ks * 1024), ks);
    wg_commit();
}
__device__ __forceinline__ uint32_t phi_tile(int i) { return OFF_PHI + ((0x432130434ull >> (4 * i + 4)) & 7) * 16384u; }
__device__ __forceinline__ void phi_store(const uint32_t (&ph)[16], uint32_t sb, uint32_t aoff, int i) {
    #pragma unroll
    for (int q = 0; q < 4; q++) stsm4(sb + phi_tile(i) + (aoff ^ (q << 5)), ph[4 * q], ph[4 * q + 1], ph[4 * q + 2], ph[4 * q + 3]);
    __syncwarp();
    arrive_one(BAR(B_PHI + i));
}

__global__ void __cluster_dims__(2, 1, 1) __launch_bounds__(NTHREADS, 1)
fused_kernel(const Ptrs p, const __grid_constant__ CUtensorMap tmW, const __grid_constant__ CUtensorMap tmWo, const __grid_constant__ CUtensorMap tmPhi,
             const __grid_constant__ CUtensorMap tmG, const __grid_constant__ CUtensorMap tmU, const __grid_constant__ CUtensorMap tmD,
             const __grid_constant__ CUtensorMap tmX, const __grid_constant__ CUtensorMap tmO, const __grid_constant__ CUtensorMap tmM,
             const __grid_constant__ CUtensorMap tmR, const __grid_constant__ CUtensorMap tmG8, const __grid_constant__ CUtensorMap tmU8,
             const __grid_constant__ CUtensorMap tmD8)
{
    extern __shared__ __align__(1024) uint8_t smem_raw[];
    const uint32_t sb = smem_u32(smem_raw);
    const int tid = threadIdx.x, lane = tid & 31, warp = __shfl_sync(0xffffffffu, tid >> 5, 0);
    const int b = blockIdx.x;
    const int pr = b >> 1, rank = b & 1;
    const int cls = pr < 4 ? 15 : pr < 36 ? 2 * ((pr - 4) & 7) : 2 * ((pr - 36) % 7) + 1, mem = pr < 4 ? pr : pr < 36 ? (pr - 4) >> 3 : (pr - 36) / 7;
    const int hg = (((cls + 1) >> 1) & 1) * 4 + mem, rb = (cls >> 1) * 2 + rank;
    const bool ffn = b < 112;
    const uint32_t cstart = clk32();

    if (warp >= 8) {
        const int t = tid & 127, w4 = warp & 3, g = lane >> 2, c = lane & 3;
        if (w4 == 0) TS(40);
        reg_dec<40>();
        if (w4 == 2) TS(41);
        if (w4 == 0) { tmap_prefetch(&tmX); tmap_prefetch(&tmW); }
        if (w4 == 3) tmap_prefetch(&tmM);
        if (w4 == 2) {
            if (elect_one()) init_barriers<B_XS, B_WS>(sb);
            __syncwarp();
            while (clk32() - cstart < T_X0) {}
            expect_tx_e(BAR(B_XS), 8192);
            bulk_load_e(sb + OFF_XS, p.x + (size_t)b * 16384, 8192, BAR(B_XS));
            TS(43);
        } else while (clk32() - cstart < T_INI) {}
        if (elect_one()) {
            if (w4 & 2) { if (w4 & 1) init_barriers<B_WS, B_COUNT>(sb); }
            else { if (w4 & 1) init_barriers<B_MP, B_XS>(sb); else init_barriers<0, B_MP>(sb); }
            asm volatile("fence.mbarrier_init.release.cluster;" ::: "memory");
        }
        __syncwarp();
        if (w4 == 1) { expect_tx_e(BAR(B_PX), 1024); sts32(sb + OFF_SEEN, 0); }
        if (w4 == 0) TS(42);
        if (w4 == 2) TS(44);
        bar_arrive(0, 384);
        cluster_arrive();
        if (w4 == 2) TS(48);
        if (w4 == 2) {
            #pragma unroll 1
            for (int i = 1; i < 4; i++) {
                while (clk32() - cstart < T_X0 + i * T_XD) {}
                expect_tx_e(BAR(B_XS + i), 8192);
                bulk_load_e(sb + OFF_XS + i * 8192u, p.x + (size_t)(b * 16 + i * 4) * 1024, 8192, BAR(B_XS + i));
            }
        }
        if (w4 == 3 && b < 32 * NC) {
            while (b >= NW0 && clk32() - cstart < T_W1 + (b >> 3) * T_WD) {}
            #pragma unroll 1
            for (int i = 0; i < 8; i++) {
                if (!(i & 1)) expect_tx_e(BAR(B_WS + (i >> 1)), 8192);
                tma2_ef_e(sb + OFF_WST + i * 4096u, &tmM, (((b >> 2) & 1) ? 0 : 1024) + (b >> 3) * 64, (b & 3) * 256 + i * 32, BAR(B_WS + (i >> 1)));
            }
        }
        const uint32_t tag = ld_rlx(p.s->done) + 1, tag2 = tag % 3u;
        if (w4 == 0) {
            int piece = ffn ? 0 : 20;
            uint4* clr = p.s->kvp + (hg * 1024 + rb) * 32 + lane;
            int s = 0;
            #pragma unroll 1
            for (int j = 0; j < 17; j++) {
                if (j >= 3) mbar_wait(BAR(B_E1 + s), ((j / 3) - 1) & 1);
                else if (j == 2) mbar_wait(BAR(B_STFREE), 0);
                else while (clk32() - cstart < (j ? T_S1 : T_S0)) {}
                const uint32_t st = sb + OFF_RING + s * 65536u;
                if (j < 16) {
                    expect_tx_e(BAR(B_F1 + s), 65536);
                    tma4_ef_e(st + 16384u, &tmW, j * 64, hg * 2, BAR(B_F1 + s));
                    tma2_e(st, &tmX, j * 64, rb * 128, BAR(B_F1 + s));
                } else {
                    #pragma unroll 1
                    for (int n = 0; n < 4; n++) {
                        if (!(n & 1)) expect_tx_e(BAR(B_FB + 4 + (n >> 1)), 16384);
                        TMA_WO(st + n * 8192u, &tmWo, hg * 128 + (n & 1) * 64, (2 * hg + (n >> 1)) * 64, BAR(B_FB + 4 + (n >> 1)));
                    }
                }
                if (j == 1) TS(50);
                s = s == 2 ? 0 : s + 1;
                if (j == 3) expect_tx_e(BAR(B_PF), ffn ? 20480 : 0);
                #pragma unroll 1
                for (; j >= 3 && piece < min(20, j < 16 ? (j - PFJ) * PFM / 4 : 20); piece++)
                    tma2_e(sb + OFF_PAR, piece < 8 ? &tmD8 : piece < 16 ? &tmU8 : &tmG8, piece < 8 ? rank * 512 + piece * 64 : pr * 64,
                           piece < 8 ? pr * 64 : rank * 512 + (piece < 16 ? piece - 8 : piece - 12) * 64, BAR(B_PF));
                if (j >= WOJ && j < WOJ + 4 * WON) asm volatile("prefetch.global.L2 [%0];" :: "l"((const char*)p.wo + ((j - WOJ) & 3) * 524288 + (b * 32 + lane) * 128));
                if (j >= CLRJ && j < CLRJ + 8) {
                    #pragma unroll
                    for (int i = 0; i < 8; i++) stg_fill(clr + i * 512, EMPTY);
                    clr += 4096;
                }
            }
            mbar_wait(BAR(B_E1 + 0), 1);
            expect_tx_e(BAR(B_S0), ffn ? 65536 : 32768);
            tma2_ef_e(sb + OFF_XT, &tmX, hg * 128, rb * 128, BAR(B_S0)); tma2_ef_e(sb + OFF_XT + 16384u, &tmX, hg * 128 + 64, rb * 128, BAR(B_S0));
            #pragma unroll 1
            for (int i = 0; i < (ffn ? 2 : 0); i++) tma2_ef_e(sb + OFF_GA + i * 16384u, &tmG, pr * 64, rank * 512 + i * 128, BAR(B_S0));
        } else if (w4 == 1) {
            while (clk32() - cstart < T_COL) {}
            #pragma unroll 1
            for (int it = 0, jb = 0, ph = 0; it < POLL_MAX && jb < 16; it++) {
                const int n = jb < NLD ? 1 : min(4, 16 - jb);
                if (jb >= NLD) {
                    expect_tx_e(BAR(B_MP), n * 2048);
                    bulk_load_e(sb + OFF_WPHI, p.s->mp + jb * 128, n * 2048, BAR(B_MP));
                    mbar_wait(BAR(B_MP), ph);
                    ph ^= 1;
                }
                #pragma unroll 1
                for (int q = 0; q < n; q++) {
                    uint4 w[4];
                    if (jb < NLD) {
                        #pragma unroll
                        for (int i = 0; i < 4; i++) w[i] = ld_ll(p.s->mp + (jb * 8 + (lane >> 4) * 4 + i) * 16 + (lane & 15));
                    } else {
                        #pragma unroll
                        for (int i = 0; i < 4; i++) w[i] = lds128(sb + OFF_WPHI + q * 2048 + (lane >> 4) * 1024 + (lane & 15) * 16 + i * 256);
                    }
                    if (!__all_sync(0xffffffffu, mod_collect(w[0], w[1], w[2], w[3], sb, jb, lane, tag2))) { if (jb >= 4) __nanosleep(300); break; }
                    arrive_many(BAR(B_MOD + jb), bar_count(B_MOD));
                    if (jb == 0) TS(51);
                    if (jb == 4) TS(5);
                    if (jb == 15) TS(8);
                    jb++;
                }
            }
            fence_async_smem();
            __syncwarp();
            expect_tx_e(BAR(B_WPHI), 8192);
            tma2_e(sb + OFF_WPHI, &tmPhi, 0, hg * 128, BAR(B_WPHI));
            #pragma unroll 1
            for (int i = 0; i < 4; i++) {
                if (ffn) { uint4* y = p.s->yp + pr * 512 + rank * 128 + i * 32 + lane; stg_fill(y, EMPTY); stg_fill(y + 256, EMPTY); }
                stg_fill(p.s->rowh + (lane >> 4) * 8192 + (rb * 4 + i) * 128 + hg * 16 + (lane & 15), EMPTY);
                if (lane < 18) stg_fill(p.s->kvf + (hg * 4 + i) * 288 + (lane < 16 ? (rb >> 2) * 64 + (rb & 3) * 8 + (lane >> 3) * 32 + (lane & 7) : 240 + rb * 2 + lane), EMPTY);
            }
            #pragma unroll 1
            for (int i = 0; i < 8; i++) {
                #pragma unroll
                for (int q = 0; q < 8; q++) stg_fill(p.s->os + (rb * 16 + 2 * hg) * 1024 + i * 256 + q * 32 + lane, EMPTY);
                __nanosleep(CLRS);
            }
            if (hg == 0 && lane < 8) stg_fill(p.s->cand + rb * 8 + lane, 0);
            if (lane < 28) stg_fill(lane < 16 ? p.s->st2 + rb * 128 + hg * 16 + lane : lane < 20 ? p.s->flo + (rb * 16 + hg * 2) * 2 + lane - 16
                                    : p.s->rsc + ((rb * 4 + ((lane - 20) >> 1)) * 8 + hg) * 2 + (lane & 1), 0);
            fence_rel_gpu();
            TS(36);
        } else {
            const int hw = w4 & 1;
            const uint32_t fb = BAR(B_RF + 2 * hw);
            float macc[8];
            if (w4 == 2) {
                if (lane < 8) stg_fill(p.s->rest + b * 8 + lane, 0);
                else if (lane < 24 && b >= 32 * NC) stg_fill(p.s->mp + b * 16 + lane - 8, EMPTY);
            }
            bar_sync(3, 320);
            #pragma unroll 1
            for (int job = b < 32 * NC; job < 2; job++) {
                const int nr = job ? 8 : 4;
                const uint32_t buf = sb + OFF_SP + hw * 8192u;
                const CUtensorMap* tm = job ? &tmR : &tmM;
                const int c0 = job ? 2048 + b * 32 : (((b >> 2) & 1) ? 0 : 1024) + (b >> 3) * 64;
                const int row0 = job ? hw * 512 : (b & 3) * 256 + hw * 128, rows = job ? 64 : 32;
                while (clk32() - cstart < (job ? T_REST : T_WLATE)) __nanosleep(100);
                #pragma unroll
                for (int i = 0; i < 8; i++) macc[i] = 0.f;
                #pragma unroll 1
                for (int q = -2; q < nr; q++) {
                    if (q >= 0) {
                        mbar_wait(fb + (q & 1) * 8, (q >> 1) & 1);
                        const uint32_t sv0 = sb + OFF_SILU + (row0 + q * rows + (job ? lane >> 2 : lane >> 3)) * 2, svs = job ? 16 : 8;
                        const uint32_t wa = buf + (q & 1) * 4096u + lane * 16u;
                        #pragma unroll 1
                        for (int i = 0; i < 8; i += 2) {
                            const uint32_t s0 = lds16(sv0 + i * svs), s1 = lds16(sv0 + (i + 1) * svs);
                            const uint4 w = lds128(wa + i * 512u), w1 = lds128(wa + (i + 1) * 512u);
                            fma8(macc, w, bf_lo(s0)); fma8(macc, w1, bf_lo(s1));
                        }
                    }
                    fence_async_smem();
                    __syncwarp();
                    if (q + 2 < nr) {
                        const uint32_t bar = fb + (q & 1) * 8;
                        expect_tx_e(bar, 4096);
                        TMA_M(buf + (q & 1) * 4096u, tm, c0, row0 + (q + 2) * rows, bar);
                    }
                }
                const uint32_t red = sb + OFF_RED0 + hw * 256;
                if (job == 0) mod_scatter(macc, red, lane);
                else stsf(red + (c * 8 + g) * 4, reduce8(macc, lane));
                bar_sync(4, 64);
                if (w4 == 2) {
                    const uint4 u0 = lds128(sb + OFF_RED0 + (lane & 15) * 16), u1 = lds128(sb + OFF_RED0 + 256 + (lane & 15) * 16);
                    const float v0 = __uint_as_float(u0.x) + __uint_as_float(u1.x), v1 = __uint_as_float(u0.y) + __uint_as_float(u1.y);
                    const float v2 = __uint_as_float(u0.z) + __uint_as_float(u1.z), v3 = __uint_as_float(u0.w) + __uint_as_float(u1.w);
                    const uint32_t add = (b >> 5) == 2 ? ONE2 : 0u;
                    if (job == 0) { if (lane < 16) st_ll(p.s->mp + b * 16 + lane, __float_as_uint(v0), __float_as_uint(v1), __float_as_uint(v2), low_bits(v3, tag2)); TS(13); }
                    else { if (lane < 8) st_ll(p.s->rest + b * 8 + lane, hadd2(pack2(v0, v1), add), hadd2(pack2(v2, v3), add), 0, tag); TS(33); }
                }
                bar_sync(4, 64);
            }
            tmap_prefetch(hw ? &tmWo : &tmG); tmap_prefetch(hw ? &tmU : &tmD); tmap_prefetch(hw ? &tmPhi : &tmO);
        }
        __syncwarp();
        cluster_wait();
        bar_sync(2, 128);
        reg_inc<504 - 2 * CREG>();
        if (w4 == 0) TS(6);
        #pragma unroll 1
        for (int h = 0; h < 4; h++) {
            mbar_wait(BAR(B_PHI + h), 0);
            if (w4 == 0) TS(h == 0 ? 58 : h == 1 ? 52 : h == 2 ? 53 : 59);
            fence_async_smem();
            float o[20];
            const uint32_t vb = OFF_V + h * 8192u;
            const uint64_t dp = mk_desc(sb + phi_tile(h), 16, 1024, 1), dv = mk_desc(sb + vb, OFF_ONES - vb, 512, 2);
            wg_fence();
            #pragma unroll
            for (int ks = 0; ks < 8; ks++)
                wgmma_n40_ss<1, 1>(o, desc_add(dp, ks * 2048), desc_raw(dv, ks * (64 - (64 << 16))), ks);
            wg_commit();
            if (h == w4 + 2) {
                expect_tx_e(BAR(B_KVS + w4), 8192);
                bulk_load_e(sb + OFF_KVS + w4 * 8192u, p.s->kvp + ((hg * 4 + w4) * 16 + rb) * 512, 8192, BAR(B_KVS + w4));
            }
            wg_wait<0>();
            acc_fence(o);
            arrive_one(BAR(B_KVD + h));
            uint4* dst = p.s->kvp + (((hg * 4 + h) * 16 + (t >> 3)) * 16 + rb) * 32 + (t & 7);
            #pragma unroll
            for (int k = 0; k < 2; k++) {
                const uint32_t z = __float_as_uint(o[16 + 2 * k]) + 0x80u;
                st_ll(dst + k * 8, low_byte<1>(o[4 * k], z), low_byte<2>(o[4 * k + 1], z), low_byte<3>(o[4 * k + 2], z), low_bits(o[4 * k + 3], tag2));
                st_ll(dst + 16 + k * 8, __float_as_uint(o[8 + 4 * k]), __float_as_uint(o[9 + 4 * k]), __float_as_uint(o[10 + 4 * k]), low_bits(o[11 + 4 * k], tag2));
            }
        }
        if (w4 == 0) TS(17);
        {
            uint4* const fin = p.s->kvf + (hg * 4 + w4) * 288;
            {
                const uint4* src = p.s->kvp + ((hg * 4 + w4) * 16 + rb) * 512 + lane;
                uint4 w[16];
                if (w4 < 2) {
                    mbar_wait(BAR(B_KVS + w4), 1);
                    #pragma unroll
                    for (int i = 0; i < 16; i++) w[i] = lds128(sb + OFF_KVS + w4 * 8192u + i * 512u + lane * 16u);
                } else {
                    #pragma unroll
                    for (int i = 0; i < 16; i++) w[i].w = EMPTY;
                }
                #pragma unroll 1
                for (int it = 0; it < POLL_MAX; it++) {
                    bool ok = true;
                    #pragma unroll
                    for (int i = 0; i < 16; i++) { const bool miss = !tagged2(w[i].w, tag2); ok = ok && !miss; ld_ll_if(w[i], src + i * 32, miss); }
                    if (__all_sync(0xffffffffu, ok)) break;
                }
                if (w4 == 0) TS(18);
                if (w4 == 3) TS(10);
                float s[2][5];
                #pragma unroll
                for (int i = 0; i < 16; i++) {
                    const float z = __uint_as_float(__byte_perm(__byte_perm(w[i].x, w[i].y, 0x0400), w[i].z, 0x4210) & 0xffffff00u);
                    float (&a)[5] = s[i & 1];
                    if (i < 2) { a[0] = __uint_as_float(w[i].x); a[1] = __uint_as_float(w[i].y); a[2] = __uint_as_float(w[i].z); a[3] = __uint_as_float(w[i].w); a[4] = z; }
                    else { a[0] += __uint_as_float(w[i].x); a[1] += __uint_as_float(w[i].y); a[2] += __uint_as_float(w[i].z); a[3] += __uint_as_float(w[i].w); a[4] += z; }
                }
                char* d = (char*)fin + ((rb >> 2) * 16 + (rb & 3) * 2 + (g & 1)) * 64 + (((lane >> 3) ^ (rb & 3)) << 4) + c * 4;
                st_ll4(d, pack2(s[0][0] + s[1][0], s[0][1] + s[1][1]));
                st_ll4(d + 512, pack2(s[0][2] + s[1][2], s[0][3] + s[1][3]));
                if (lane < 16 && c < 2) st_ll4((char*)fin + 4096 + rb * 32 + (g * 2 + c) * 4, pack2(s[0][4] + s[1][4], 0.f));
            }
            fence_acq_gpu();
            uint4 v[9];
            #pragma unroll 1
            for (int it = 0; it < POLL_MAX; it++) {
                uint32_t m = 0;
                #pragma unroll
                for (int k = 0; k < 9; k++) v[k] = ld_ll(fin + k * 32 + lane);
                #pragma unroll
                for (int k = 0; k < 9; k++) m = max(m, umax4(v[k]));
                if (__all_sync(0xffffffffu, m != EMPTY)) break;
            }
            #pragma unroll
            for (int k = 0; k < 8; k++) sts128(sb + OFF_SP + w4 * 4096u + k * 512u + lane * 16u, v[k]);
            const uint32_t za = sb + OFF_Z + ((lane >> 3) * 16 + ((lane >> 1) & 3) * 2 + (lane & 1) * 8) * 64u + ((w4 ^ ((lane >> 1) & 3)) << 4);
            sts16(za, v[8].x); sts16(za + 64, v[8].z);
            fence_async_smem();
            __syncwarp();
            arrive_one(BAR(B_KVF + (w4 >> 1)));
            if (w4 == 0) TS(19);
            if (w4 == 3) TS(1);
        }
        if (w4 == 0) {
            const unsigned* f = (const unsigned*)(p.s->flo + (rb * 16 + d_block(hg, lane & 15)) * 2);
            const uint4* const a0 = p.s->os + rb * 16384;
            uint32_t seen = 0;
            uint32_t kb = hg ? 0 : 2, s = 0, freeb = BAR(B_OWN), par = 0;
            mbar_wait(BAR(B_OWN), 0);
            #pragma unroll 1
            for (int n = 2; n < 16; n++) {
                if (!((seen >> n) & 1)) {
                    if (n >= 8) asm volatile("ld.acquire.cta.shared.u32 %0, [%1];" : "=r"(seen) : "r"(sb + OFF_SEEN) : "memory");
                    #pragma unroll 1
                    for (int it = 0; it < POLL_MAX && !((seen >> n) & 1); it++) { seen = __ballot_sync(0xffffffffu, ld_rlx(f) == tag); fence_acq_gpu(); }
                }
                mbar_wait(freeb, par);
                TR(64 + n);
                bulk_load_e(sb + OFF_DA + s * 16384u, a0 + kb * 1024, 16384, BAR(B_FA + s));
                expect_tx_e(BAR(B_FA + s), 16384);
                if (n == 2) TS(2);
                TR(16 + n);
                if (n == OGATE) arrive_one(BAR(B_OGO));
                if (n == 5 || n == 6) mbar_wait(BAR(B_PUB + n - 5), 0);
                kb = n == 8 ? 1 : kb + 2;
                if ((kb >> 1) == hg) kb += 2;
                s = (SLOT_A >> (4 * n + 4)) & 7;
                if (n >= 5) { freeb = BAR(B_ED + n - 5); par = 1; } else if (n == 3) freeb = BAR(B_OWN + 1);
            }
        } else if (w4 == 1) {
            if (ffn) { expect_tx_e(BAR(B_GU), 98304); expect_tx_e(BAR(B_WD), 65536); }
            mbar_wait(BAR(B_S0FREE), 1);
            #pragma unroll 1
            for (int n = 2; n < (ffn ? 20 : 16); n++) {
                if (n == BG1) mbar_wait(BAR(B_KVF + 1), 0);
                if (n == BG2) mbar_wait(BAR(B_PUB), 0);
                if (n == BG5) mbar_wait(BAR(B_OGO), 1);
                if (n >= 6) mbar_wait(BAR(B_ED + n - 6), 1);
                if (n < 16) {
                    const uint32_t s = (SLOT_B >> (4 * n)) & 7, bar = BAR(B_FB + s), dst = sb + OFF_DB + s * 16384u;
                    expect_tx_e(bar, 16384);
                    if (MCB && n >= 6) tma2_mc_e(dst + rank * 8192u, &tmWo, hg * 128 + rank * 64, d_block(hg, n) * 64, bar);
                    else { TMA_WO(dst, &tmWo, hg * 128, d_block(hg, n) * 64, bar); TMA_WO(dst + 8192u, &tmWo, hg * 128 + 64, d_block(hg, n) * 64, bar); }
                    if (ffn && n >= GBN && n < GBN + 2) TMA_F(sb + OFF_GB + (n - GBN) * 16384u, &tmG, pr * 64, rank * 512 + 256 + (n - GBN) * 128, BAR(B_GU));
                } else if (n < 18) {
                    if (n == 16) TS(49);
                    TMA_F(sb + OFF_UP0 + (n & 1) * 16384u, &tmU, pr * 64, rank * 512 + (n & 1) * 128, BAR(B_GU));
                    TMA_F(sb + OFF_UP1 + (n & 1) * 16384u, &tmU, pr * 64, rank * 512 + 256 + (n & 1) * 128, BAR(B_GU));
                } else {
                    tma3_ef_e(sb + OFF_DN0 + (n & 1) * 16384u, &tmD, pr * 64, rank * 8 + (n & 1) * 2, BAR(B_WD));
                    tma3_ef_e(sb + OFF_DN1 + (n & 1) * 16384u, &tmD, pr * 64, rank * 8 + 4 + (n & 1) * 2, BAR(B_WD));
                }
            }
        } else if (w4 == 3) {
            const unsigned* f = (const unsigned*)(p.s->flo + (rb * 16 + d_block(hg, lane & 15)) * 2);
            uint32_t seen = 0xffff0003u;
            mbar_wait(BAR(B_PUB + 1), 0);
            #pragma unroll 1
            for (int it = 0; it < POLL_MAX && seen != 0xffffffffu; it++) {
                const uint32_t m = seen | __ballot_sync(0xffffffffu, !((seen >> lane) & 1) && ld_rlx(f) == tag);
                if (m != seen) {
                    seen = m;
                    fence_acq_gpu();
                    __syncwarp();
                    asm volatile(EL "st.release.cta.shared.u32 [%0], %1;\n}" :: "r"(sb + OFF_SEEN), "r"(seen) : "memory");
                }
            }
        } else {
            #pragma unroll 1
            for (int q = 0; q < 2; q++) {
                if (q) mbar_wait(BAR(B_OGO), 1);
                mbar_wait(BAR(B_OWN + q), 0);
                bulk_store_e(p.s->os + (rb * 16 + 2 * hg + q) * 1024, sb + OFF_OWN + q * 16384u, 16384);
                bulk_commit();
                bulk_wait();
                st_flag_e(p.s->flo + (rb * 16 + 2 * hg + q) * 2, tag);
                arrive_one(BAR(B_PUB + q));
                if (q == 0) TS(3);
                TR(q);
            }
            mbar_wait(BAR(B_PF), 1);
            {
                uint4 w[4];
                poll_words<4>(w, p.s->rest + hg * 32 + lane, 256, tag);
                sts128(sb + OFF_PAR + lane * 32, make_uint4(w[2].x, w[1].x, w[3].x, w[0].x));
                sts128(sb + OFF_PAR + lane * 32 + 16, make_uint4(w[2].y, w[1].y, w[3].y, w[0].y));
                const uint2 wr = ldg64(p.wr + hg * 128 + lane * 4);
                sts64(sb + OFF_BQ + lane * 8, hmul2(w[2].x, wr.x), hmul2(w[2].y, wr.y));
            }
            float s = 0.f;
            #pragma unroll 1
            for (int i = 0; i < 2; i++) {
                uint4 w[4]; uint2 wr[4];
                #pragma unroll
                for (int q = 0; q < 4; q++) wr[q] = ldg64(p.wr + (lane + 32 * q + 128 * i) * 4);
                poll_words<4>(w, p.s->rest + 512 + i * 128 + lane, 32, tag);
                #pragma unroll
                for (int q = 0; q < 4; q++) { const uint32_t r0 = hmul2(w[q].x, wr[q].x), r1 = hmul2(w[q].y, wr[q].y); s += (bf_lo(r0) + bf_hi(r0)) + (bf_lo(r1) + bf_hi(r1)); }
            }
            __syncwarp();
            #pragma unroll
            for (int m = 16; m >= 1; m >>= 1) s += shfl_x(s, m);
            if (lane == 0) stsf(sb + OFF_ATOT, s);
            __syncwarp();
            arrive_one(BAR(B_PAR));
        }
        __syncwarp();
        {
            mbar_wait(BAR(B_PAR), 0);
            const uint2 pa0 = lds64(sb + OFF_PAR + lane * 32), pa1 = lds64(sb + OFF_PAR + lane * 32 + 16), wr = ldg64(p.wr + hg * 128 + lane * 4);
            const float atot = ldsf(sb + OFF_ATOT);
            mbar_wait(BAR(B_X2), 0);
            uint4 w;
            #pragma unroll 1
            for (int it = 0; it < POLL_MAX; it++) {
                w = ld_ll(p.s->st2 + rb * 128 + t);
                if (__all_sync(0xffffffffu, __uint_as_float(w.w) == 8.0f)) break;
            }
            if (w4 == 0) TS(31);
            uint32_t m2; float rinv;
            ln_final(__uint_as_float(w.x), __uint_as_float(w.y), m2, rinv);
            sts32(sb + OFF_KEYS + t * 4, (f2key(fmaf(-bf_lo(m2), atot, __uint_as_float(w.z)) * rinv) & ~127u) | (127 - t));
            sts64(sb + OFF_ST2 + t * 8, m2, __float_as_uint(rinv));
            bar_sync(2, 128);
            arrive_one(BAR(B_ST2));
            const uint4 kk = lds128(sb + OFF_KEYS + lane * 16);
            uint32_t k[4] = {kk.x, kk.y, kk.z, kk.w}, best;
            #pragma unroll 1
            for (int r = 0; r <= w4; r++) best = pop_max(k);
            const uint32_t row = 127 - (best & 127u), slot = rb * 4 + w4;
            if (hg == 0 && lane < 2) st_ll(p.s->cand + slot * 2 + lane, best, rb * 128 + row, 0, tag);
            if (w4 == 3) TS(23);
            const uint2 xv = lds64(sb + OFF_OUT + (row >> 3) * 2048u + (lane >> 4) * 1024u + (row & 7) * 128u + ((((lane >> 1) ^ row) & 7) << 4) + (lane & 1) * 8);
            const uint2 sv = lds64(sb + OFF_ST2 + row * 8);
            const uint32_t h0 = ln_pair(xv.x, sv.x, __uint_as_float(sv.y), pa0.x, pa0.y), h1 = ln_pair(xv.y, sv.x, __uint_as_float(sv.y), pa1.x, pa1.y);
            char* d = (char*)(p.s->rowh + slot * 128 + hg * 16) + lane * 8;
            st_ll8(d, h0, h1);
            st_ll8(d + 131072, xv.x, xv.y);
            __syncwarp();
            arrive_one(BAR(B_RD));
            float r = fmaf(bf_lo(h0), bf_lo(wr.x), bf_hi(h0) * bf_hi(wr.x)) + fmaf(bf_lo(h1), bf_lo(wr.y), bf_hi(h1) * bf_hi(wr.y));
            #pragma unroll
            for (int m = 16; m >= 1; m >>= 1) r += shfl_x(r, m);
            if (lane < 2) st_ll(p.s->rsc + (slot * 8 + hg) * 2 + lane, __float_as_uint(r), 0, 0, tag);
            if (w4 == 3) TS(24);
        }
        if (w4 == 0) {
            uint4 cv[2];
            poll_words<2>(cv, p.s->cand + lane * 2, 64, tag);
            __syncwarp();
            TS(11);
            uint32_t k[2] = {(cv[0].x & ~127u) | (63 - lane), (cv[1].x & ~127u) | (31 - lane)}, slot[4];
            #pragma unroll
            for (int i = 0; i < 4; i++) slot[i] = 63 - (pop_max(k) & 127u);
            const uint32_t myslot = lane < 16 ? (lane < 8 ? slot[0] : slot[1]) : (lane < 24 ? slot[2] : slot[3]);
            uint4 hv[4][2], sc;
            #pragma unroll 1
            for (int it = 0; it < POLL_MAX; it++) {
                sc = ld_ll(p.s->rsc + (myslot * 8 + (lane & 7)) * 2);
                uint32_t m = 0;
                #pragma unroll
                for (int i = 0; i < 4; i++) { hv[i][0] = ld_ll(p.s->rowh + slot[i] * 128 + rank * 64 + lane); hv[i][1] = ld_ll(p.s->rowh + slot[i] * 128 + rank * 64 + 32 + lane); }
                #pragma unroll
                for (int i = 0; i < 4; i++) m = max(m, max(max(hv[i][0].x, hv[i][0].z), max(hv[i][1].x, hv[i][1].z)));
                if (__all_sync(0xffffffffu, m != EMPTY && sc.w == tag)) break;
            }
            TS(12);
            const uint32_t r0 = __shfl_sync(0xffffffffu, cv[0].y, myslot & 31), r1 = __shfl_sync(0xffffffffu, cv[1].y, myslot & 31), row = myslot < 32 ? r0 : r1;
            float r = __uint_as_float(sc.x);
            r += shfl_x(r, 1); r += shfl_x(r, 2); r += shfl_x(r, 4);
            r = rbf(r);
            const uint32_t key = (f2key(r) & 0xffff0000u) | (0xffffu - row);
            uint32_t kq[1] = {key};
            const uint32_t best0 = pop_max(kq), best1 = pop_max(kq);
            const uint32_t m0 = __ballot_sync(0xffffffffu, key == best0), m1 = __ballot_sync(0xffffffffu, key == best1);
            #pragma unroll
            for (int i = 0; i < 4; i++)
                if (((m0 | m1) >> (8 * i)) & 1) {
                    const uint32_t a = sb + OFF_ROWS + ((m1 >> (8 * i)) & 1) * 1040u + lane * 16u;
                    sts128(a, hv[i][0]); sts128(a + 512, hv[i][1]);
                }
            if (key == best0 || key == best1) sts128(sb + OFF_SEL + (key == best1) * 16, make_uint4(row, myslot, __float_as_uint(r), 0));
            __syncwarp();
            arrive_one(BAR(B_ROWS));
            TS(25);
        } else if (w4 == 1) {
            mbar_wait(BAR(B_ROWS), 0);
            const uint4 sel = lds128(sb + OFF_SEL + rank * 16);
            const int col = pr * 16 + c * 2 + (lane >> 4) + (lane & 8);
            uint32_t xs, hs; uint4 gw;
            #pragma unroll 1
            for (int it = 0; it < POLL_MAX; it++) {
                const char* a = (const char*)(p.s->rowh + sel.y * 128) + (col >> 1) * 4;
                hs = ld_rlx(a); xs = ld_rlx(a + 131072); gw = ld_ll(p.s->rest + 768 + (col >> 2));
                if (hs != EMPTY && xs != EMPTY && gw.w == tag) break;
            }
            const uint32_t gq = (col & 2) ? gw.y : gw.x;
            const float fx = (col & 1) ? bf_hi(xs) : bf_lo(xs), fh = (col & 1) ? bf_hi(hs) : bf_lo(hs), fg = (col & 1) ? bf_hi(gq) : bf_lo(gq);
            const float sg = rbf(sigmoidf(__uint_as_float(sel.z)));
            const uint4* src = p.s->yp + g * 512 + rank * 256 + pr * 4 + c;
            uint4 w[7];
            #pragma unroll
            for (int i = 0; i < 7; i++) w[i] = make_uint4(0, EMPTY, 0, EMPTY);
            if (ffn) mbar_wait(BAR(B_PX), 0);
            #pragma unroll 1
            for (int it = 0; it < POLL_MAX; it++) {
                bool ok = true;
                #pragma unroll
                for (int i = 0; i < 7; i++) ld_ll_if(w[i], src + i * 4096, !(tagged2(w[i].y, tag2) && tagged2(w[i].w, tag2)));
                #pragma unroll
                for (int i = 0; i < 7; i++) ok = ok && tagged2(w[i].y, tag2) && tagged2(w[i].w, tag2);
                if (__all_sync(0xffffffffu, ok)) break;
            }
            TS(29);
            float y0 = 0.f, y1 = 0.f, y2 = 0.f, y3 = 0.f;
            #pragma unroll
            for (int i = 0; i < 7; i++) { y0 += __uint_as_float(w[i].x); y1 += __uint_as_float(w[i].y); y2 += __uint_as_float(w[i].z); y3 += __uint_as_float(w[i].w); }
            const bool b4 = lane & 16, b3 = lane & 8;
            const float a0 = (b4 ? y2 : y0) + shfl_x(b4 ? y0 : y2, 16), a1 = (b4 ? y3 : y1) + shfl_x(b4 ? y1 : y3, 16);
            float y = (b3 ? a1 : a0) + shfl_x(b3 ? a0 : a1, 8);
            y += shfl_x(y, 4);
            const float upd = rbf(rbf(y) * sg);
            if (!(lane & 4)) p.out[(size_t)sel.x * 1024 + col] = __float2bfloat16(fx + rbf(fg * rbf(fh + upd)));
            if (b == 0 && lane == 0) p.s->done[0] = tag;
            TS(28);
        } else if (w4 == 2) {
            mbar_wait(BAR(B_ROWS), 0);
            const uint32_t row0 = lds32(sb + OFF_SEL) - rb * 128, row1 = lds32(sb + OFF_SEL + 16) - rb * 128;
            mbar_wait(BAR(B_OUTW), 0);
            #pragma unroll 1
            for (uint32_t i = 0; i < 16; i++) {
                if ((row0 >> 3) != i && (row1 >> 3) != i) {
                    asm volatile(EL "cp.async.bulk.tensor.3d.global.shared::cta.bulk_group [%0, {0, %2, %3}], [%1];\n}"
                        :: "l"(&tmO), "r"(sb + OFF_OUT + i * 2048u), "r"(rb * 128 + i * 8), "r"(hg * 2) : "memory");
                } else {
                    #pragma unroll 1
                    for (uint32_t q = 0; q < 4; q++) {
                        const uint32_t r = q * 2 + (lane >> 4), ch = lane & 15;
                        const uint4 v = lds128(sb + OFF_OUT + i * 2048u + (ch >> 3) * 1024u + r * 128u + (((ch ^ r) & 7) << 4));
                        if (i * 8 + r != row0 && i * 8 + r != row1) stg128(p.out + (size_t)(rb * 128 + i * 8 + r) * 1024 + hg * 128 + ch * 8, v);
                    }
                }
            }
            bulk_commit();
            bulk_wait();
            TS(35);
        }
    } else {
        const int w4 = warp & 3, wgi = warp >> 2, g = lane >> 2, c = lane & 3;
        uint32_t m2[2]; float rinv[2];
        uint32_t tag2;
        {
            const int xrow = b * 16 + warp * 2;
            if (b < NW0)
                asm volatile("prefetch.global.L2 [%0];" :: "l"(p.wmod + (size_t)((b & 3) * 256 + tid) * 6144 + (((b >> 2) & 1) ? 0 : 1024) + (b >> 3) * 64));
            const uint2 cv = ldg64(p.c + tid * 4);
            const uint32_t tag = ld_rlx(p.s->done) + 1;
            if (lane < 2) stg_fill(p.s->st1 + xrow + lane, 0);
            if (warp == 0 && lane < 16 && b < 32 * NC) stg_fill(p.s->mp + b * 16 + lane, EMPTY);
            if (tid < 64) { int s = tid >> 2; sts128(sb + OFF_ONES + tid * 16, make_uint4(((tid & 3) == ((s >> 1) & 3)) ? 0x3F80u : 0u, 0, 0, 0)); }
            cluster_arrive();
            reg_inc<232>();
            {
                const float c0 = bf_lo(cv.x), c1 = bf_hi(cv.x), c2 = bf_lo(cv.y), c3 = bf_hi(cv.y);
                sts64(sb + OFF_SILU + tid * 8, pack2(c0 * sigmoidf(c0), c1 * sigmoidf(c1)), pack2(c2 * sigmoidf(c2), c3 * sigmoidf(c3)));
            }
            tag2 = tag % 3u;
            bar_sync(0, 384);
            bar_arrive(3, 320);
            if (warp == 0) TS(47);
            #pragma unroll 1
            for (int part = 0; part < 2; part++)
            if (part == (b < NW0)) {
                float s[2], q[2];
                mbar_wait(BAR(B_XS + (warp >> 1)), 0);
                #pragma unroll
                for (int r = 0; r < 2; r++) s[r] = q[r] = 0.f;
                #pragma unroll 1
                for (int i = 0; i < 4; i++) {
                    #pragma unroll
                    for (int r = 0; r < 2; r++) {
                        const uint4 xv = lds128(sb + OFF_XS + warp * 4096u + r * 2048u + (i * 32 + lane) * 16u);
                        const uint32_t u[4] = {xv.x, xv.y, xv.z, xv.w};
                        float s0 = 0.f, q0 = 0.f;
                        #pragma unroll
                        for (int e = 0; e < 4; e++) {
                            const float lo = bf_lo(u[e]), hi = bf_hi(u[e]);
                            s0 += lo; s[r] += hi; q0 = fmaf(lo, lo, q0); q[r] = fmaf(hi, hi, q[r]);
                        }
                        s[r] += s0; q[r] += q0;
                    }
                }
                if (warp == 0) TS(30);
                float sk = (lane & 16) ? s[1] : s[0], qk = (lane & 16) ? q[1] : q[0];
                sk += shfl_x((lane & 16) ? s[0] : s[1], 16); qk += shfl_x((lane & 16) ? q[0] : q[1], 16);
                #pragma unroll
                for (int m = 8; m >= 1; m >>= 1) { sk += shfl_x(sk, m); qk += shfl_x(qk, m); }
                uint32_t mm; float ri;
                ln_final(sk, qk, mm, ri);
                if (!(lane & 15)) st_ll(p.s->st1 + xrow + (lane >> 4), mm, __float_as_uint(ri), 0, tag);
                if (warp == 0) TS(14);
            } else if (b < 32 * NC) {
                float macc[8];
                #pragma unroll
                for (int i = 0; i < 8; i++) macc[i] = 0.f;
                mbar_wait(BAR(B_WS + (warp >> 1)), 0);
                #pragma unroll 2
                for (int i = 0; i < 8; i++)
                    fma8(macc, lds128(sb + OFF_WST + warp * 4096u + i * 512u + lane * 16u), bf_lo(lds16(sb + OFF_SILU + ((b & 3) * 256 + warp * 32 + i * 4 + (lane >> 3)) * 2)));
                if (warp == 0) TS(46);
                mod_scatter(macc, sb + OFF_RED0 + warp * 256, lane);
                if (warp != 7) bar_arrive(5, 256);
                else {
                    bar_sync(5, 256);
                    float v0 = 0.f, v1 = 0.f, v2 = 0.f, v3 = 0.f;
                    #pragma unroll
                    for (int w = 0; w < 4; w++) {
                        const uint4 u = lds128(sb + OFF_RED0 + w * 512 + lane * 16);
                        v0 += __uint_as_float(u.x); v1 += __uint_as_float(u.y); v2 += __uint_as_float(u.z); v3 += __uint_as_float(u.w);
                    }
                    v0 += shfl_x(v0, 16); v1 += shfl_x(v1, 16); v2 += shfl_x(v2, 16); v3 += shfl_x(v3, 16);
                    if (lane < 16) st_ll(p.s->mp + b * 16 + lane, __float_as_uint(v0), __float_as_uint(v1), __float_as_uint(v2), low_bits(v3, tag2));
                    TS(45);
                }
            }
            arrive_one(BAR(B_STFREE));
            cluster_wait();
            uint4 st[2];
            poll_words<2>(st, p.s->st1 + rb * 128 + warp * 16 + g, 8, tag);
            __syncwarp();
            m2[0] = st[0].x; rinv[0] = __uint_as_float(st[0].y); m2[1] = st[1].x; rinv[1] = __uint_as_float(st[1].y);
            if (warp == 0) TS(4);
        }
        const int srow = warp * 16 + (lane & 15);
        const uint32_t aoff = srow * 128u + ((((lane >> 4) ^ srow) & 7) << 4);
        uint32_t pk[16], kq[48];
        {
            float accKV[128], accQ[64];
            {
                uint32_t f[2][4], r[4];
                mbar_wait(BAR(B_F1), 0);
                ldsm4(r[0], r[1], r[2], r[3], sb + OFF_RING + aoff);
                mbar_wait(BAR(B_MOD), 0);
                if (warp == 0) TS(15);
                uint4 md = lds128(sb + OFF_MODS + c * 16);
                int s = 0, sp = 2, par = 0;
                #pragma unroll 1
                for (int j = 0; j < 16; j++) {
                    const int sn = s == 2 ? 0 : s + 1;
                    par ^= s == 2;
                    const uint64_t db = mk_desc(sb + OFF_RING + s * 65536u + 16384u, 8192, 1024, 1);
                    #pragma unroll
                    for (int ks = 0; ks < 4; ks++) {
                        uint32_t (&ff)[4] = f[ks & 1];
                        ff[0] = ln_pair(r[0], m2[0], rinv[0], md.x, md.z); ff[1] = ln_pair(r[1], m2[1], rinv[1], md.x, md.z);
                        ff[2] = ln_pair(r[2], m2[0], rinv[0], md.y, md.w); ff[3] = ln_pair(r[3], m2[1], rinv[1], md.y, md.w);
                        const int kn = (ks + 1) & 3;
                        ldsm4(r[0], r[1], r[2], r[3], sb + OFF_RING + (ks == 3 ? sn : s) * 65536u + (aoff ^ (kn << 5)));
                        md = lds128(sb + OFF_MODS + ((ks == 3 ? j + 1 : j) * 4 + kn) * 64 + c * 16);
                        wg_fence();
                        wgmma_n256_rs<1>(accKV, ff[0], ff[1], ff[2], ff[3], desc_add(db, 16384 + ks * 2048), ks ? 1 : j);
                        wgmma_n128_rs<1>(accQ, ff[0], ff[1], ff[2], ff[3], desc_add(db, ks * 2048), ks ? 1 : j);
                        wg_commit();
                        wg_wait<1>();
                        if (ks == 0) arrive_if(BAR(B_E1 + sp), j);
                        if (ks == 2) {
                            WT0();
                            mbar_wait(BAR(B_MOD + ((j + 1) & 15)), 0);
                            mbar_wait(BAR(j < 15 ? B_F1 + sn : B_WPHI), j < 15 ? par : 0);
                        }
                    }
                    sp = s; s = sn;
                }
            }
            mbar_wait(BAR(B_E1 + 2), 0);
            wg_wait<0>();
            acc_fence(accKV); acc_fence(accQ);
            arrive_one(BAR(B_E1));
            if (warp == 0) TS(16);
            float pp[2][16];
            #pragma unroll
            for (int h = 0; h < 4; h++) {
                if (h == VFIRST) {
                    #pragma unroll
                    for (int i = 0; i < 16; i++) pk[i] = pack2(accKV[2 * i], accKV[2 * i + 1]);
                    phi_issue(pp, pk, sb, 0);
                }
                #pragma unroll
                for (int q = 0; q < 2; q++) {
                    const int o = 64 + 16 * h + 8 * q;
                    stsm4(sb + OFF_V + h * 8192u + srow * 64u + (((2 * q + (lane >> 4)) ^ ((srow >> 1) & 3)) << 4),
                          pack2(accKV[o], accKV[o + 1]), pack2(accKV[o + 2], accKV[o + 3]), pack2(accKV[o + 4], accKV[o + 5]), pack2(accKV[o + 6], accKV[o + 7]));
                }
            }
            #pragma unroll
            for (int i = 0; i < 48; i++) kq[i] = i < 16 ? pack2(accKV[32 + 2 * i], accKV[33 + 2 * i]) : pack2(accQ[2 * i - 32], accQ[2 * i - 31]);
            wg_wait<0>();
            acc_fence(pp[0]); acc_fence(pp[1]);
            #pragma unroll
            for (int i = 0; i < 16; i++) pk[i] = pack2(pp[i >> 3][2 * (i & 7)], pp[i >> 3][2 * (i & 7) + 1]);
        }
        reg_dec<CREG>();
        if (warp == 0) TS(56);
        {
            uint32_t ph[16];
            FmState fs; float ea[16], eb[16];
            #pragma unroll
            for (int i = 0; i < 16; i++) { ph[i] = 0; eb[i] = 0.f; }
            fs.sp = fs.sn = 1.f;
            fm_slot<false, false, true>(fs, ea, ph, pk, ea, pk);
            #pragma unroll 1
            for (int u = 0; u < 4; u++) {
                float pp[2][16];
                if (u & 2) { mbar_wait(BAR(B_KVD + 2 * u - 3), 0); phi_issue(pp, kq + 32, sb, 1); }
                else if (u & 1) phi_issue(pp, kq + 16, sb, 0);
                else phi_issue(pp, kq, sb, 1);
                fm_slot<true, true, true>(fs, eb, ph + 1, pk, ea, pk + 1);
                phi_store(ph, sb, aoff, 2 * u - 1);
                fm_slot<true, true, true>(fs, ea, ph, pk + 1, eb, pk + 8);
                fm_slot<true, true, true>(fs, eb, ph + 1, pk + 8, ea, pk + 9);
                phi_store(ph, sb, aoff, 2 * u);
                wg_wait<0>();
                acc_fence(pp[0]); acc_fence(pp[1]);
                #pragma unroll
                for (int i = 0; i < 8; i++) pk[i] = pack2(pp[0][2 * i], pp[0][2 * i + 1]);
                fm_slot<true, true, true>(fs, ea, ph, pk + 9, eb, pk);
                #pragma unroll
                for (int i = 0; i < 8; i++) pk[8 + i] = pack2(pp[1][2 * i], pp[1][2 * i + 1]);
            }
            fm_slot<true, false, false>(fs, eb, ph + 1, pk, ea, pk);
            phi_store(ph, sb, aoff, 7);
        }
        if (warp == 0) TS(57);
        uint32_t x2[16][2], gf[64];
        const uint32_t woff = lane * 128u + (((warp ^ lane) & 7) << 4);
        mbar_wait(BAR(B_S0), 0);
        #pragma unroll
        for (int q = 0; q < 8; q++) {
            ldsm4(x2[2 * q][0], x2[2 * q][1], x2[2 * q + 1][0], x2[2 * q + 1][1], sb + OFF_XT + (q >> 2) * 16384u + (aoff ^ ((q & 3) << 5)));
            ldsm4t(gf[4 * q], gf[4 * q + 1], gf[4 * q + 2], gf[4 * q + 3], sb + OFF_GA + q * 4096u + woff);
        }
        __syncwarp();
        arrive_one(BAR(B_S0FREE));
        #pragma unroll 1
        for (int pp = 0; pp < 2; pp++) {
            float o0[20], o1[20];
            const uint64_t dk = mk_desc(sb + OFF_SP + pp * 8192u, OFF_Z - OFF_SP - pp * 8160u, 512, 2);
            const uint64_t dq = mk_desc(sb + OFF_V + pp * 32768u + wgi * 8192u, 16, 1024, 1);
            mbar_wait(BAR(B_PHI + 5 + 2 * pp), 0);
            fence_async_smem();
            mbar_wait(BAR(B_KVF + pp), 0);
            wg_fence();
            #pragma unroll
            for (int ks = 0; ks < 4; ks++) {
                wgmma_n40_ss<0, 1>(o0, desc_add(dq, ks * 32), desc_add(dk, ks * 1024), ks);
                wgmma_n40_ss<0, 1>(o1, desc_add(dq, 16384 + ks * 32), desc_raw(dk, 256 + ks * 64 - (255 << 16)), ks);
            }
            wg_commit();
            wg_wait<0>();
            acc_fence(o0); acc_fence(o1);
            #pragma unroll
            for (int hh = 0; hh < 2; hh++) {
                const float (&o)[20] = hh ? o1 : o0;
                const Recip rd0 = split_recip(rcp(rbf(rbf(__shfl_sync(0xffffffffu, o[16], lane & ~3)) + 1e-6f)));
                const Recip rd1 = split_recip(rcp(rbf(rbf(__shfl_sync(0xffffffffu, o[18], lane & ~3)) + 1e-6f)));
                uint32_t op[8];
                #pragma unroll
                for (int j = 0; j < 4; j++) { op[2 * j] = hdiv2(pack2(o[4 * j], o[4 * j + 1]), rd0); op[2 * j + 1] = hdiv2(pack2(o[4 * j + 2], o[4 * j + 3]), rd1); }
                #pragma unroll
                for (int q = 0; q < 2; q++) stsm4(sb + OFF_OWN + pp * 16384u + (aoff ^ ((2 * hh + q) << 5)), op[4 * q], op[4 * q + 1], op[4 * q + 2], op[4 * q + 3]);
            }
            fence_async_smem();
            __syncwarp();
            arrive_one(BAR(B_OWN + pp));
            if (warp == 0) TS(20 + pp);
        }
        const uint32_t ooff = sb + OFF_OUT + (srow >> 3) * 1024u + aoff;
        {
            float acc[64];
            const uint32_t vchk = lane * 32u + g * 4u;
            const uint64_t da0 = mk_desc(sb + OFF_DA + wgi * 8192u, 16, 1024, 1), db0 = mk_desc(sb + OFF_DB, 8192, 1024, 1);
            #pragma unroll 1
            for (int n = 0; n < 16; n++) {
                const uint32_t s = (SLOT_A >> (4 * n)) & 7, sB = (SLOT_B >> (4 * n)) & 7;
                WT0();
                mbar_wait(BAR(B_FB + sB), (PAR_B >> n) & 1);
                WTJ(16 + n);
                mbar_wait(BAR(n < 2 ? B_OWN + n : B_FA + s), (PAR_A >> n) & 1);
                WTJ(n);
                {
                    const uint32_t ra = sb + OFF_DA + s * 16384u + warp * 2048u;
                    if (__any_sync(0xffffffffu, max(lds32(ra + vchk), lds32(ra + vchk + 1024)) == EMPTY)) {
                        #pragma unroll 1
                        for (int i = 0; i < 4; i++) {
                            uint4 v;
                            #pragma unroll 1
                            for (int it = 0; it < POLL_MAX; it++) {
                                v = ld_ll(p.s->os + (rb * 16 + d_block(hg, n)) * 1024 + warp * 128 + i * 32 + lane);
                                if (umax4(v) != EMPTY) break;
                            }
                            sts128(ra + i * 512 + lane * 16, v);
                        }
                        fence_async_smem();
                        __syncwarp();
                    }
                }
                TR(32 + 16 * wgi + n);
                const uint64_t da = desc_add(da0, s * 16384u), db = desc_add(db0, sB * 16384u);
                wg_fence();
                #pragma unroll
                for (int ks = 0; ks < 4; ks++) wgmma_n128_ss<0, 1>(acc, desc_add(da, ks * 32), desc_add(db, ks * 2048), ks ? 1 : n);
                wg_commit();
                wg_wait<1>();
                if (MCB) arrive_both_if(BAR(B_ED - 1 + n), n); else arrive_if(BAR(B_ED - 1 + n), n);
            }
            mbar_wait(BAR(B_PAR), 0);
            uint32_t gar[16], bfr[16];
            #pragma unroll
            for (int j = 0; j < 16; j++) {
                gar[j] = lds32(sb + OFF_PAR + j * 64 + c * 16 + 12);
                const uint32_t bq = lds32(sb + OFF_BQ + j * 16 + c * 4);
                bfr[j] = (g & 1) ? bq : ONE2;
            }
            wg_wait<0>();
            acc_fence(acc);
            bar_arrive(6 + wgi, 256);
            if (warp == 0) TS(9);
            float sd[2][4], q1[2][4], q2[2][4];
            #pragma unroll
            for (int e = 0; e < 4; e++) { sd[0][e] = sd[1][e] = q1[0][e] = q1[1][e] = q2[0][e] = q2[1][e] = 0.f; }
            #pragma unroll
            for (int s = 0; s < 8; s++) {
                #pragma unroll
                for (int e = 0; e < 4; e++) { const int j = 2 * s + (e >> 1), h = e & 1; x2[j][h] = hadd2(x2[j][h], hmul2(gar[j], pack2(acc[4 * j + 2 * h], acc[4 * j + 2 * h + 1]))); }
                mma16816(sd[s & 1], x2[2 * s][0], x2[2 * s][1], x2[2 * s + 1][0], x2[2 * s + 1][1], bfr[2 * s], bfr[2 * s + 1]);
                mma16816(q1[s & 1], x2[2 * s][0], x2[2 * s][1], x2[2 * s + 1][0], x2[2 * s + 1][1], x2[2 * s][0], x2[2 * s + 1][0]);
                mma16816(q2[s & 1], x2[2 * s][0], x2[2 * s][1], x2[2 * s + 1][0], x2[2 * s + 1][1], x2[2 * s][1], x2[2 * s + 1][1]);
            }
            if (c == (g >> 1)) {
                uint4* d = p.s->st2 + rb * 128 + warp * 16 + g;
                red_add4(d, sd[0][0] + sd[1][0], (g & 1) ? q1[0][1] + q1[1][1] : q1[0][0] + q1[1][0], sd[0][1] + sd[1][1], 1.0f);
                red_add4(d + 8, sd[0][2] + sd[1][2], (g & 1) ? q2[0][3] + q2[1][3] : q2[0][2] + q2[1][2], sd[0][3] + sd[1][3], 1.0f);
            }
            if (warp == 0) TS(22);
            bar_sync(7 - wgi, 256);
            #pragma unroll
            for (int q = 0; q < 8; q++) stsm4((ooff + (q >> 2) * 1024u) ^ ((q & 3) << 5), x2[2 * q][0], x2[2 * q][1], x2[2 * q + 1][0], x2[2 * q + 1][1]);
            __syncwarp();
            arrive_one(BAR(B_X2));
        }
        if (ffn) {
            mbar_wait(BAR(B_GU), 0);
            if (warp == 0) TS(38);
            #pragma unroll
            for (int q = 8; q < 16; q++) ldsm4t(gf[4 * q], gf[4 * q + 1], gf[4 * q + 2], gf[4 * q + 3], sb + OFF_GB + (q - 8) * 4096u + woff);
        }
        {
            mbar_wait(BAR(B_ST2), 0);
            const uint2 s0 = lds64(sb + OFF_ST2 + (warp * 16 + g) * 8), s1 = lds64(sb + OFF_ST2 + (warp * 16 + g + 8) * 8);
            const Recip r0 = split_recip(__uint_as_float(s0.y)), r1 = split_recip(__uint_as_float(s1.y));
            #pragma unroll
            for (int j = 0; j < 16; j++) {
                const uint4 pa = lds128(sb + OFF_PAR + j * 64 + c * 16);
                x2[j][0] = hadd2(x2[j][0], hmul2(pa.z, ln_pair(x2[j][0], s0.x, r0, pa.x, pa.y)));
                x2[j][1] = hadd2(x2[j][1], hmul2(pa.z, ln_pair(x2[j][1], s1.x, r1, pa.x, pa.y)));
            }
            mbar_wait(BAR(B_RD), 0);
            #pragma unroll
            for (int q = 0; q < 8; q++) stsm4((ooff + (q >> 2) * 1024u) ^ ((q & 3) << 5), x2[2 * q][0], x2[2 * q][1], x2[2 * q + 1][0], x2[2 * q + 1][1]);
            fence_async_smem();
            __syncwarp();
            arrive_one(BAR(B_OUTW));
            if (warp == 0) TS(32);
        }
        if (ffn) {
            float acc[4][4];
            {
                uint32_t uf[64];
                #pragma unroll
                for (int q = 0; q < 16; q++) ldsm4t(uf[4 * q], uf[4 * q + 1], uf[4 * q + 2], uf[4 * q + 3], sb + (q < 8 ? OFF_UP0 : OFF_UP1 - 32768u) + q * 4096u + woff);
                #pragma unroll
                for (int i = 0; i < 4; i++) { acc[i][0] = acc[i][1] = acc[i][2] = acc[i][3] = 0.f; }
                mbar_wait(BAR(B_WD), 0);
                mbar_wait(BAR(B_ROWS), 0);
                #pragma unroll
                for (int q = 0; q < 16; q++) {
                    uint32_t b0, b1, b2, b3;
                    ldsm4(b0, b1, b2, b3, sb + OFF_ROWS + (lane & 1) * 1040u + (lane >> 3) * 16u + q * 64u);
                    mma16816(acc[(2 * q) & 3], gf[4 * q], uf[4 * q], gf[4 * q + 1], uf[4 * q + 1], b0, b1);
                    mma16816(acc[(2 * q + 1) & 3], gf[4 * q + 2], uf[4 * q + 2], gf[4 * q + 3], uf[4 * q + 3], b2, b3);
                }
            }
            float s[4];
            #pragma unroll
            for (int e = 0; e < 4; e++) s[e] = (acc[0][e] + acc[1][e]) + (acc[2][e] + acc[3][e]);
            const uint32_t pxa = sb + OFF_PX + (warp * 8 + g) * 16u;
            if (c == 0) st_partner128(pxa, BAR(B_PX), rank ^ 1, s[0], s[1], s[2], s[3]);
            if (warp == 0) TS(34);
            uint32_t df[4][4][4];
            {
                const uint32_t da = sb + (wgi ? OFF_DN1 : OFF_DN0) + w4 * 8192u + ((lane & 7) + ((lane >> 4) << 3)) * 128u;
                #pragma unroll
                for (int tt = 0; tt < 4; tt++)
                    #pragma unroll
                    for (int ks = 0; ks < 4; ks++)
                        ldsm4t(df[tt][ks][0], df[tt][ks][1], df[tt][ks][2], df[tt][ks][3], da + ks * 2048u + (((2 * tt + ((lane >> 3) & 1)) ^ (lane & 7)) << 4));
            }
            mbar_wait(BAR(B_PX), 0);
            {
                const uint4 q = lds128(pxa);
                float gt = rbf((c & 1) ? s[1] + __uint_as_float(q.y) : s[0] + __uint_as_float(q.x));
                const float us = rbf((c & 1) ? s[3] + __uint_as_float(q.w) : s[2] + __uint_as_float(q.z));
                gt = rbf(gt * sigmoidf(gt));
                if (c < 2) sts16(sb + OFF_HID + c * 144 + (warp * 8 + g) * 2, pack2(gt * us, 0.f));
            }
            if (warp == 0) TS(26);
            bar_sync(1, 256);
            uint32_t bh[8];
            ldsm4(bh[0], bh[1], bh[2], bh[3], sb + OFF_HID + (lane & 1) * 144u + (lane >> 3) * 16u);
            ldsm4(bh[4], bh[5], bh[6], bh[7], sb + OFF_HID + (lane & 1) * 144u + (lane >> 3) * 16u + 64u);
            float y[4][4];
            #pragma unroll
            for (int tt = 0; tt < 4; tt++) { y[tt][0] = y[tt][1] = y[tt][2] = y[tt][3] = 0.f; }
            #pragma unroll
            for (int ks = 0; ks < 4; ks++)
                #pragma unroll
                for (int tt = 0; tt < 4; tt++) mma16816(y[tt], df[tt][ks][0], df[tt][ks][1], df[tt][ks][2], df[tt][ks][3], bh[2 * ks], bh[2 * ks + 1]);
            float e[4];
            #pragma unroll
            for (int i = 0; i < 4; i++) e[i] = (c & 2) ? ((c & 1) ? y[3][i] : y[2][i]) : ((c & 1) ? y[1][i] : y[0][i]);
            char* d = (char*)(p.s->yp + pr * 512 + rank * 128 + (warp * 4 + c) * 4) + g * 8;
            st_ll8(d, __float_as_uint(e[0]), low_bits(e[2], tag2));
            st_ll8(d + 4096, __float_as_uint(e[1]), low_bits(e[3], tag2));
            if (warp == 0) TS(27);
        }
    }
}

typedef CUresult (*EncodeFn)(CUtensorMap*, CUtensorMapDataType, cuuint32_t, void*, const cuuint64_t*, const cuuint64_t*, const cuuint32_t*,
                             const cuuint32_t*, CUtensorMapInterleave, CUtensorMapSwizzle, CUtensorMapL2promotion, CUtensorMapFloatOOBfill);

CUtensorMap make_map(EncodeFn enc, const void* ptr, uint64_t cols, uint64_t rows, uint32_t bc, uint32_t br, CUtensorMapSwizzle swz, CUtensorMapL2promotion promo) {
    CUtensorMap m;
    cuuint64_t dims[2] = {cols, rows}, strides[1] = {cols * 2};
    cuuint32_t box[2] = {bc, br}, es[2] = {1, 1};
    enc(&m, CU_TENSOR_MAP_DATA_TYPE_BFLOAT16, 2, const_cast<void*>(ptr), dims, strides, box, es, CU_TENSOR_MAP_INTERLEAVE_NONE, swz, promo,
        CU_TENSOR_MAP_FLOAT_OOB_FILL_NONE);
    return m;
}
CUtensorMap make_block_map(EncodeFn enc, const void* ptr, uint32_t sections, uint64_t rows, uint32_t br, CUtensorMapL2promotion promo) {
    CUtensorMap m;
    cuuint64_t dims[4] = {64, rows, 16, sections}, strides[3] = {sections * 2048ull, 128, 2048};
    cuuint32_t box[4] = {64, br, 2, sections}, es[4] = {1, 1, 1, 1};
    enc(&m, CU_TENSOR_MAP_DATA_TYPE_BFLOAT16, sections > 1 ? 4 : 3, const_cast<void*>(ptr), dims, strides, box, es, CU_TENSOR_MAP_INTERLEAVE_NONE,
        CU_TENSOR_MAP_SWIZZLE_128B, promo, CU_TENSOR_MAP_FLOAT_OOB_FILL_NONE);
    return m;
}

}

extern "C" void kernel_launch(void* const* d_in, const int* in_sizes, int n_in, void* d_out, int out_size) {
    (void)in_sizes; (void)n_in; (void)out_size;
    void* fn = nullptr; cudaDriverEntryPointQueryResult qr;
    cudaGetDriverEntryPoint("cuTensorMapEncodeTiled", &fn, cudaEnableDefault, &qr);
    EncodeFn enc = (EncodeFn)fn;
    void* hs = nullptr;
    cudaGetSymbolAddress(&hs, g_scratch);
    const CUtensorMapL2promotion P256 = CU_TENSOR_MAP_L2_PROMOTION_L2_256B, P128 = CU_TENSOR_MAP_L2_PROMOTION_L2_128B;
    CUtensorMap tmW = make_block_map(enc, d_in[1], 3, 1024, 64, P256);
    CUtensorMap tmWo = make_map(enc, d_in[3], 1024, 1024, 64, 64, CU_TENSOR_MAP_SWIZZLE_128B, P256);
    CUtensorMap tmPhi = make_map(enc, d_in[2], 32, 1024, 32, 128, CU_TENSOR_MAP_SWIZZLE_64B, P128);
    CUtensorMap tmG = make_map(enc, d_in[6], 3584, 1024, 64, 128, CU_TENSOR_MAP_SWIZZLE_128B, P128);
    CUtensorMap tmU = make_map(enc, d_in[7], 3584, 1024, 64, 128, CU_TENSOR_MAP_SWIZZLE_128B, P128);
    CUtensorMap tmD = make_block_map(enc, d_in[8], 1, 3584, 64, P128);
    CUtensorMap tmX = make_map(enc, d_in[0], 1024, 2048, 64, 128, CU_TENSOR_MAP_SWIZZLE_128B, P128);
    CUtensorMap tmO = make_block_map(enc, d_out, 1, 2048, 8, P128);
    CUtensorMap tmM = make_map(enc, d_in[10], 6144, 1024, 64, 32, CU_TENSOR_MAP_SWIZZLE_NONE, P128);
    CUtensorMap tmR = make_map(enc, d_in[10], 6144, 1024, 32, 64, CU_TENSOR_MAP_SWIZZLE_NONE, P128);
    CUtensorMap tmG8 = make_map(enc, d_in[6], 3584, 1024, 8, 64, CU_TENSOR_MAP_SWIZZLE_NONE, P128);
    CUtensorMap tmU8 = make_map(enc, d_in[7], 3584, 1024, 8, 64, CU_TENSOR_MAP_SWIZZLE_NONE, P128);
    CUtensorMap tmD8 = make_map(enc, d_in[8], 1024, 3584, 8, 64, CU_TENSOR_MAP_SWIZZLE_NONE, P128);
    Ptrs p;
    p.x = (const bf16*)d_in[0]; p.c = (const bf16*)d_in[9]; p.wmod = (const bf16*)d_in[10]; p.wr = (const bf16*)d_in[5];
    p.wg = (const bf16*)d_in[6]; p.wu = (const bf16*)d_in[7]; p.wd = (const bf16*)d_in[8]; p.out = (bf16*)d_out; p.s = (Scratch*)hs;
    p.wqkv = (const bf16*)d_in[1]; p.wo = (const bf16*)d_in[3];
    cudaFuncSetAttribute(fused_kernel, cudaFuncAttributeMaxDynamicSharedMemorySize, SMEM_BYTES);
    fused_kernel<<<128, NTHREADS, SMEM_BYTES, cudaStreamPerThread>>>(p, tmW, tmWo, tmPhi, tmG, tmU, tmD, tmX, tmO, tmM, tmR, tmG8, tmU8, tmD8);
}
```

```cpp
#include <cuda_runtime.h>
#include <cuda.h>
#include <cuda_bf16.h>
#include <stdint.h>

namespace {

typedef __nv_bfloat16 bf16;

constexpr int NTHREADS = 384;
constexpr int POLL_MAX = 400000;
constexpr uint32_t EMPTY = 0xffffffffu;

constexpr uint32_t OFF_RING = 0;
constexpr uint32_t OFF_XS   = 131072;
constexpr uint32_t OFF_WST  = 163840;
constexpr uint32_t OFF_XT   = 0;
constexpr uint32_t OFF_GA   = 32768;
constexpr uint32_t OFF_KVS  = 98304;
constexpr uint32_t OFF_PHI  = 114688;
constexpr uint32_t OFF_V    = 131072;
constexpr uint32_t OFF_DB   = 0;
constexpr uint32_t OFF_DA   = 98304;
constexpr uint64_t SLOT_A   = 0x1032541032541032ull, SLOT_B = 0x1054321054321054ull;
constexpr uint32_t PAR_A    = 0x3f00, PAR_B = 0x0fc0;
constexpr uint32_t OFF_OWN  = OFF_DA + 32768;
constexpr uint32_t OFF_OUT  = OFF_DA;
constexpr uint32_t OFF_UP0  = OFF_DA + 65536, OFF_UP1 = OFF_DB + 32768, OFF_DN0 = OFF_DA + 32768, OFF_DN1 = OFF_DB + 65536;
constexpr uint32_t OFF_WPHI = 196608;
constexpr uint32_t OFF_SP   = 204800;
constexpr uint32_t OFF_Z    = 221184;
constexpr uint32_t OFF_ONES = 225280;
constexpr uint32_t OFF_MODS = 226304;
constexpr uint32_t OFF_GB   = 196608;
constexpr uint32_t OFF_BQ   = 229376;
constexpr uint32_t OFF_ATOT = OFF_BQ + 256;
constexpr uint32_t OFF_BAR  = 230400;
constexpr uint32_t OFF_SEEN = OFF_BAR + 632;
constexpr uint32_t OFF_PAR  = OFF_BAR + 640;
constexpr uint32_t SMEM_BYTES = 232448;
constexpr uint32_t OFF_SILU = OFF_Z;
constexpr uint32_t OFF_RED0 = OFF_Z + 2048;
constexpr uint32_t OFF_ST2  = OFF_DB;
constexpr uint32_t OFF_KEYS = OFF_ST2 + 1024;
constexpr uint32_t OFF_SEL  = OFF_KEYS + 512;
constexpr uint32_t OFF_ROWS = OFF_ST2 + 2048;
constexpr uint32_t OFF_PX   = OFF_ROWS + 2560;
constexpr uint32_t OFF_HID  = OFF_PX + 1024;

enum {
    B_F1 = 0, B_E1 = 3, B_STFREE = 6, B_WPHI = 7, B_FA = 8, B_FB = 14, B_RF = 20, B_KVD = 24, B_PAR = 28, B_S0 = 29, B_GU = 30, B_WD = 31,
    B_X2 = 32, B_ST2 = 33, B_RD = 34, B_ROWS = 35,
    B_MP = 36, B_MOD = 37, B_PX = 53, B_NONE = 54, B_PHI = 55, B_OUTW = 63, B_PUB = 64, B_KVF = 66, B_OWN = 68, B_REL = 70,
    B_XS = 71,
    B_WS = 75, B_COUNT = 79,
    B_ED = B_MOD, B_S0FREE = B_NONE, B_KVS = B_XS, B_OGO = B_XS + 2, B_PF = B_XS + 3
};

struct Scratch {
    uint4 os[256 * 1024];
    uint4 kvp[32 * 256 * 32];
    uint4 kvf[32 * 288];
    uint4 st1[2048];
    uint4 mp[128 * 16];
    uint4 rest[1024];
    uint4 flo[256 * 2];
    uint4 st2[2048];
    uint4 cand[64 * 2];
    uint4 rowh[64 * 128];
    uint4 rowx[64 * 128];
    uint4 rsc[64 * 8 * 2];
    uint4 yp[56 * 512];
    unsigned done[4];
};
__device__ __align__(1024) Scratch g_scratch;
#define TS(i) do {} while (0)
#define TR(i)
#define TRL(i)
#define WT0()
#define WTJ(j)

__device__ __forceinline__ uint32_t smem_u32(const void* p) { return (uint32_t)__cvta_generic_to_shared(p); }
__device__ __forceinline__ uint32_t clk32() { uint32_t c; asm volatile("mov.u32 %0, %%clock;" : "=r"(c) :: "memory"); return c; }
__device__ __forceinline__ void arrive_one(uint32_t bar) {
    asm volatile("{\n.reg .pred p;\nelect.sync _|p, 0xffffffff;\n@p mbarrier.arrive.shared::cta.b64 _, [%0];\n}" :: "r"(bar) : "memory");
}
__device__ __forceinline__ void arrive_many(uint32_t bar, uint32_t n) {
    asm volatile("{\n.reg .pred p;\nelect.sync _|p, 0xffffffff;\n@p mbarrier.arrive.shared::cta.b64 _, [%0], %1;\n}" :: "r"(bar), "r"(n) : "memory");
}
__device__ __forceinline__ void arrive_if(uint32_t bar, uint32_t on) {
    asm volatile("{\n.reg .pred q, p;\nelect.sync _|q, 0xffffffff;\nsetp.ne.and.u32 p, %1, 0, q;\n@p mbarrier.arrive.shared::cta.b64 _, [%0];\n}" :: "r"(bar), "r"(on) : "memory");
}
__device__ __forceinline__ void arrive_both_if(uint32_t bar, uint32_t on) {
    asm volatile("{\n.reg .pred q, p;\n.reg .b32 r0, r1;\nelect.sync _|q, 0xffffffff;\nsetp.ne.and.u32 p, %1, 0, q;\n"
        "mapa.shared::cluster.u32 r0, %0, 0;\nmapa.shared::cluster.u32 r1, %0, 1;\n"
        "@p mbarrier.arrive.shared::cluster.b64 _, [r0];\n@p mbarrier.arrive.shared::cluster.b64 _, [r1];\n}" :: "r"(bar), "r"(on) : "memory");
}
__device__ __forceinline__ void st_partner128(uint32_t a, uint32_t bar, uint32_t cta, float x, float y, float z, float w) {
    asm volatile("{\n.reg .b32 ra, rb;\nmapa.shared::cluster.u32 ra, %0, %2;\nmapa.shared::cluster.u32 rb, %1, %2;\n"
        "st.async.weak.shared::cluster.mbarrier::complete_tx::bytes.v4.f32 [ra], {%3, %4, %5, %6}, [rb];\n}" :: "r"(a), "r"(bar), "r"(cta), "f"(x), "f"(y), "f"(z), "f"(w) : "memory");
}
__device__ __forceinline__ void mbar_wait(uint32_t bar, uint32_t parity) {
    asm volatile("{\n.reg .pred P1;\n.reg .u32 cnt;\nmov.u32 cnt, 0;\nLAB_WAIT:\n"
        "mbarrier.try_wait.parity.shared::cta.b64 P1, [%0], %1;\n@P1 bra DONE;\n"
        "add.u32 cnt, cnt, 1;\nsetp.lt.u32 P1, cnt, 1000000;\n@P1 bra LAB_WAIT;\ntrap;\nDONE:\n}" :: "r"(bar), "r"(parity) : "memory");
}
__device__ __forceinline__ uint64_t policy_evict_first() { uint64_t p; asm("createpolicy.fractional.L2::evict_first.b64 %0, 1.0;" : "=l"(p)); return p; }
#define EF_W 1
#define EF_WO 1
#define EF_F 1
#define EF_M 1
__device__ __forceinline__ void bulk_commit() { asm volatile("cp.async.bulk.commit_group;" ::: "memory"); }
__device__ __forceinline__ void bulk_wait() { asm volatile("cp.async.bulk.wait_group 0;" ::: "memory"); }
__device__ __forceinline__ void tmap_prefetch(const CUtensorMap* tm) { asm volatile("prefetch.tensormap [%0];" :: "l"(tm) : "memory"); }
#define EL "{\n.reg .pred e;\nelect.sync _|e, 0xffffffff;\n@e "
__device__ __forceinline__ void expect_tx_e(uint32_t bar, uint32_t bytes) { asm volatile(EL "mbarrier.arrive.expect_tx.shared::cta.b64 _, [%0], %1;\n}" :: "r"(bar), "r"(bytes) : "memory"); }
__device__ __forceinline__ void tma2_e(uint32_t dst, const CUtensorMap* tm, int c0, int c1, uint32_t bar) {
    asm volatile(EL "cp.async.bulk.tensor.2d.shared::cluster.global.mbarrier::complete_tx::bytes [%0], [%1, {%3, %4}], [%2];\n}"
        :: "r"(dst), "l"(tm), "r"(bar), "r"(c0), "r"(c1) : "memory");
}
__device__ __forceinline__ void tma2_ef_e(uint32_t dst, const CUtensorMap* tm, int c0, int c1, uint32_t bar) {
    asm volatile(EL "cp.async.bulk.tensor.2d.shared::cluster.global.mbarrier::complete_tx::bytes.L2::cache_hint [%0], [%1, {%3, %4}], [%2], %5;\n}"
        :: "r"(dst), "l"(tm), "r"(bar), "r"(c0), "r"(c1), "l"(policy_evict_first()) : "memory");
}
__device__ __forceinline__ void tma2_mc_e(uint32_t dst, const CUtensorMap* tm, int c0, int c1, uint32_t bar) {
    if (!EF_WO) asm volatile(EL "cp.async.bulk.tensor.2d.shared::cluster.global.mbarrier::complete_tx::bytes.multicast::cluster [%0], [%1, {%3, %4}], [%2], %5;\n}"
        :: "r"(dst), "l"(tm), "r"(bar), "r"(c0), "r"(c1), "h"((uint16_t)3) : "memory");
    else
    asm volatile(EL "cp.async.bulk.tensor.2d.shared::cluster.global.mbarrier::complete_tx::bytes.multicast::cluster.L2::cache_hint [%0], [%1, {%3, %4}], [%2], %5, %6;\n}"
        :: "r"(dst), "l"(tm), "r"(bar), "r"(c0), "r"(c1), "h"((uint16_t)3), "l"(policy_evict_first()) : "memory");
}
__device__ __forceinline__ void tma3_ef_e(uint32_t dst, const CUtensorMap* tm, int row, int blk, uint32_t bar) {
    if (!EF_F) asm volatile(EL "cp.async.bulk.tensor.3d.shared::cluster.global.mbarrier::complete_tx::bytes [%0], [%1, {0, %3, %4}], [%2];\n}"
        :: "r"(dst), "l"(tm), "r"(bar), "r"(row), "r"(blk) : "memory");
    else
    asm volatile(EL "cp.async.bulk.tensor.3d.shared::cluster.global.mbarrier::complete_tx::bytes.L2::cache_hint [%0], [%1, {0, %3, %4}], [%2], %5;\n}"
        :: "r"(dst), "l"(tm), "r"(bar), "r"(row), "r"(blk), "l"(policy_evict_first()) : "memory");
}
__device__ __forceinline__ void tma4_ef_e(uint32_t dst, const CUtensorMap* tm, int row, int blk, uint32_t bar) {
    if (!EF_W) asm volatile(EL "cp.async.bulk.tensor.4d.shared::cluster.global.mbarrier::complete_tx::bytes [%0], [%1, {0, %3, %4, 0}], [%2];\n}"
        :: "r"(dst), "l"(tm), "r"(bar), "r"(row), "r"(blk) : "memory");
    else
    asm volatile(EL "cp.async.bulk.tensor.4d.shared::cluster.global.mbarrier::complete_tx::bytes.L2::cache_hint [%0], [%1, {0, %3, %4, 0}], [%2], %5;\n}"
        :: "r"(dst), "l"(tm), "r"(bar), "r"(row), "r"(blk), "l"(policy_evict_first()) : "memory");
}
__device__ __forceinline__ void bulk_load_e(uint32_t dst, const void* src, uint32_t bytes, uint32_t bar) {
    asm volatile(EL "cp.async.bulk.shared::cluster.global.mbarrier::complete_tx::bytes [%0], [%1], %2, [%3];\n}" :: "r"(dst), "l"(src), "r"(bytes), "r"(bar) : "memory");
}
__device__ __forceinline__ void bulk_store_e(void* dst, uint32_t src, uint32_t bytes) {
    asm volatile(EL "cp.async.bulk.global.shared::cta.bulk_group [%0], [%1], %2;\n}" :: "l"(dst), "r"(src), "r"(bytes) : "memory");
}
__device__ __forceinline__ void st_flag_e(void* p, unsigned v) { asm volatile(EL "st.relaxed.gpu.global.u32 [%0], %1;\n}" :: "l"(p), "r"(v) : "memory"); }
__device__ __forceinline__ void mbar_init(uint32_t bar, uint32_t cnt) { asm volatile("mbarrier.init.shared::cta.b64 [%0], %1;" :: "r"(bar), "r"(cnt) : "memory"); }
__device__ __forceinline__ bool elect_one() {
    uint32_t p;
    asm volatile("{\n.reg .pred P;\nelect.sync _|P, 0xffffffff;\nselp.u32 %0, 1, 0, P;\n}" : "=r"(p));
    return p;
}
__device__ __forceinline__ void wg_fence() { asm volatile("wgmma.fence.sync.aligned;" ::: "memory"); }
__device__ __forceinline__ void wg_commit() { asm volatile("wgmma.commit_group.sync.aligned;" ::: "memory"); }
template<int N> __device__ __forceinline__ void wg_wait() { asm volatile("wgmma.wait_group.sync.aligned %0;" :: "n"(N) : "memory"); }
template<int N> __device__ __forceinline__ void acc_fence(float (&d)[N]) {
    #pragma unroll
    for (int i = 0; i < N; i++) asm volatile("" : "+f"(d[i]) :: "memory");
}
__device__ __forceinline__ uint64_t mk_desc(uint32_t addr, uint32_t lbo, uint32_t sbo, uint32_t swz) {
    uint32_t lo = ((addr & 0x3FFFF) >> 4) | (((lbo & 0x3FFFF) >> 4) << 16);
    uint32_t hi = (sbo >> 4) | (swz << 30);
    return ((uint64_t)hi << 32) | lo;
}
__device__ __forceinline__ uint64_t desc_add(uint64_t d, uint32_t bytes) { return (d & 0xffffffff00000000ull) | (uint32_t)((uint32_t)d + (bytes >> 4)); }
__device__ __forceinline__ uint64_t desc_raw(uint64_t d, uint32_t inc) { return (d & 0xffffffff00000000ull) | (uint32_t)((uint32_t)d + inc); }
__device__ __forceinline__ void fence_async_smem() { asm volatile("fence.proxy.async.shared::cta;" ::: "memory"); }
__device__ __forceinline__ void bar_sync(int id, int n) { asm volatile("bar.sync %0, %1;" :: "r"(id), "r"(n) : "memory"); }
__device__ __forceinline__ void bar_arrive(int id, int n) { asm volatile("bar.arrive %0, %1;" :: "r"(id), "r"(n) : "memory"); }
template<int R> __device__ __forceinline__ void reg_inc() { asm volatile("setmaxnreg.inc.sync.aligned.u32 %0;" :: "n"(R)); }
template<int R> __device__ __forceinline__ void reg_dec() { asm volatile("setmaxnreg.dec.sync.aligned.u32 %0;" :: "n"(R)); }
__device__ __forceinline__ void cluster_arrive() { asm volatile("barrier.cluster.arrive.relaxed.aligned;" ::: "memory"); }
__device__ __forceinline__ void cluster_wait() { asm volatile("barrier.cluster.wait.acquire.aligned;" ::: "memory"); }

__device__ __forceinline__ void stsm4(uint32_t addr, uint32_t r0, uint32_t r1, uint32_t r2, uint32_t r3) {
    asm volatile("stmatrix.sync.aligned.m8n8.x4.shared.b16 [%0], {%1,%2,%3,%4};" :: "r"(addr), "r"(r0), "r"(r1), "r"(r2), "r"(r3) : "memory");
}
__device__ __forceinline__ void ldsm4(uint32_t& r0, uint32_t& r1, uint32_t& r2, uint32_t& r3, uint32_t addr) {
    asm volatile("ldmatrix.sync.aligned.m8n8.x4.shared.b16 {%0,%1,%2,%3}, [%4];" : "=r"(r0), "=r"(r1), "=r"(r2), "=r"(r3) : "r"(addr) : "memory");
}
__device__ __forceinline__ void ldsm4t(uint32_t& r0, uint32_t& r1, uint32_t& r2, uint32_t& r3, uint32_t addr) {
    asm volatile("ldmatrix.sync.aligned.m8n8.x4.trans.shared.b16 {%0,%1,%2,%3}, [%4];" : "=r"(r0), "=r"(r1), "=r"(r2), "=r"(r3) : "r"(addr) : "memory");
}
__device__ __forceinline__ void mma16816(float (&d)[4], uint32_t a0, uint32_t a1, uint32_t a2, uint32_t a3, uint32_t b0, uint32_t b1) {
    asm("mma.sync.aligned.m16n8k16.row.col.f32.bf16.bf16.f32 {%0,%1,%2,%3}, {%4,%5,%6,%7}, {%8,%9}, {%0,%1,%2,%3};"
        : "+f"(d[0]), "+f"(d[1]), "+f"(d[2]), "+f"(d[3]) : "r"(a0), "r"(a1), "r"(a2), "r"(a3), "r"(b0), "r"(b1));
}
__device__ __forceinline__ uint4 lds128(uint32_t a) { uint4 v; asm volatile("ld.shared.v4.b32 {%0,%1,%2,%3}, [%4];" : "=r"(v.x), "=r"(v.y), "=r"(v.z), "=r"(v.w) : "r"(a) : "memory"); return v; }
__device__ __forceinline__ uint2 lds64(uint32_t a) { uint2 v; asm volatile("ld.shared.v2.b32 {%0,%1}, [%2];" : "=r"(v.x), "=r"(v.y) : "r"(a) : "memory"); return v; }
__device__ __forceinline__ uint32_t lds32(uint32_t a) { uint32_t v; asm volatile("ld.shared.b32 %0, [%1];" : "=r"(v) : "r"(a) : "memory"); return v; }
__device__ __forceinline__ float ldsf(uint32_t a) { float v; asm volatile("ld.shared.f32 %0, [%1];" : "=f"(v) : "r"(a) : "memory"); return v; }
__device__ __forceinline__ uint32_t lds16(uint32_t a) { uint16_t v; asm volatile("ld.shared.b16 %0, [%1];" : "=h"(v) : "r"(a) : "memory"); return v; }
__device__ __forceinline__ void sts128(uint32_t a, uint4 v) { asm volatile("st.shared.v4.b32 [%0], {%1,%2,%3,%4};" :: "r"(a), "r"(v.x), "r"(v.y), "r"(v.z), "r"(v.w) : "memory"); }
__device__ __forceinline__ void sts64(uint32_t a, uint32_t x, uint32_t y) { asm volatile("st.shared.v2.b32 [%0], {%1,%2};" :: "r"(a), "r"(x), "r"(y) : "memory"); }
__device__ __forceinline__ void sts32(uint32_t a, uint32_t x) { asm volatile("st.shared.b32 [%0], %1;" :: "r"(a), "r"(x) : "memory"); }
__device__ __forceinline__ void stsf(uint32_t a, float x) { asm volatile("st.shared.f32 [%0], %1;" :: "r"(a), "f"(x) : "memory"); }
__device__ __forceinline__ void sts16(uint32_t a, uint32_t x) { asm volatile("st.shared.b16 [%0], %1;" :: "r"(a), "h"((uint16_t)x) : "memory"); }

__device__ __forceinline__ uint2 ldg64(const void* p) { uint2 v; asm volatile("ld.global.nc.v2.b32 {%0,%1}, [%2];" : "=r"(v.x), "=r"(v.y) : "l"(p)); return v; }
__device__ __forceinline__ void stg128(void* p, uint4 v) { asm volatile("st.global.v4.b32 [%0], {%1,%2,%3,%4};" :: "l"(p), "r"(v.x), "r"(v.y), "r"(v.z), "r"(v.w) : "memory"); }
__device__ __forceinline__ void stg_fill(void* p, uint32_t v) { asm volatile("st.global.v4.b32 [%0], {%1,%1,%1,%1};" :: "l"(p), "r"(v) : "memory"); }
__device__ __forceinline__ void st_ll(void* p, uint32_t x, uint32_t y, uint32_t z, uint32_t w) {
    asm volatile("{\n.reg .b128 t;\n.reg .b64 a, b;\nmov.b64 a, {%1, %2};\nmov.b64 b, {%3, %4};\nmov.b128 t, {a, b};\nst.relaxed.gpu.global.b128 [%0], t;\n}"
        :: "l"(p), "r"(x), "r"(y), "r"(z), "r"(w) : "memory");
}
__device__ __forceinline__ uint4 ld_ll(const void* p) {
    uint4 v;
    asm volatile("{\n.reg .b128 t;\n.reg .b64 a, b;\nld.relaxed.gpu.global.b128 t, [%4];\nmov.b128 {a, b}, t;\nmov.b64 {%0, %1}, a;\nmov.b64 {%2, %3}, b;\n}"
        : "=r"(v.x), "=r"(v.y), "=r"(v.z), "=r"(v.w) : "l"(p) : "memory");
    return v;
}
__device__ __forceinline__ void ld_ll_if(uint4& v, const void* p, bool go) {
    asm volatile("{\n.reg .b128 t;\n.reg .b64 a, b;\n.reg .pred q;\nsetp.ne.u32 q, %5, 0;\nmov.b64 a, {%0, %1};\nmov.b64 b, {%2, %3};\nmov.b128 t, {a, b};\n"
        "@q ld.relaxed.gpu.global.b128 t, [%4];\nmov.b128 {a, b}, t;\nmov.b64 {%0, %1}, a;\nmov.b64 {%2, %3}, b;\n}"
        : "+r"(v.x), "+r"(v.y), "+r"(v.z), "+r"(v.w) : "l"(p), "r"((uint32_t)go) : "memory");
}
__device__ __forceinline__ void st_ll8(void* p, uint32_t x, uint32_t y) {
    asm volatile("{\n.reg .b64 a;\nmov.b64 a, {%1, %2};\nst.relaxed.gpu.global.b64 [%0], a;\n}" :: "l"(p), "r"(x), "r"(y) : "memory");
}
__device__ __forceinline__ void st_ll4(void* p, uint32_t x) { asm volatile("st.relaxed.gpu.global.b32 [%0], %1;" :: "l"(p), "r"(x) : "memory"); }
__device__ __forceinline__ unsigned ld_rlx(const void* p) { unsigned v; asm volatile("ld.relaxed.gpu.global.u32 %0, [%1];" : "=r"(v) : "l"(p) : "memory"); return v; }
__device__ __forceinline__ void red_add4(void* p, float x, float y, float z, float w) {
    asm volatile("red.relaxed.gpu.global.add.v4.f32 [%0], {%1, %2, %3, %4};" :: "l"(p), "f"(x), "f"(y), "f"(z), "f"(w) : "memory");
}
__device__ __forceinline__ void fence_rel_gpu() { asm volatile("fence.proxy.async.global;\nfence.release.gpu;" ::: "memory"); }
__device__ __forceinline__ void fence_acq_gpu() { asm volatile("fence.acquire.gpu;" ::: "memory"); }
template<int N> __device__ __forceinline__ void poll_words(uint4 (&v)[N], const uint4* p, int stride, uint32_t tag) {
    #pragma unroll 1
    for (int it = 0; it < POLL_MAX; it++) {
        bool ok = true;
        #pragma unroll
        for (int i = 0; i < N; i++) v[i] = ld_ll(p + i * stride);
        #pragma unroll
        for (int i = 0; i < N; i++) ok = ok && (v[i].w == tag);
        if (ok) break;
    }
}
template<int B> __device__ __forceinline__ uint32_t low_byte(float v, uint32_t src) { return __byte_perm(__float_as_uint(v), src, 0x3214 + B); }
__device__ __forceinline__ uint32_t low_bits(float v, uint32_t tag2) { return (__float_as_uint(v) & ~3u) | tag2; }
__device__ __forceinline__ bool tagged2(uint32_t w, uint32_t tag2) { return (w & 3u) == tag2; }
__device__ __forceinline__ uint32_t umax4(uint4 v) { return max(max(v.x, v.y), max(v.z, v.w)); }
constexpr uint32_t ONE2 = 0x3F803F80u;
__device__ __forceinline__ uint32_t pack2(float lo, float hi) { uint32_t d; asm("cvt.rn.bf16x2.f32 %0, %1, %2;" : "=r"(d) : "f"(hi), "f"(lo)); return d; }
__device__ __forceinline__ float bf_lo(uint32_t v) { return __uint_as_float(v << 16); }
__device__ __forceinline__ float bf_lo_alu(uint32_t v) { uint32_t d; asm("prmt.b32 %0, %1, 0, 0x1044;" : "=r"(d) : "r"(v)); return __uint_as_float(d); }
__device__ __forceinline__ float bf_hi(uint32_t v) { return __uint_as_float(v & 0xffff0000u); }
__device__ __forceinline__ float rbf(float x) { return bf_lo(pack2(x, 0.f)); }
__device__ __forceinline__ uint32_t hsub2(uint32_t a, uint32_t b) { uint32_t d; asm("sub.rn.bf16x2 %0, %1, %2;" : "=r"(d) : "r"(a), "r"(b)); return d; }
__device__ __forceinline__ uint32_t hadd2(uint32_t a, uint32_t b) { uint32_t d; asm("add.rn.bf16x2 %0, %1, %2;" : "=r"(d) : "r"(a), "r"(b)); return d; }
__device__ __forceinline__ uint32_t hmul2(uint32_t a, uint32_t b) { uint32_t d; asm("mul.rn.bf16x2 %0, %1, %2;" : "=r"(d) : "r"(a), "r"(b)); return d; }
__device__ __forceinline__ uint32_t hmax2(uint32_t a, uint32_t b) { uint32_t d; asm("max.bf16x2 %0, %1, %2;" : "=r"(d) : "r"(a), "r"(b)); return d; }
__device__ __forceinline__ uint32_t hmin2(uint32_t a, uint32_t b) { uint32_t d; asm("min.bf16x2 %0, %1, %2;" : "=r"(d) : "r"(a), "r"(b)); return d; }
__device__ __forceinline__ float ex2(float x) { float y; asm("ex2.approx.ftz.f32 %0, %1;" : "=f"(y) : "f"(x)); return y; }
__device__ __forceinline__ float rcp(float x) { float y; asm("rcp.approx.ftz.f32 %0, %1;" : "=f"(y) : "f"(x)); return y; }
__device__ __forceinline__ float shfl_x(float v, int m) { return __shfl_xor_sync(0xffffffffu, v, m); }
constexpr float LOG2E = 1.4426950408889634f;
__device__ __forceinline__ float sigmoidf(float x) { return rcp(1.0f + ex2(-LOG2E * x)); }
__device__ __forceinline__ uint32_t ln_pair(uint32_t x, uint32_t m2, float rinv, uint32_t a, uint32_t s) {
    uint32_t d = hsub2(x, m2);
    uint32_t n = pack2(bf_lo(d) * rinv, bf_hi(d) * rinv);
    return hadd2(hmul2(n, a), s);
}
struct Recip { uint32_t hi, lo; };
__device__ __forceinline__ Recip split_recip(float r) { Recip q; q.hi = pack2(r, r); const float l = r - bf_hi(q.hi); q.lo = pack2(l, l); return q; }
__device__ __forceinline__ uint32_t hdiv2(uint32_t n, Recip r) { uint32_t d; asm("fma.rn.bf16x2 %0, %1, %2, %3;" : "=r"(d) : "r"(n), "r"(r.hi), "r"(hmul2(n, r.lo))); return d; }
__device__ __forceinline__ uint32_t ln_pair(uint32_t x, uint32_t m2, Recip r, uint32_t a, uint32_t s) { return hadd2(hmul2(hdiv2(hsub2(x, m2), r), a), s); }
__device__ __forceinline__ void ln_final(float s1, float s2, uint32_t& m2, float& rinv) {
    const float mean = s1 * (1.0f / 1024.0f), var = fmaf(-mean, mean, s2 * (1.0f / 1024.0f));
    m2 = pack2(mean, mean);
    float sd;
    asm("sqrt.approx.ftz.f32 %0, %1;" : "=f"(sd) : "f"(rbf(rbf(fmaxf(var, 0.f)) + 1e-5f)));
    rinv = rcp(rbf(sd));
}
__device__ __forceinline__ uint32_t f2key(float f) { uint32_t u = __float_as_uint(f); return (u & 0x80000000u) ? ~u : (u | 0x80000000u); }

struct FmState { float cp, cn, sp, sn; };
__device__ __forceinline__ uint32_t fm_extrema(const uint32_t* p) {
    const uint32_t mx = hmax2(hmax2(p[0], p[2]), hmax2(p[4], p[6]));
    const uint32_t mn = hmin2(hmin2(p[0], p[2]), hmin2(p[4], p[6])) ^ 0x80008000u;
    return hmax2(__byte_perm(mx, mn, 0x5410), __byte_perm(mx, mn, 0x7632));
}
template<bool PREV, bool CUR, bool NEXT>
__device__ __forceinline__ void fm_slot(FmState& s, const float (&ep)[16], uint32_t* o, const uint32_t* p, float (&e)[16], const uint32_t* pn) {
    float psp = s.sp, psn = s.sn, rp = 0.f, rn = 0.f, sp = 0.f, sn = 0.f;
    uint32_t mm = 0;
    #pragma unroll
    for (int j = 0; j < 4; j++) {
        float a0 = 0.f, a1 = 0.f, b0 = 0.f, b1 = 0.f;
        if (CUR) {
            const float f0 = bf_lo_alu(p[2 * j]), f1 = bf_hi(p[2 * j]);
            a0 = fmaf(f0, LOG2E, s.cp); a1 = fmaf(f1, LOG2E, s.cp); b0 = fmaf(f0, -LOG2E, s.cn); b1 = fmaf(f1, -LOG2E, s.cn);
            e[2 * j] = ex2(a0);
        }
        if (PREV && j == 0) { psp += shfl_x(psp, 1); psn += shfl_x(psn, 1); }
        if (NEXT && j == 0) mm = fm_extrema(pn);
        if (PREV && j >= 2) { const float r = j == 2 ? rp : rn; o[8 * (j - 2)] = pack2(ep[8 * (j - 2)] * r, ep[8 * (j - 2) + 1] * r); }
        if (CUR) e[2 * j + 1] = ex2(a1);
        if (NEXT && j == 0) mm = hmax2(mm, __shfl_xor_sync(0xffffffffu, mm, 1));
        if (PREV && j == 1) { const float r = rcp(psp * psn); rp = r * psn; rn = r * psp; }
        if (PREV && j >= 2) { const float r = j == 2 ? rp : rn; o[8 * (j - 2) + 2] = pack2(ep[8 * (j - 2) + 2] * r, ep[8 * (j - 2) + 3] * r); }
        if (CUR && j >= 1) sp = j == 1 ? e[0] + e[1] : (sp + e[2 * j - 2]) + e[2 * j - 1];
        if (CUR) e[8 + 2 * j] = ex2(b0);
        if (PREV && j == 0) { psp += shfl_x(psp, 2); psn += shfl_x(psn, 2); }
        if (NEXT && j == 1) mm = hmax2(mm, __shfl_xor_sync(0xffffffffu, mm, 2));
        if (PREV && j >= 2) { const float r = j == 2 ? rp : rn; o[8 * (j - 2) + 4] = pack2(ep[8 * (j - 2) + 4] * r, ep[8 * (j - 2) + 5] * r); }
        if (CUR) e[9 + 2 * j] = ex2(b1);
        if (PREV && j >= 2) { const float r = j == 2 ? rp : rn; o[8 * (j - 2) + 6] = pack2(ep[8 * (j - 2) + 6] * r, ep[8 * (j - 2) + 7] * r); }
        if (CUR && j >= 1) sn = j == 1 ? e[8] + e[9] : (sn + e[6 + 2 * j]) + e[7 + 2 * j];
    }
    if (NEXT) { s.cp = -bf_lo(mm) * LOG2E; s.cn = -bf_hi(mm) * LOG2E; }
    if (CUR) { s.sp = (sp + e[6]) + e[7]; s.sn = (sn + e[14]) + e[15]; }
}
template<int TB> __device__ __forceinline__ void wgmma_n32_rs(float (&d)[16], uint32_t a0, uint32_t a1, uint32_t a2, uint32_t a3, uint64_t db, int sc) {
  asm volatile("{\n.reg .pred p;\nsetp.ne.b32 p, %21, 0;\n"
    "wgmma.mma_async.sync.aligned.m64n32k16.f32.bf16.bf16 {%0, %1, %2, %3, %4, %5, %6, %7, %8, %9, %10, %11, %12, %13, %14, %15}, {%16,%17,%18,%19}, %20, p, 1, 1, %22;\n}\n"
    : "+f"(d[0]), "+f"(d[1]), "+f"(d[2]), "+f"(d[3]), "+f"(d[4]), "+f"(d[5]), "+f"(d[6]), "+f"(d[7]), "+f"(d[8]), "+f"(d[9]), "+f"(d[10]), "+f"(d[11]), "+f"(d[12]), "+f"(d[13]), "+f"(d[14]), "+f"(d[15])
    : "r"(a0), "r"(a1), "r"(a2), "r"(a3), "l"(db), "r"(sc), "n"(TB));
}
template<int TA, int TB> __device__ __forceinline__ void wgmma_n40_ss(float (&d)[20], uint64_t da, uint64_t db, int sc) {
  asm volatile("{\n.reg .pred p;\nsetp.ne.b32 p, %22, 0;\n"
    "wgmma.mma_async.sync.aligned.m64n40k16.f32.bf16.bf16 {%0, %1, %2, %3, %4, %5, %6, %7, %8, %9, %10, %11, %12, %13, %14, %15, %16, %17, %18, %19}, %20, %21, p, 1, 1, %23, %24;\n}\n"
    : "+f"(d[0]), "+f"(d[1]), "+f"(d[2]), "+f"(d[3]), "+f"(d[4]), "+f"(d[5]), "+f"(d[6]), "+f"(d[7]), "+f"(d[8]), "+f"(d[9]), "+f"(d[10]), "+f"(d[11]), "+f"(d[12]), "+f"(d[13]), "+f"(d[14]), "+f"(d[15]), "+f"(d[16]), "+f"(d[17]), "+f"(d[18]), "+f"(d[19])
    : "l"(da), "l"(db), "r"(sc), "n"(TA), "n"(TB));
}
template<int TA, int TB> __device__ __forceinline__ void wgmma_n128_ss(float (&d)[64], uint64_t da, uint64_t db, int sc) {
  asm volatile("{\n.reg .pred p;\nsetp.ne.b32 p, %66, 0;\n"
    "wgmma.mma_async.sync.aligned.m64n128k16.f32.bf16.bf16 {%0, %1, %2, %3, %4, %5, %6, %7, %8, %9, %10, %11, %12, %13, %14, %15, %16, %17, %18, %19, %20, %21, %22, %23, %24, %25, %26, %27, %28, %29, %30, %31, %32, %33, %34, %35, %36, %37, %38, %39, %40, %41, %42, %43, %44, %45, %46, %47, %48, %49, %50, %51, %52, %53, %54, %55, %56, %57, %58, %59, %60, %61, %62, %63}, %64, %65, p, 1, 1, %67, %68;\n}\n"
    : "+f"(d[0]), "+f"(d[1]), "+f"(d[2]), "+f"(d[3]), "+f"(d[4]), "+f"(d[5]), "+f"(d[6]), "+f"(d[7]), "+f"(d[8]), "+f"(d[9]), "+f"(d[10]), "+f"(d[11]), "+f"(d[12]), "+f"(d[13]), "+f"(d[14]), "+f"(d[15]), "+f"(d[16]), "+f"(d[17]), "+f"(d[18]), "+f"(d[19]), "+f"(d[20]), "+f"(d[21]), "+f"(d[22]), "+f"(d[23]), "+f"(d[24]), "+f"(d[25]), "+f"(d[26]), "+f"(d[27]), "+f"(d[28]), "+f"(d[29]), "+f"(d[30]), "+f"(d[31]), "+f"(d[32]), "+f"(d[33]), "+f"(d[34]), "+f"(d[35]), "+f"(d[36]), "+f"(d[37]), "+f"(d[38]), "+f"(d[39]), "+f"(d[40]), "+f"(d[41]), "+f"(d[42]), "+f"(d[43]), "+f"(d[44]), "+f"(d[45]), "+f"(d[46]), "+f"(d[47]), "+f"(d[48]), "+f"(d[49]), "+f"(d[50]), "+f"(d[51]), "+f"(d[52]), "+f"(d[53]), "+f"(d[54]), "+f"(d[55]), "+f"(d[56]), "+f"(d[57]), "+f"(d[58]), "+f"(d[59]), "+f"(d[60]), "+f"(d[61]), "+f"(d[62]), "+f"(d[63])
    : "l"(da), "l"(db), "r"(sc), "n"(TA), "n"(TB));
}
template<int TB> __device__ __forceinline__ void wgmma_n128_rs(float (&d)[64], uint32_t a0, uint32_t a1, uint32_t a2, uint32_t a3, uint64_t db, int sc) {
  asm volatile("{\n.reg .pred p;\nsetp.ne.b32 p, %69, 0;\n"
    "wgmma.mma_async.sync.aligned.m64n128k16.f32.bf16.bf16 {%0, %1, %2, %3, %4, %5, %6, %7, %8, %9, %10, %11, %12, %13, %14, %15, %16, %17, %18, %19, %20, %21, %22, %23, %24, %25, %26, %27, %28, %29, %30, %31, %32, %33, %34, %35, %36, %37, %38, %39, %40, %41, %42, %43, %44, %45, %46, %47, %48, %49, %50, %51, %52, %53, %54, %55, %56, %57, %58, %59, %60, %61, %62, %63}, {%64,%65,%66,%67}, %68, p, 1, 1, %70;\n}\n"
    : "+f"(d[0]), "+f"(d[1]), "+f"(d[2]), "+f"(d[3]), "+f"(d[4]), "+f"(d[5]), "+f"(d[6]), "+f"(d[7]), "+f"(d[8]), "+f"(d[9]), "+f"(d[10]), "+f"(d[11]), "+f"(d[12]), "+f"(d[13]), "+f"(d[14]), "+f"(d[15]), "+f"(d[16]), "+f"(d[17]), "+f"(d[18]), "+f"(d[19]), "+f"(d[20]), "+f"(d[21]), "+f"(d[22]), "+f"(d[23]), "+f"(d[24]), "+f"(d[25]), "+f"(d[26]), "+f"(d[27]), "+f"(d[28]), "+f"(d[29]), "+f"(d[30]), "+f"(d[31]), "+f"(d[32]), "+f"(d[33]), "+f"(d[34]), "+f"(d[35]), "+f"(d[36]), "+f"(d[37]), "+f"(d[38]), "+f"(d[39]), "+f"(d[40]), "+f"(d[41]), "+f"(d[42]), "+f"(d[43]), "+f"(d[44]), "+f"(d[45]), "+f"(d[46]), "+f"(d[47]), "+f"(d[48]), "+f"(d[49]), "+f"(d[50]), "+f"(d[51]), "+f"(d[52]), "+f"(d[53]), "+f"(d[54]), "+f"(d[55]), "+f"(d[56]), "+f"(d[57]), "+f"(d[58]), "+f"(d[59]), "+f"(d[60]), "+f"(d[61]), "+f"(d[62]), "+f"(d[63])
    : "r"(a0), "r"(a1), "r"(a2), "r"(a3), "l"(db), "r"(sc), "n"(TB));
}
template<int TB> __device__ __forceinline__ void wgmma_n256_rs(float (&d)[128], uint32_t a0, uint32_t a1, uint32_t a2, uint32_t a3, uint64_t db, int sc) {
  asm volatile("{\n.reg .pred p;\nsetp.ne.b32 p, %133, 0;\n"
    "wgmma.mma_async.sync.aligned.m64n256k16.f32.bf16.bf16 {%0, %1, %2, %3, %4, %5, %6, %7, %8, %9, %10, %11, %12, %13, %14, %15, %16, %17, %18, %19, %20, %21, %22, %23, %24, %25, %26, %27, %28, %29, %30, %31, %32, %33, %34, %35, %36, %37, %38, %39, %40, %41, %42, %43, %44, %45, %46, %47, %48, %49, %50, %51, %52, %53, %54, %55, %56, %57, %58, %59, %60, %61, %62, %63, %64, %65, %66, %67, %68, %69, %70, %71, %72, %73, %74, %75, %76, %77, %78, %79, %80, %81, %82, %83, %84, %85, %86, %87, %88, %89, %90, %91, %92, %93, %94, %95, %96, %97, %98, %99, %100, %101, %102, %103, %104, %105, %106, %107, %108, %109, %110, %111, %112, %113, %114, %115, %116, %117, %118, %119, %120, %121, %122, %123, %124, %125, %126, %127}, {%128,%129,%130,%131}, %132, p, 1, 1, %134;\n}\n"
    : "+f"(d[0]), "+f"(d[1]), "+f"(d[2]), "+f"(d[3]), "+f"(d[4]), "+f"(d[5]), "+f"(d[6]), "+f"(d[7]), "+f"(d[8]), "+f"(d[9]), "+f"(d[10]), "+f"(d[11]), "+f"(d[12]), "+f"(d[13]), "+f"(d[14]), "+f"(d[15]), "+f"(d[16]), "+f"(d[17]), "+f"(d[18]), "+f"(d[19]), "+f"(d[20]), "+f"(d[21]), "+f"(d[22]), "+f"(d[23]), "+f"(d[24]), "+f"(d[25]), "+f"(d[26]), "+f"(d[27]), "+f"(d[28]), "+f"(d[29]), "+f"(d[30]), "+f"(d[31]), "+f"(d[32]), "+f"(d[33]), "+f"(d[34]), "+f"(d[35]), "+f"(d[36]), "+f"(d[37]), "+f"(d[38]), "+f"(d[39]), "+f"(d[40]), "+f"(d[41]), "+f"(d[42]), "+f"(d[43]), "+f"(d[44]), "+f"(d[45]), "+f"(d[46]), "+f"(d[47]), "+f"(d[48]), "+f"(d[49]), "+f"(d[50]), "+f"(d[51]), "+f"(d[52]), "+f"(d[53]), "+f"(d[54]), "+f"(d[55]), "+f"(d[56]), "+f"(d[57]), "+f"(d[58]), "+f"(d[59]), "+f"(d[60]), "+f"(d[61]), "+f"(d[62]), "+f"(d[63]), "+f"(d[64]), "+f"(d[65]), "+f"(d[66]), "+f"(d[67]), "+f"(d[68]), "+f"(d[69]), "+f"(d[70]), "+f"(d[71]), "+f"(d[72]), "+f"(d[73]), "+f"(d[74]), "+f"(d[75]), "+f"(d[76]), "+f"(d[77]), "+f"(d[78]), "+f"(d[79]), "+f"(d[80]), "+f"(d[81]), "+f"(d[82]), "+f"(d[83]), "+f"(d[84]), "+f"(d[85]), "+f"(d[86]), "+f"(d[87]), "+f"(d[88]), "+f"(d[89]), "+f"(d[90]), "+f"(d[91]), "+f"(d[92]), "+f"(d[93]), "+f"(d[94]), "+f"(d[95]), "+f"(d[96]), "+f"(d[97]), "+f"(d[98]), "+f"(d[99]), "+f"(d[100]), "+f"(d[101]), "+f"(d[102]), "+f"(d[103]), "+f"(d[104]), "+f"(d[105]), "+f"(d[106]), "+f"(d[107]), "+f"(d[108]), "+f"(d[109]), "+f"(d[110]), "+f"(d[111]), "+f"(d[112]), "+f"(d[113]), "+f"(d[114]), "+f"(d[115]), "+f"(d[116]), "+f"(d[117]), "+f"(d[118]), "+f"(d[119]), "+f"(d[120]), "+f"(d[121]), "+f"(d[122]), "+f"(d[123]), "+f"(d[124]), "+f"(d[125]), "+f"(d[126]), "+f"(d[127])
    : "r"(a0), "r"(a1), "r"(a2), "r"(a3), "l"(db), "r"(sc), "n"(TB));
}

#define T_S0 3300
#define T_S1 5000
#define G1W 1
#define LNP 1
#define CG1 232
#define JU 2
#define WPF 0
#define FPF 0
#define SGATE 2
#define T_P0 1500
#define T_P1 3000
#define LATEFREE 1
#define NC 2
#define T_W1 2800
#define T_WD 0
#define NW0 32
#define PFN 3
#define PFJ 2
#define PFM 4
#define WOJ 10
#define WON 1
#define NLD 1
#define VFIRST 2
#define T_X0 450
#define T_XD 600
#define MCB 1
#define ORIENT 2
#define PFORDER 0x51634
#define PFORDER2 0x51
#define PFW0 2
#define CLRJ 3
#define CLRK 8
#define JPF 0
#define CLRGATE (B_FB + 4)
#define KVC0 0
#define CLRS 50
#define OGATE 5
#define PFD 0
#define GBN 6
#define BG1 99
#define BG2 99
#define BG3 99
#define BG4 99
#define BG5 99
#define SYNCQ 640
#define SYNCG 4
#define BSP 0
#define T_INI 500
#define T_WLATE 4000
#define T_REST 7000
#define T_COL 3000
#define PF_START 9000
#define PF_FIRST 2
#define PFP 400
#define CREG 208
#define TMA_WO tma2_ef_e
#define TMA_M tma2_ef_e
#define TMA_F tma2_ef_e
#define JUN 4
constexpr int JUU = JUN;
struct Ptrs { const bf16 *x, *c, *wmod, *wr, *wg, *wu, *wd, *wqkv, *wo; bf16* out; Scratch* s; };

#define BAR(i) (sb + OFF_BAR + 8u * (i))

__device__ __forceinline__ int d_block(int hg, int n) {
    const int m = n - (n >= 9 ? 9 : 2);
    return n < 2 ? 2 * hg + n : 2 * (m + (m >= hg)) + (n >= 9);
}
__host__ __device__ constexpr uint32_t bar_count(int i) {
    return (MCB && i >= B_ED && i < B_ED + 16) ? 16 : ((i >= B_E1 && i < B_E1 + 3) || (i >= B_NONE && i < B_PHI + 8) || i == B_OWN || i == B_OWN + 1 || (i >= B_ED && i < B_ED + 16)
            || i == B_STFREE || i == B_X2 || i == B_OUTW) ? 8
         : ((i >= B_KVD && i < B_KVD + 4) || i == B_ST2 || i == B_RD) ? 4 : (i == B_KVF || i == B_KVF + 1 ) ? 2 : 1;
}
template<int I0, int I1> __device__ __forceinline__ void init_barriers(uint32_t sb) {
    #pragma unroll
    for (int i = I0; i < I1; i++) mbar_init(BAR(i), bar_count(i));
}
template<int N> __device__ __forceinline__ uint32_t pop_max(uint32_t (&k)[N]) {
    uint32_t m = k[0];
    #pragma unroll
    for (int i = 1; i < N; i++) m = max(m, k[i]);
    m = __reduce_max_sync(0xffffffffu, m);
    #pragma unroll
    for (int i = 0; i < N; i++) k[i] = (k[i] == m) ? 0u : k[i];
    return m;
}
__device__ __forceinline__ uint32_t mod_pos(int step, int g) { return step * 64 + (g >> 1) * 16 + (g & 1) * 4; }
__device__ __forceinline__ void fma8(float (&a)[8], uint4 w, float s) {
    a[0] = fmaf(bf_lo(w.x), s, a[0]); a[1] = fmaf(bf_hi(w.x), s, a[1]); a[2] = fmaf(bf_lo(w.y), s, a[2]); a[3] = fmaf(bf_hi(w.y), s, a[3]);
    a[4] = fmaf(bf_lo(w.z), s, a[4]); a[5] = fmaf(bf_hi(w.z), s, a[5]); a[6] = fmaf(bf_lo(w.w), s, a[6]); a[7] = fmaf(bf_hi(w.w), s, a[7]);
}
__device__ __forceinline__ float reduce8(const float (&v)[8], int lane) {
    const bool b3 = lane & 16, b2 = lane & 8, b1 = lane & 4;
    float a[4], b[2];
    #pragma unroll
    for (int i = 0; i < 4; i++) { float keep = b3 ? v[4 + i] : v[i], send = b3 ? v[i] : v[4 + i]; a[i] = keep + shfl_x(send, 16); }
    #pragma unroll
    for (int i = 0; i < 2; i++) { float keep = b2 ? a[2 + i] : a[i], send = b2 ? a[i] : a[2 + i]; b[i] = keep + shfl_x(send, 8); }
    float keep = b1 ? b[1] : b[0], send = b1 ? b[0] : b[1];
    return keep + shfl_x(send, 4);
}
__device__ __forceinline__ bool mod_collect(uint4 w0, uint4 w1, uint4 w2, uint4 w3, uint32_t sb, int jb, int lane, uint32_t tag2) {
    const uint32_t add = lane < 16 ? ONE2 : 0u;
    const uint32_t lo = pack2((__uint_as_float(w0.x) + __uint_as_float(w1.x)) + (__uint_as_float(w2.x) + __uint_as_float(w3.x)),
                              (__uint_as_float(w0.y) + __uint_as_float(w1.y)) + (__uint_as_float(w2.y) + __uint_as_float(w3.y)));
    const uint32_t hi = pack2((__uint_as_float(w0.z) + __uint_as_float(w1.z)) + (__uint_as_float(w2.z) + __uint_as_float(w3.z)),
                              (__uint_as_float(w0.w) + __uint_as_float(w1.w)) + (__uint_as_float(w2.w) + __uint_as_float(w3.w)));
    sts64(sb + OFF_MODS + jb * 256 + (lane & 15) * 16 + (lane >> 4) * 8, hadd2(lo, add), hadd2(hi, add));
    return tagged2(w0.w, tag2) && tagged2(w1.w, tag2) && tagged2(w2.w, tag2) && tagged2(w3.w, tag2);
}
__device__ __forceinline__ void phi_issue(float (&pp)[2][16], const uint32_t* a, uint32_t sb, int pair) {
    const uint64_t dw = mk_desc(sb + OFF_WPHI + pair * 4096, 16, 512, 2);
    wg_fence();
    #pragma unroll
    for (int ks = 0; ks < 2; ks++)
        #pragma unroll
        for (int h = 0; h < 2; h++) wgmma_n32_rs<1>(pp[h], a[8 * h + 4 * ks], a[8 * h + 4 * ks + 1], a[8 * h + 4 * ks + 2], a[8 * h + 4 * ks + 3], desc_add(dw, h * 2048 + ks * 1024), ks);
    wg_commit();
}
__device__ __forceinline__ uint32_t phi_tile(int i) { return OFF_PHI + ((0x432130434ull >> (4 * i + 4)) & 7) * 16384u; }
__device__ __forceinline__ void phi_store(const uint32_t (&ph)[16], uint32_t sb, uint32_t aoff, int i) {
    #pragma unroll
    for (int q = 0; q < 4; q++) stsm4(sb + phi_tile(i) + (aoff ^ (q << 5)), ph[4 * q], ph[4 * q + 1], ph[4 * q + 2], ph[4 * q + 3]);
    __syncwarp();
    arrive_one(BAR(B_PHI + i));
}

__global__ void __cluster_dims__(2, 1, 1) __launch_bounds__(NTHREADS, 1)
fused_kernel(const Ptrs p, const __grid_constant__ CUtensorMap tmW, const __grid_constant__ CUtensorMap tmWo, const __grid_constant__ CUtensorMap tmPhi,
             const __grid_constant__ CUtensorMap tmG, const __grid_constant__ CUtensorMap tmU, const __grid_constant__ CUtensorMap tmD,
             const __grid_constant__ CUtensorMap tmX, const __grid_constant__ CUtensorMap tmO, const __grid_constant__ CUtensorMap tmM,
             const __grid_constant__ CUtensorMap tmR, const __grid_constant__ CUtensorMap tmG8, const __grid_constant__ CUtensorMap tmU8,
             const __grid_constant__ CUtensorMap tmD8)
{
    extern __shared__ __align__(1024) uint8_t smem_raw[];
    const uint32_t sb = smem_u32(smem_raw);
    const int tid = threadIdx.x, lane = tid & 31, warp = __shfl_sync(0xffffffffu, tid >> 5, 0);
    const int b = blockIdx.x;
    const int pr = b >> 1, rank = b & 1;
    const int cls = pr < 4 ? 15 : pr < 36 ? 2 * ((pr - 4) & 7) : 2 * ((pr - 36) % 7) + 1, mem = pr < 4 ? pr : pr < 36 ? (pr - 4) >> 3 : (pr - 36) / 7;
    const int hg = (((cls + 1) >> 1) & 1) * 4 + mem, rb = (cls >> 1) * 2 + rank;
    const bool ffn = b < 112;
    const uint32_t cstart = clk32();

    if (warp >= 8) {
        const int t = tid & 127, w4 = warp & 3, g = lane >> 2, c = lane & 3;
        if (w4 == 0) TS(40);
        reg_dec<504 - 2 * CG1>();
        if (w4 == 2) TS(41);
        if (w4 == 0) { tmap_prefetch(&tmX); tmap_prefetch(&tmW); }
        if (w4 == 3) tmap_prefetch(&tmM);
        if (w4 < 2) while (clk32() - cstart < T_INI) {}
        if (elect_one()) {
            if (w4 & 2) { if (w4 & 1) init_barriers<B_WS, B_COUNT>(sb); else init_barriers<B_XS, B_WS>(sb); }
            else { if (w4 & 1) init_barriers<B_MP, B_XS>(sb); else init_barriers<0, B_MP>(sb); }
        }
        __syncwarp();
        if (w4 == 1) {
            asm volatile("fence.mbarrier_init.release.cluster;" ::: "memory");
            expect_tx_e(BAR(B_PX), 1024); sts32(sb + OFF_SEEN, 0);
        }
        if (w4 == 0) TS(42);
        bar_arrive(0, 384);
        if (w4 == 2) {
            #pragma unroll 1
            for (int i = 0; i < 4; i++) {
                while (clk32() - cstart < T_X0 + i * T_XD) {}
                bulk_load_e(sb + OFF_XS + i * 8192u, p.x + (size_t)(b * 16 + i * 4) * 1024, 8192, BAR(B_XS + i));
                expect_tx_e(BAR(B_XS + i), 8192);
                if (i == 0) TS(43);
            }
        }
        if (w4 == 3 && b < 32 * NC) {
            while (b >= NW0 && clk32() - cstart < T_W1 + (b >> 5) * T_WD) {}
            #pragma unroll 1
            for (int i = 0; i < 4; i++) {
                tma2_ef_e(sb + OFF_WST + i * 8192u, &tmM, (((b >> 2) & 1) ? 0 : 1024) + (b >> 3) * 64, (b & 3) * 256 + i * 64, BAR(B_WS + i));
                expect_tx_e(BAR(B_WS + i), 8192);
            }
            TS(44);
        }
        cluster_arrive();
        const uint32_t tag = ld_rlx(p.s->done) + 1, tag2 = tag % 3u;
        if (w4 == 0) {
            int piece = ffn ? 0 : 20;
            uint4* clr = p.s->kvp + (hg * 1024 + KVC0 * 128 + rb) * 32 + lane;
            #pragma unroll 1
            for (int j = 0; j < 3; j++) {
                while (clk32() - cstart < (j ? T_P1 : T_P0)) {}
                if (lane < 24) asm volatile("prefetch.global.L2 [%0];" :: "l"((const char*)p.wqkv + ((j * 128 + b) * 24 + lane) * 128));
            }
            int s = 0;
            #pragma unroll 1
            for (int j = 0; j < 17; j++) {
                if (j >= 3) mbar_wait(BAR(B_E1 + s), ((j / 3) - 1) & 1);
                else if (j >= SGATE) mbar_wait(BAR(B_STFREE), 0);
                else while (clk32() - cstart < (j ? T_S1 : T_S0)) {}
                const uint32_t st = sb + OFF_RING + s * 65536u;
                if (j < 16) {
                    expect_tx_e(BAR(B_F1 + s), 65536);
                    tma4_ef_e(st + 16384u, &tmW, j * 64, hg * 2, BAR(B_F1 + s));
                    tma2_e(st, &tmX, j * 64, rb * 128, BAR(B_F1 + s));
                } else {
                    #pragma unroll 1
                    for (int n = 0; n < 4; n++) {
                        if (!(n & 1)) expect_tx_e(BAR(B_FB + 4 + (n >> 1)), 16384);
                        TMA_WO(st + n * 8192u, &tmWo, hg * 128 + (n & 1) * 64, (2 * hg + (n >> 1)) * 64, BAR(B_FB + 4 + (n >> 1)));
                    }
                }
                if (j == 1) TS(50);
                s = s == 2 ? 0 : s + 1;
                if (j == 3) expect_tx_e(BAR(B_PF), ffn ? 20480 : 0);
                #pragma unroll 1
                for (; j >= 3 && piece < min(20, j < 16 ? (j - PFJ) * PFM / 4 : 20); piece++)
                    tma2_e(sb + OFF_PAR, piece < 8 ? &tmD8 : piece < 16 ? &tmU8 : &tmG8, piece < 8 ? rank * 512 + piece * 64 : pr * 64,
                           piece < 8 ? pr * 64 : rank * 512 + (piece < 16 ? piece - 8 : piece - 12) * 64, BAR(B_PF));
                if (j >= WOJ && j < WOJ + 4 * WON) asm volatile("prefetch.global.L2 [%0];" :: "l"((const char*)p.wo + ((j - WOJ) & 3) * 524288 + (b * 32 + lane) * 128));
                if (j >= CLRJ && j < CLRJ + 8 - KVC0) {
                    #pragma unroll
                    for (int i = 0; i < 8; i++) stg_fill(clr + i * 512, EMPTY);
                    clr += 4096;
                }
            }
            mbar_wait(BAR(B_E1 + 0), 1);
            expect_tx_e(BAR(B_S0), ffn ? 65536 : 32768);
            tma2_ef_e(sb + OFF_XT, &tmX, hg * 128, rb * 128, BAR(B_S0)); tma2_ef_e(sb + OFF_XT + 16384u, &tmX, hg * 128 + 64, rb * 128, BAR(B_S0));
            #pragma unroll 1
            for (int i = 0; i < (ffn ? 2 : 0); i++) tma2_ef_e(sb + OFF_GA + i * 16384u, &tmG, pr * 64, rank * 512 + i * 128, BAR(B_S0));
        } else if (w4 == 1) {
            while (clk32() - cstart < T_COL) {}
            #pragma unroll 1
            for (int it = 0, jb = 0, ph = 0; it < POLL_MAX && jb < 16; it++) {
                const int n = jb < NLD ? 1 : min(4, 16 - jb);
                if (jb >= NLD) {
                    expect_tx_e(BAR(B_MP), n * 2048);
                    bulk_load_e(sb + OFF_WPHI, p.s->mp + jb * 128, n * 2048, BAR(B_MP));
                    mbar_wait(BAR(B_MP), ph);
                    ph ^= 1;
                }
                #pragma unroll 1
                for (int q = 0; q < n; q++) {
                    uint4 w[4];
                    if (jb < NLD) {
                        #pragma unroll
                        for (int i = 0; i < 4; i++) w[i] = ld_ll(p.s->mp + (jb * 8 + (lane >> 4) * 4 + i) * 16 + (lane & 15));
                    } else {
                        #pragma unroll
                        for (int i = 0; i < 4; i++) w[i] = lds128(sb + OFF_WPHI + q * 2048 + (lane >> 4) * 1024 + (lane & 15) * 16 + i * 256);
                    }
                    if (!__all_sync(0xffffffffu, mod_collect(w[0], w[1], w[2], w[3], sb, jb, lane, tag2))) { if (jb >= 4) __nanosleep(300); break; }
                    arrive_many(BAR(B_MOD + jb), bar_count(B_MOD));
                    if (jb == 0) TS(51);
                    if (jb == 4) TS(5);
                    if (jb == 15) TS(8);
                    jb++;
                }
            }
            fence_async_smem();
            __syncwarp();
            expect_tx_e(BAR(B_WPHI), 8192);
            tma2_e(sb + OFF_WPHI, &tmPhi, 0, hg * 128, BAR(B_WPHI));
            #pragma unroll 1
            for (int i = 0; i < 4; i++) {
                stg_fill(p.s->rowh + (lane >> 4) * 8192 + (rb * 4 + i) * 128 + hg * 16 + (lane & 15), EMPTY);
                if (lane < 18) stg_fill(p.s->kvf + (hg * 4 + i) * 288 + (lane < 16 ? (rb >> 2) * 64 + (rb & 3) * 8 + (lane >> 3) * 32 + (lane & 7) : 240 + rb * 2 + lane), EMPTY);
            }
            if (hg == 0 && lane < 8) stg_fill(p.s->cand + rb * 8 + lane, 0);
            if (lane < 28) stg_fill(lane < 16 ? p.s->st2 + rb * 128 + hg * 16 + lane : lane < 20 ? p.s->flo + (rb * 16 + hg * 2) * 2 + lane - 16
                                    : p.s->rsc + ((rb * 4 + ((lane - 20) >> 1)) * 8 + hg) * 2 + (lane & 1), 0);
            fence_rel_gpu();
            #pragma unroll 1
            for (int i = 0; i < (ffn ? 9 : 8); i++) {
                uint4* d = (i < 8 ? p.s->os + (rb * 16 + 2 * hg) * 1024 + i * 256 : p.s->yp + pr * 512 + rank * 128) + lane;
                #pragma unroll
                for (int q = 0; q < 4; q++) { stg_fill(d + q * 32, EMPTY); stg_fill(d + (i < 8 ? 128 : 256) + q * 32, EMPTY); }
            }
            TS(36);
        } else {
            const int hw = w4 & 1;
            const uint32_t fb = BAR(B_RF + 2 * hw);
            if (w4 == 2) {
                if (lane < 8) stg_fill(p.s->rest + b * 8 + lane, 0);
                else if (lane < 24 && b >= 32 * NC) stg_fill(p.s->mp + b * 16 + lane - 8, EMPTY);
            }
            bar_sync(3, 320);
            const uint32_t buf = sb + OFF_SP + hw * 8192u;
            #pragma unroll 1
            for (int job = b < 32 * NC; job < 2; job++) {
                const int nr = job ? 8 : 4;
                const int c0 = job ? 2048 + b * 32 : (((b >> 2) & 1) ? 0 : 1024) + (b >> 3) * 64 + hw * 32;
                const int row0 = job ? hw * 512 : (b & 3) * 256;
                while (clk32() - cstart < (job ? T_REST : T_WLATE)) __nanosleep(100);
                float macc[8] = {0.f, 0.f, 0.f, 0.f, 0.f, 0.f, 0.f, 0.f};
                #pragma unroll 1
                for (int q = -2; q < nr; q++) {
                    if (q >= 0) {
                        mbar_wait(fb + (q & 1) * 8, (q >> 1) & 1);
                        const uint32_t sv0 = sb + OFF_SILU + (row0 + q * 64 + g) * 2, wa = buf + (q & 1) * 4096u + lane * 16u;
                        #pragma unroll JUU
                        for (int i = 0; i < 8; i += 2) {
                            const uint32_t s0 = lds16(sv0 + i * 16), s1 = lds16(sv0 + i * 16 + 16);
                            const uint4 w0 = lds128(wa + i * 512u), w1 = lds128(wa + i * 512u + 512u);
                            fma8(macc, w0, bf_lo(s0)); fma8(macc, w1, bf_lo(s1));
                        }
                    }
                    __syncwarp();
                    if (q + 2 < nr) {
                        expect_tx_e(fb + (q & 1) * 8, 4096);
                        TMA_M(buf + (q & 1) * 4096u, &tmR, c0, row0 + (q + 2) * 64, fb + (q & 1) * 8);
                    }
                }
                stsf(sb + OFF_RED0 + (job ? hw * 256 + (c * 8 + g) * 4 : mod_pos(hw * 2 + (c >> 1), g) + (c & 1) * 8), reduce8(macc, lane));
                bar_sync(4, 64);
                if (w4 == 2) {
                    const uint4 u0 = lds128(sb + OFF_RED0 + (lane & 15) * 16), u1 = lds128(sb + OFF_RED0 + 256 + (lane & 15) * 16);
                    const float v0 = __uint_as_float(u0.x) + __uint_as_float(u1.x), v1 = __uint_as_float(u0.y) + __uint_as_float(u1.y);
                    const float v2 = __uint_as_float(u0.z) + __uint_as_float(u1.z), v3 = __uint_as_float(u0.w) + __uint_as_float(u1.w);
                    const uint32_t add = (b >> 5) == 2 ? ONE2 : 0u;
                    if (job == 0) { if (lane < 16) st_ll(p.s->mp + b * 16 + lane, u0.x, u0.y, u0.z, low_bits(__uint_as_float(u0.w), tag2)); TS(13); }
                    else { if (lane < 8) st_ll(p.s->rest + b * 8 + lane, hadd2(pack2(v0, v1), add), hadd2(pack2(v2, v3), add), 0, tag); TS(33); }
                }
                bar_sync(4, 64);
            }
            tmap_prefetch(hw ? &tmWo : &tmG); tmap_prefetch(hw ? &tmU : &tmD); tmap_prefetch(hw ? &tmPhi : &tmO);
        }
        __syncwarp();
        cluster_wait();
        bar_sync(2, 128);
        reg_inc<504 - 2 * CREG>();
        if (w4 == 0) TS(6);
        #pragma unroll 1
        for (int h = 0; h < 4; h++) {
            mbar_wait(BAR(B_PHI + h), 0);
            if (w4 == 0) TS(h == 0 ? 58 : h == 1 ? 52 : h == 2 ? 53 : 59);
            fence_async_smem();
            float o[20];
            const uint32_t vb = OFF_V + h * 8192u;
            const uint64_t dp = mk_desc(sb + phi_tile(h), 16, 1024, 1), dv = mk_desc(sb + vb, OFF_ONES - vb, 512, 2);
            wg_fence();
            #pragma unroll
            for (int ks = 0; ks < 8; ks++)
                wgmma_n40_ss<1, 1>(o, desc_add(dp, ks * 2048), desc_raw(dv, ks * (64 - (64 << 16))), ks);
            wg_commit();
            if (h == w4 + 2) {
                expect_tx_e(BAR(B_KVS + w4), 8192);
                bulk_load_e(sb + OFF_KVS + w4 * 8192u, p.s->kvp + ((hg * 4 + w4) * 16 + rb) * 512, 8192, BAR(B_KVS + w4));
            }
            wg_wait<0>();
            acc_fence(o);
            arrive_one(BAR(B_KVD + h));
            uint4* dst = p.s->kvp + (((hg * 4 + h) * 16 + (t >> 3)) * 16 + rb) * 32 + (t & 7);
            #pragma unroll
            for (int k = 0; k < 2; k++) {
                const uint32_t z = __float_as_uint(o[16 + 2 * k]) + 0x80u;
                st_ll(dst + k * 8, low_byte<1>(o[4 * k], z), low_byte<2>(o[4 * k + 1], z), low_byte<3>(o[4 * k + 2], z), low_bits(o[4 * k + 3], tag2));
                st_ll(dst + 16 + k * 8, __float_as_uint(o[8 + 4 * k]), __float_as_uint(o[9 + 4 * k]), __float_as_uint(o[10 + 4 * k]), low_bits(o[11 + 4 * k], tag2));
            }
        }
        if (w4 == 0) TS(17);
        {
            uint4* const fin = p.s->kvf + (hg * 4 + w4) * 288;
            {
                const uint4* src = p.s->kvp + ((hg * 4 + w4) * 16 + rb) * 512 + lane;
                uint4 w[16];
                if (w4 < 2) {
                    mbar_wait(BAR(B_KVS + w4), 1);
                    #pragma unroll
                    for (int i = 0; i < 16; i++) w[i] = lds128(sb + OFF_KVS + w4 * 8192u + i * 512u + lane * 16u);
                } else {
                    #pragma unroll
                    for (int i = 0; i < 16; i++) w[i].w = EMPTY;
                }
                #pragma unroll 1
                for (int it = 0; it < POLL_MAX; it++) {
                    bool ok = true;
                    #pragma unroll
                    for (int i = 0; i < 16; i++) { const bool miss = !tagged2(w[i].w, tag2); ok = ok && !miss; ld_ll_if(w[i], src + i * 32, miss); }
                    if (__all_sync(0xffffffffu, ok)) break;
                }
                if (w4 == 0) TS(18);
                if (w4 == 3) TS(10);
                float s[2][5];
                #pragma unroll
                for (int i = 0; i < 16; i++) {
                    const float z = __uint_as_float(__byte_perm(__byte_perm(w[i].x, w[i].y, 0x0400), w[i].z, 0x4210) & 0xffffff00u);
                    float (&a)[5] = s[i & 1];
                    if (i < 2) { a[0] = __uint_as_float(w[i].x); a[1] = __uint_as_float(w[i].y); a[2] = __uint_as_float(w[i].z); a[3] = __uint_as_float(w[i].w); a[4] = z; }
                    else { a[0] += __uint_as_float(w[i].x); a[1] += __uint_as_float(w[i].y); a[2] += __uint_as_float(w[i].z); a[3] += __uint_as_float(w[i].w); a[4] += z; }
                }
                char* d = (char*)fin + ((rb >> 2) * 16 + (rb & 3) * 2 + (g & 1)) * 64 + (((lane >> 3) ^ (rb & 3)) << 4) + c * 4;
                st_ll4(d, pack2(s[0][0] + s[1][0], s[0][1] + s[1][1]));
                st_ll4(d + 512, pack2(s[0][2] + s[1][2], s[0][3] + s[1][3]));
                if (lane < 16 && c < 2) st_ll4((char*)fin + 4096 + rb * 32 + (g * 2 + c) * 4, pack2(s[0][4] + s[1][4], 0.f));
            }
            fence_acq_gpu();
            uint4 v[9];
            #pragma unroll 1
            for (int it = 0; it < POLL_MAX; it++) {
                uint32_t m = 0;
                #pragma unroll
                for (int k = 0; k < 9; k++) v[k] = ld_ll(fin + k * 32 + lane);
                #pragma unroll
                for (int k = 0; k < 9; k++) m = max(m, umax4(v[k]));
                if (__all_sync(0xffffffffu, m != EMPTY)) break;
            }
            #pragma unroll
            for (int k = 0; k < 8; k++) sts128(sb + OFF_SP + w4 * 4096u + k * 512u + lane * 16u, v[k]);
            const uint32_t za = sb + OFF_Z + ((lane >> 3) * 16 + ((lane >> 1) & 3) * 2 + (lane & 1) * 8) * 64u + ((w4 ^ ((lane >> 1) & 3)) << 4);
            sts16(za, v[8].x); sts16(za + 64, v[8].z);
            fence_async_smem();
            __syncwarp();
            arrive_one(BAR(B_KVF + (w4 >> 1)));
            if (w4 == 0) TS(19);
            if (w4 == 3) TS(1);
        }
        if (w4 == 0) {
            const unsigned* f = (const unsigned*)(p.s->flo + (rb * 16 + d_block(hg, lane & 15)) * 2);
            const uint4* const a0 = p.s->os + rb * 16384;
            uint32_t seen = 0;
            uint32_t kb = hg ? 0 : 2, s = 0, freeb = BAR(B_OWN), par = 0;
            fence_rel_gpu();
            arrive_one(BAR(B_REL));
            mbar_wait(BAR(B_OWN), 0);
            #pragma unroll 1
            for (int n = 2; n < 16; n++) {
                if (!((seen >> n) & 1)) {
                    if (n >= 8) asm volatile("ld.acquire.cta.shared.u32 %0, [%1];" : "=r"(seen) : "r"(sb + OFF_SEEN) : "memory");
                    #pragma unroll 1
                    for (int it = 0; it < POLL_MAX && !((seen >> n) & 1); it++) { seen = __ballot_sync(0xffffffffu, ld_rlx(f) == tag); fence_acq_gpu(); }
                }
                mbar_wait(freeb, par);
                TR(64 + n);
                bulk_load_e(sb + OFF_DA + s * 16384u, a0 + kb * 1024, 16384, BAR(B_FA + s));
                expect_tx_e(BAR(B_FA + s), 16384);
                if (n == 2) TS(2);
                TR(16 + n);
                if (n == OGATE) arrive_one(BAR(B_OGO));
                if (n == 5 || n == 6) mbar_wait(BAR(B_PUB + n - 5), 0);
                kb = n == 8 ? 1 : kb + 2;
                if ((kb >> 1) == hg) kb += 2;
                s = (SLOT_A >> (4 * n + 4)) & 7;
                if (n >= 5) { freeb = BAR(B_ED + n - 5); par = 1; } else if (n == 3) freeb = BAR(B_OWN + 1);
            }
        } else if (w4 == 1) {
            if (ffn) { expect_tx_e(BAR(B_GU), 98304); expect_tx_e(BAR(B_WD), 65536); }
            mbar_wait(BAR(B_S0FREE), 1);
            #pragma unroll 1
            for (int n = 2; n < (ffn ? 20 : 16); n++) {
                if (n == BG1) mbar_wait(BAR(B_KVF + 1), 0);
                if (n == BG2) mbar_wait(BAR(B_PUB), 0);
                if (n == BG5) mbar_wait(BAR(B_OGO), 1);
                if (n >= 6) mbar_wait(BAR(B_ED + n - 6), 1);
                if (n < 16) {
                    const uint32_t s = (SLOT_B >> (4 * n)) & 7, bar = BAR(B_FB + s), dst = sb + OFF_DB + s * 16384u;
                    expect_tx_e(bar, 16384);
                    if (MCB && n >= 6) tma2_mc_e(dst + rank * 8192u, &tmWo, hg * 128 + rank * 64, d_block(hg, n) * 64, bar);
                    else { TMA_WO(dst, &tmWo, hg * 128, d_block(hg, n) * 64, bar); TMA_WO(dst + 8192u, &tmWo, hg * 128 + 64, d_block(hg, n) * 64, bar); }
                    if (ffn && n >= GBN && n < GBN + 2) TMA_F(sb + OFF_GB + (n - GBN) * 16384u, &tmG, pr * 64, rank * 512 + 256 + (n - GBN) * 128, BAR(B_GU));
                } else if (n < 18) {
                    if (n == 16) TS(49);
                    TMA_F(sb + OFF_UP0 + (n & 1) * 16384u, &tmU, pr * 64, rank * 512 + (n & 1) * 128, BAR(B_GU));
                    TMA_F(sb + OFF_UP1 + (n & 1) * 16384u, &tmU, pr * 64, rank * 512 + 256 + (n & 1) * 128, BAR(B_GU));
                } else {
                    tma3_ef_e(sb + OFF_DN0 + (n & 1) * 16384u, &tmD, pr * 64, rank * 8 + (n & 1) * 2, BAR(B_WD));
                    tma3_ef_e(sb + OFF_DN1 + (n & 1) * 16384u, &tmD, pr * 64, rank * 8 + 4 + (n & 1) * 2, BAR(B_WD));
                }
            }
        } else if (w4 == 3) {
            const unsigned* f = (const unsigned*)(p.s->flo + (rb * 16 + d_block(hg, lane & 15)) * 2);
            uint32_t seen = 0xffff0003u;
            mbar_wait(BAR(B_PUB + 1), 0);
            #pragma unroll 1
            for (int it = 0; it < POLL_MAX && seen != 0xffffffffu; it++) {
                const uint32_t m = seen | __ballot_sync(0xffffffffu, !((seen >> lane) & 1) && ld_rlx(f) == tag);
                if (m != seen) {
                    seen = m;
                    fence_acq_gpu();
                    __syncwarp();
                    asm volatile(EL "st.release.cta.shared.u32 [%0], %1;\n}" :: "r"(sb + OFF_SEEN), "r"(seen) : "memory");
                }
            }
        } else {
            asm volatile("fence.proxy.async.global;" ::: "memory");
            #pragma unroll 1
            for (int q = 0; q < 2; q++) {
                if (q) mbar_wait(BAR(B_OGO), 1);
                mbar_wait(BAR(B_OWN + q), 0);
                bulk_store_e(p.s->os + (rb * 16 + 2 * hg + q) * 1024, sb + OFF_OWN + q * 16384u, 16384);
                bulk_commit();
                bulk_wait();
                mbar_wait(BAR(B_REL), 0);
                st_flag_e(p.s->flo + (rb * 16 + 2 * hg + q) * 2, tag);
                arrive_one(BAR(B_PUB + q));
                if (q == 0) TS(3);
                TR(q);
            }
            mbar_wait(BAR(B_PF), 1);
            {
                uint4 w[4];
                poll_words<4>(w, p.s->rest + hg * 32 + lane, 256, tag);
                sts128(sb + OFF_PAR + lane * 32, make_uint4(w[2].x, w[1].x, w[3].x, w[0].x));
                sts128(sb + OFF_PAR + lane * 32 + 16, make_uint4(w[2].y, w[1].y, w[3].y, w[0].y));
                const uint2 wr = ldg64(p.wr + hg * 128 + lane * 4);
                sts64(sb + OFF_BQ + lane * 8, hmul2(w[2].x, wr.x), hmul2(w[2].y, wr.y));
            }
            float s = 0.f;
            #pragma unroll 1
            for (int i = 0; i < 2; i++) {
                uint4 w[4]; uint2 wr[4];
                #pragma unroll
                for (int q = 0; q < 4; q++) wr[q] = ldg64(p.wr + (lane + 32 * q + 128 * i) * 4);
                poll_words<4>(w, p.s->rest + 512 + i * 128 + lane, 32, tag);
                #pragma unroll
                for (int q = 0; q < 4; q++) { const uint32_t r0 = hmul2(w[q].x, wr[q].x), r1 = hmul2(w[q].y, wr[q].y); s += (bf_lo(r0) + bf_hi(r0)) + (bf_lo(r1) + bf_hi(r1)); }
            }
            __syncwarp();
            #pragma unroll
            for (int m = 16; m >= 1; m >>= 1) s += shfl_x(s, m);
            if (lane == 0) stsf(sb + OFF_ATOT, s);
            __syncwarp();
            arrive_one(BAR(B_PAR));
        }
        __syncwarp();
        {
            mbar_wait(BAR(B_PAR), 0);
            const uint2 pa0 = lds64(sb + OFF_PAR + lane * 32), pa1 = lds64(sb + OFF_PAR + lane * 32 + 16), wr = ldg64(p.wr + hg * 128 + lane * 4);
            const float atot = ldsf(sb + OFF_ATOT);
            mbar_wait(BAR(B_X2), 0);
            uint4 w;
            #pragma unroll 1
            for (int it = 0; it < POLL_MAX; it++) {
                w = ld_ll(p.s->st2 + rb * 128 + t);
                if (__all_sync(0xffffffffu, __uint_as_float(w.w) == 8.0f)) break;
            }
            if (w4 == 0) TS(31);
            uint32_t m2; float rinv;
            ln_final(__uint_as_float(w.x), __uint_as_float(w.y), m2, rinv);
            sts32(sb + OFF_KEYS + t * 4, (f2key(fmaf(-bf_lo(m2), atot, __uint_as_float(w.z)) * rinv) & ~127u) | (127 - t));
            sts64(sb + OFF_ST2 + t * 8, m2, __float_as_uint(rinv));
            bar_sync(2, 128);
            arrive_one(BAR(B_ST2));
            const uint4 kk = lds128(sb + OFF_KEYS + lane * 16);
            uint32_t k[4] = {kk.x, kk.y, kk.z, kk.w}, best;
            #pragma unroll 1
            for (int r = 0; r <= w4; r++) best = pop_max(k);
            const uint32_t row = 127 - (best & 127u), slot = rb * 4 + w4;
            if (hg == 0 && lane < 2) st_ll(p.s->cand + slot * 2 + lane, best, rb * 128 + row, 0, tag);
            if (w4 == 3) TS(23);
            const uint2 xv = lds64(sb + OFF_OUT + (row >> 3) * 2048u + (lane >> 4) * 1024u + (row & 7) * 128u + ((((lane >> 1) ^ row) & 7) << 4) + (lane & 1) * 8);
            const uint2 sv = lds64(sb + OFF_ST2 + row * 8);
            const uint32_t h0 = ln_pair(xv.x, sv.x, __uint_as_float(sv.y), pa0.x, pa0.y), h1 = ln_pair(xv.y, sv.x, __uint_as_float(sv.y), pa1.x, pa1.y);
            char* d = (char*)(p.s->rowh + slot * 128 + hg * 16) + lane * 8;
            st_ll8(d, h0, h1);
            st_ll8(d + 131072, xv.x, xv.y);
            __syncwarp();
            arrive_one(BAR(B_RD));
            float r = fmaf(bf_lo(h0), bf_lo(wr.x), bf_hi(h0) * bf_hi(wr.x)) + fmaf(bf_lo(h1), bf_lo(wr.y), bf_hi(h1) * bf_hi(wr.y));
            #pragma unroll
            for (int m = 16; m >= 1; m >>= 1) r += shfl_x(r, m);
            if (lane < 2) st_ll(p.s->rsc + (slot * 8 + hg) * 2 + lane, __float_as_uint(r), 0, 0, tag);
            if (w4 == 3) TS(24);
        }
        if (w4 == 0) {
            uint4 cv[2];
            poll_words<2>(cv, p.s->cand + lane * 2, 64, tag);
            __syncwarp();
            TS(11);
            uint32_t k[2] = {(cv[0].x & ~127u) | (63 - lane), (cv[1].x & ~127u) | (31 - lane)}, slot[4];
            #pragma unroll
            for (int i = 0; i < 4; i++) slot[i] = 63 - (pop_max(k) & 127u);
            const uint32_t myslot = lane < 16 ? (lane < 8 ? slot[0] : slot[1]) : (lane < 24 ? slot[2] : slot[3]);
            uint4 hv[4][2], sc;
            #pragma unroll 1
            for (int it = 0; it < POLL_MAX; it++) {
                sc = ld_ll(p.s->rsc + (myslot * 8 + (lane & 7)) * 2);
                uint32_t m = 0;
                #pragma unroll
                for (int i = 0; i < 4; i++) { hv[i][0] = ld_ll(p.s->rowh + slot[i] * 128 + rank * 64 + lane); hv[i][1] = ld_ll(p.s->rowh + slot[i] * 128 + rank * 64 + 32 + lane); }
                #pragma unroll
                for (int i = 0; i < 4; i++) m = max(m, max(max(hv[i][0].x, hv[i][0].z), max(hv[i][1].x, hv[i][1].z)));
                if (__all_sync(0xffffffffu, m != EMPTY && sc.w == tag)) break;
            }
            TS(12);
            const uint32_t r0 = __shfl_sync(0xffffffffu, cv[0].y, myslot & 31), r1 = __shfl_sync(0xffffffffu, cv[1].y, myslot & 31), row = myslot < 32 ? r0 : r1;
            float r = __uint_as_float(sc.x);
            r += shfl_x(r, 1); r += shfl_x(r, 2); r += shfl_x(r, 4);
            r = rbf(r);
            const uint32_t key = (f2key(r) & 0xffff0000u) | (0xffffu - row);
            uint32_t kq[1] = {key};
            const uint32_t best0 = pop_max(kq), best1 = pop_max(kq);
            const uint32_t m0 = __ballot_sync(0xffffffffu, key == best0), m1 = __ballot_sync(0xffffffffu, key == best1);
            #pragma unroll
            for (int i = 0; i < 4; i++)
                if (((m0 | m1) >> (8 * i)) & 1) {
                    const uint32_t a = sb + OFF_ROWS + ((m1 >> (8 * i)) & 1) * 1040u + lane * 16u;
                    sts128(a, hv[i][0]); sts128(a + 512, hv[i][1]);
                }
            if (key == best0 || key == best1) sts128(sb + OFF_SEL + (key == best1) * 16, make_uint4(row, myslot, __float_as_uint(r), 0));
            __syncwarp();
            arrive_one(BAR(B_ROWS));
            TS(25);
        } else if (w4 == 1) {
            mbar_wait(BAR(B_ROWS), 0);
            const uint4 sel = lds128(sb + OFF_SEL + rank * 16);
            const int col = pr * 16 + c * 2 + (lane >> 4) + (lane & 8);
            uint32_t xs, hs; uint4 gw;
            #pragma unroll 1
            for (int it = 0; it < POLL_MAX; it++) {
                const char* a = (const char*)(p.s->rowh + sel.y * 128) + (col >> 1) * 4;
                hs = ld_rlx(a); xs = ld_rlx(a + 131072); gw = ld_ll(p.s->rest + 768 + (col >> 2));
                if (hs != EMPTY && xs != EMPTY && gw.w == tag) break;
            }
            const uint32_t gq = (col & 2) ? gw.y : gw.x;
            const float fx = (col & 1) ? bf_hi(xs) : bf_lo(xs), fh = (col & 1) ? bf_hi(hs) : bf_lo(hs), fg = (col & 1) ? bf_hi(gq) : bf_lo(gq);
            const float sg = rbf(sigmoidf(__uint_as_float(sel.z)));
            const uint4* src = p.s->yp + g * 512 + rank * 256 + pr * 4 + c;
            uint4 w[7];
            #pragma unroll
            for (int i = 0; i < 7; i++) w[i] = make_uint4(0, EMPTY, 0, EMPTY);
            if (ffn) mbar_wait(BAR(B_PX), 0);
            #pragma unroll 1
            for (int it = 0; it < POLL_MAX; it++) {
                bool ok = true;
                #pragma unroll
                for (int i = 0; i < 7; i++) ld_ll_if(w[i], src + i * 4096, !(tagged2(w[i].y, tag2) && tagged2(w[i].w, tag2)));
                #pragma unroll
                for (int i = 0; i < 7; i++) ok = ok && tagged2(w[i].y, tag2) && tagged2(w[i].w, tag2);
                if (__all_sync(0xffffffffu, ok)) break;
            }
            TS(29);
            float y0 = 0.f, y1 = 0.f, y2 = 0.f, y3 = 0.f;
            #pragma unroll
            for (int i = 0; i < 7; i++) { y0 += __uint_as_float(w[i].x); y1 += __uint_as_float(w[i].y); y2 += __uint_as_float(w[i].z); y3 += __uint_as_float(w[i].w); }
            const bool b4 = lane & 16, b3 = lane & 8;
            const float a0 = (b4 ? y2 : y0) + shfl_x(b4 ? y0 : y2, 16), a1 = (b4 ? y3 : y1) + shfl_x(b4 ? y1 : y3, 16);
            float y = (b3 ? a1 : a0) + shfl_x(b3 ? a0 : a1, 8);
            y += shfl_x(y, 4);
            const float upd = rbf(rbf(y) * sg);
            if (!(lane & 4)) p.out[(size_t)sel.x * 1024 + col] = __float2bfloat16(fx + rbf(fg * rbf(fh + upd)));
            if (b == 0 && lane == 0) p.s->done[0] = tag;
            TS(28);
        } else if (w4 == 2) {
            mbar_wait(BAR(B_ROWS), 0);
            const uint32_t row0 = lds32(sb + OFF_SEL) - rb * 128, row1 = lds32(sb + OFF_SEL + 16) - rb * 128;
            mbar_wait(BAR(B_OUTW), 0);
            #pragma unroll 1
            for (uint32_t i = 0; i < 16; i++) {
                if ((row0 >> 3) != i && (row1 >> 3) != i) {
                    asm volatile(EL "cp.async.bulk.tensor.3d.global.shared::cta.bulk_group [%0, {0, %2, %3}], [%1];\n}"
                        :: "l"(&tmO), "r"(sb + OFF_OUT + i * 2048u), "r"(rb * 128 + i * 8), "r"(hg * 2) : "memory");
                } else {
                    #pragma unroll 1
                    for (uint32_t q = 0; q < 4; q++) {
                        const uint32_t r = q * 2 + (lane >> 4), ch = lane & 15;
                        const uint4 v = lds128(sb + OFF_OUT + i * 2048u + (ch >> 3) * 1024u + r * 128u + (((ch ^ r) & 7) << 4));
                        if (i * 8 + r != row0 && i * 8 + r != row1) stg128(p.out + (size_t)(rb * 128 + i * 8 + r) * 1024 + hg * 128 + ch * 8, v);
                    }
                }
            }
            bulk_commit();
            bulk_wait();
            TS(35);
        }
    } else {
        const int w4 = warp & 3, wgi = warp >> 2, g = lane >> 2, c = lane & 3;
        uint32_t m2[2]; float rinv[2];
        uint32_t tag2;
        {
            const int xrow = b * 16 + warp * 2;
            if (b < NW0)
                asm volatile("prefetch.global.L2 [%0];" :: "l"(p.wmod + (size_t)((b & 3) * 256 + tid) * 6144 + (((b >> 2) & 1) ? 0 : 1024) + (b >> 3) * 64));
            const uint2 cv = ldg64(p.c + tid * 4);
            const uint32_t tag = ld_rlx(p.s->done) + 1;
            if (lane < 2) stg_fill(p.s->st1 + xrow + lane, 0);
            if (warp == 0 && lane < 16 && b < 32 * NC) stg_fill(p.s->mp + b * 16 + lane, EMPTY);
            if (tid < 64) { int s = tid >> 2; sts128(sb + OFF_ONES + tid * 16, make_uint4(((tid & 3) == ((s >> 1) & 3)) ? 0x3F80u : 0u, 0, 0, 0)); }
            cluster_arrive();
            reg_inc<CG1>();
            {
                const float c0 = bf_lo(cv.x), c1 = bf_hi(cv.x), c2 = bf_lo(cv.y), c3 = bf_hi(cv.y);
                sts64(sb + OFF_SILU + tid * 8, pack2(c0 * sigmoidf(c0), c1 * sigmoidf(c1)), pack2(c2 * sigmoidf(c2), c3 * sigmoidf(c3)));
            }
            tag2 = tag % 3u;
            bar_sync(0, 384);
            bar_arrive(3, 320);
            if (warp == 0) TS(47);
            #pragma unroll 1
            for (int part = 0; part < 2; part++)
            if (part == (b < NW0)) {
                mbar_wait(BAR(B_XS + (warp >> 1)), 0);
                if (warp == 7) TS(60);
                if (warp == 0) TS(54);
                float sd[2][4], q1[2][4], q2[2][4];
                #pragma unroll
                for (int e = 0; e < 4; e++) { sd[0][e] = sd[1][e] = q1[0][e] = q1[1][e] = q2[0][e] = q2[1][e] = 0.f; }
                #pragma unroll
                for (int i = 0; i < 4; i++) {
                    const uint4 u = lds128(sb + OFF_XS + warp * 4096u + (i * 32 + lane) * 16u), v = lds128(sb + OFF_XS + warp * 4096u + 2048u + (i * 32 + lane) * 16u);
                    mma16816(sd[0], u.x, v.x, u.y, v.y, ONE2, ONE2); mma16816(sd[1], u.z, v.z, u.w, v.w, ONE2, ONE2);
                    mma16816(q1[0], u.x, v.x, u.y, v.y, u.x, u.y); mma16816(q1[1], u.z, v.z, u.w, v.w, u.z, u.w);
                    mma16816(q2[0], u.x, v.x, u.y, v.y, v.x, v.y); mma16816(q2[1], u.z, v.z, u.w, v.w, v.z, v.w);
                }
                if (warp == 0) TS(30);
                const float d0 = __shfl_sync(0xffffffffu, (g & 1) ? q1[0][1] + q1[1][1] : q1[0][0] + q1[1][0], g * 4 + (g >> 1));
                const float d1 = __shfl_sync(0xffffffffu, (g & 1) ? q2[0][3] + q2[1][3] : q2[0][2] + q2[1][2], g * 4 + (g >> 1));
                float sk = (c & 1) ? sd[0][2] + sd[1][2] : sd[0][0] + sd[1][0], qk = (c & 1) ? d1 : d0;
                #pragma unroll
                for (int m = 4; m <= 16; m <<= 1) { sk += shfl_x(sk, m); qk += shfl_x(qk, m); }
                uint32_t mm; float ri;
                ln_final(sk, qk, mm, ri);
                if (lane < 2) st_ll(p.s->st1 + xrow + lane, mm, __float_as_uint(ri), 0, tag);
                if (warp == 0) TS(14);
                if (warp == 7) TS(61);
            } else if (b < 32 * NC) {
                float m[4][4];
                uint32_t sv[4];
                ldsm4(sv[0], sv[1], sv[2], sv[3], sb + OFF_SILU + ((b & 3) * 256 + warp * 32) * 2 + (lane >> 3) * 16);
                mbar_wait(BAR(B_WS + (warp >> 1)), 0);
                if (warp == 7) TS(55);
                #pragma unroll
                for (int tt = 0; tt < 4; tt++) {
                    m[tt][0] = m[tt][1] = m[tt][2] = m[tt][3] = 0.f;
                    #pragma unroll
                    for (int e = 0; e < 2; e++) {
                        uint32_t a0, a1, a2, a3;
                        ldsm4t(a0, a1, a2, a3, sb + OFF_WST + warp * 4096u + (e * 16 + (lane & 7) + ((lane >> 4) << 3)) * 128u + (((2 * tt + ((lane >> 3) & 1)) ^ (lane & 7)) << 4));
                        mma16816(m[tt], a0, a1, a2, a3, sv[2 * e], sv[2 * e + 1]);
                    }
                }
                if (warp == 0) TS(46);
                const uint32_t ra = sb + OFF_RED0 + warp * 256 + mod_pos(c, g);
                stsf(ra, (c & 2) ? ((c & 1) ? m[3][0] : m[2][0]) : ((c & 1) ? m[1][0] : m[0][0]));
                stsf(ra + 8, (c & 2) ? ((c & 1) ? m[3][2] : m[2][2]) : ((c & 1) ? m[1][2] : m[0][2]));
                if (warp != 7) bar_arrive(5, 256);
                else {
                    bar_sync(5, 256);
                    float v0 = 0.f, v1 = 0.f, v2 = 0.f, v3 = 0.f;
                    #pragma unroll
                    for (int w = 0; w < 4; w++) {
                        const uint4 u = lds128(sb + OFF_RED0 + w * 512 + lane * 16);
                        v0 += __uint_as_float(u.x); v1 += __uint_as_float(u.y); v2 += __uint_as_float(u.z); v3 += __uint_as_float(u.w);
                    }
                    v0 += shfl_x(v0, 16); v1 += shfl_x(v1, 16); v2 += shfl_x(v2, 16); v3 += shfl_x(v3, 16);
                    if (lane < 16) st_ll(p.s->mp + b * 16 + lane, __float_as_uint(v0), __float_as_uint(v1), __float_as_uint(v2), low_bits(v3, tag2));
                    TS(45);
                }
            }
            if (!LATEFREE) arrive_one(BAR(B_STFREE));
            cluster_wait();
            uint4 st[2];
            poll_words<2>(st, p.s->st1 + rb * 128 + warp * 16 + g, 8, tag);
            __syncwarp();
            m2[0] = st[0].x; rinv[0] = __uint_as_float(st[0].y); m2[1] = st[1].x; rinv[1] = __uint_as_float(st[1].y);
            if (LATEFREE) arrive_one(BAR(B_STFREE));
            if (warp == 0) TS(4);
        }
        const int srow = warp * 16 + (lane & 15);
        const uint32_t aoff = srow * 128u + ((((lane >> 4) ^ srow) & 7) << 4);
        uint32_t pk[16], kq[48];
        {
            float accKV[128], accQ[64];
            {
                uint32_t f[2][4], r[4];
                const Recip ri0 = split_recip(rinv[0]), ri1 = split_recip(rinv[1]);
                mbar_wait(BAR(B_F1), 0);
                if (warp == 0) TS(63);
                ldsm4(r[0], r[1], r[2], r[3], sb + OFF_RING + aoff);
                mbar_wait(BAR(B_MOD), 0);
                if (warp == 0) TS(15);
                uint4 md = lds128(sb + OFF_MODS + c * 16);
                int s = 0, sp = 2, par = 0;
                #pragma unroll 1
                for (int j = 0; j < 16; j++) {
                    const int sn = s == 2 ? 0 : s + 1;
                    par ^= s == 2;
                    const uint64_t db = mk_desc(sb + OFF_RING + s * 65536u + 16384u, 8192, 1024, 1);
                    #pragma unroll
                    for (int ks = 0; ks < 4; ks++) {
                        uint32_t (&ff)[4] = f[ks & 1];
                        ff[0] = ln_pair(r[0], m2[0], ri0, md.x, md.z); ff[1] = ln_pair(r[1], m2[1], ri1, md.x, md.z);
                        ff[2] = ln_pair(r[2], m2[0], ri0, md.y, md.w); ff[3] = ln_pair(r[3], m2[1], ri1, md.y, md.w);
                        const int kn = (ks + 1) & 3;
                        ldsm4(r[0], r[1], r[2], r[3], sb + OFF_RING + (ks == 3 ? sn : s) * 65536u + (aoff ^ (kn << 5)));
                        md = lds128(sb + OFF_MODS + ((ks == 3 ? j + 1 : j) * 4 + kn) * 64 + c * 16);
                        wg_fence();
                        wgmma_n256_rs<1>(accKV, ff[0], ff[1], ff[2], ff[3], desc_add(db, 16384 + ks * 2048), ks ? 1 : j);
                        wgmma_n128_rs<1>(accQ, ff[0], ff[1], ff[2], ff[3], desc_add(db, ks * 2048), ks ? 1 : j);
                        wg_commit();
                        if (ks == 1) mbar_wait(BAR(B_MOD + ((j + 1) & 15)), 0);
                        if (ks == 2) { WT0(); mbar_wait(BAR(j < 15 ? B_F1 + sn : B_WPHI), j < 15 ? par : 0);
                        }
                        wg_wait<1>();
                        if (ks == 0) arrive_if(BAR(B_E1 + sp), j);
                    }
                    sp = s; s = sn;
                }
            }
            mbar_wait(BAR(B_E1 + 2), 0);
            wg_wait<0>();
            acc_fence(accKV); acc_fence(accQ);
            arrive_one(BAR(B_E1));
            if (warp == 0) TS(16);
            float pp[2][16];
            #pragma unroll
            for (int h = 0; h < 4; h++) {
                if (h == VFIRST) {
                    #pragma unroll
                    for (int i = 0; i < 16; i++) pk[i] = pack2(accKV[2 * i], accKV[2 * i + 1]);
                    phi_issue(pp, pk, sb, 0);
                }
                #pragma unroll
                for (int q = 0; q < 2; q++) {
                    const int o = 64 + 16 * h + 8 * q;
                    stsm4(sb + OFF_V + h * 8192u + srow * 64u + (((2 * q + (lane >> 4)) ^ ((srow >> 1) & 3)) << 4),
                          pack2(accKV[o], accKV[o + 1]), pack2(accKV[o + 2], accKV[o + 3]), pack2(accKV[o + 4], accKV[o + 5]), pack2(accKV[o + 6], accKV[o + 7]));
                }
            }
            #pragma unroll
            for (int i = 0; i < 48; i++) kq[i] = i < 16 ? pack2(accKV[32 + 2 * i], accKV[33 + 2 * i]) : pack2(accQ[2 * i - 32], accQ[2 * i - 31]);
            wg_wait<0>();
            acc_fence(pp[0]); acc_fence(pp[1]);
            #pragma unroll
            for (int i = 0; i < 16; i++) pk[i] = pack2(pp[i >> 3][2 * (i & 7)], pp[i >> 3][2 * (i & 7) + 1]);
        }
        reg_dec<CREG>();
        if (warp == 0) TS(56);
        {
            uint32_t ph[16];
            FmState fs; float ea[16], eb[16];
            #pragma unroll
            for (int i = 0; i < 16; i++) { ph[i] = 0; eb[i] = 0.f; }
            fs.sp = fs.sn = 1.f;
            fm_slot<false, false, true>(fs, ea, ph, pk, ea, pk);
            #pragma unroll 1
            for (int u = 0; u < 4; u++) {
                float pp[2][16];
                if (u & 2) { mbar_wait(BAR(B_KVD + 2 * u - 3), 0); phi_issue(pp, kq + 32, sb, 1); }
                else if (u & 1) phi_issue(pp, kq + 16, sb, 0);
                else phi_issue(pp, kq, sb, 1);
                fm_slot<true, true, true>(fs, eb, ph + 1, pk, ea, pk + 1);
                phi_store(ph, sb, aoff, 2 * u - 1);
                fm_slot<true, true, true>(fs, ea, ph, pk + 1, eb, pk + 8);
                fm_slot<true, true, true>(fs, eb, ph + 1, pk + 8, ea, pk + 9);
                phi_store(ph, sb, aoff, 2 * u);
                wg_wait<0>();
                acc_fence(pp[0]); acc_fence(pp[1]);
                #pragma unroll
                for (int i = 0; i < 8; i++) pk[i] = pack2(pp[0][2 * i], pp[0][2 * i + 1]);
                fm_slot<true, true, true>(fs, ea, ph, pk + 9, eb, pk);
                #pragma unroll
                for (int i = 0; i < 8; i++) pk[8 + i] = pack2(pp[1][2 * i], pp[1][2 * i + 1]);
            }
            fm_slot<true, false, false>(fs, eb, ph + 1, pk, ea, pk);
            phi_store(ph, sb, aoff, 7);
        }
        if (warp == 0) TS(57);
        uint32_t x2[16][2], gf[64];
        const uint32_t woff = lane * 128u + (((warp ^ lane) & 7) << 4);
        mbar_wait(BAR(B_S0), 0);
        #pragma unroll
        for (int q = 0; q < 8; q++) {
            ldsm4(x2[2 * q][0], x2[2 * q][1], x2[2 * q + 1][0], x2[2 * q + 1][1], sb + OFF_XT + (q >> 2) * 16384u + (aoff ^ ((q & 3) << 5)));
            ldsm4t(gf[4 * q], gf[4 * q + 1], gf[4 * q + 2], gf[4 * q + 3], sb + OFF_GA + q * 4096u + woff);
        }
        __syncwarp();
        arrive_one(BAR(B_S0FREE));
        #pragma unroll 1
        for (int pp = 0; pp < 2; pp++) {
            float o0[20], o1[20];
            const uint64_t dk = mk_desc(sb + OFF_SP + pp * 8192u, OFF_Z - OFF_SP - pp * 8160u, 512, 2);
            const uint64_t dq = mk_desc(sb + OFF_V + pp * 32768u + wgi * 8192u, 16, 1024, 1);
            mbar_wait(BAR(B_PHI + 5 + 2 * pp), 0);
            fence_async_smem();
            mbar_wait(BAR(B_KVF + pp), 0);
            wg_fence();
            #pragma unroll
            for (int ks = 0; ks < 4; ks++) {
                wgmma_n40_ss<0, 1>(o0, desc_add(dq, ks * 32), desc_add(dk, ks * 1024), ks);
                wgmma_n40_ss<0, 1>(o1, desc_add(dq, 16384 + ks * 32), desc_raw(dk, 256 + ks * 64 - (255 << 16)), ks);
            }
            wg_commit();
            wg_wait<0>();
            acc_fence(o0); acc_fence(o1);
            #pragma unroll
            for (int hh = 0; hh < 2; hh++) {
                const float (&o)[20] = hh ? o1 : o0;
                const Recip rd0 = split_recip(rcp(rbf(rbf(__shfl_sync(0xffffffffu, o[16], lane & ~3)) + 1e-6f)));
                const Recip rd1 = split_recip(rcp(rbf(rbf(__shfl_sync(0xffffffffu, o[18], lane & ~3)) + 1e-6f)));
                uint32_t op[8];
                #pragma unroll
                for (int j = 0; j < 4; j++) { op[2 * j] = hdiv2(pack2(o[4 * j], o[4 * j + 1]), rd0); op[2 * j + 1] = hdiv2(pack2(o[4 * j + 2], o[4 * j + 3]), rd1); }
                #pragma unroll
                for (int q = 0; q < 2; q++) stsm4(sb + OFF_OWN + pp * 16384u + (aoff ^ ((2 * hh + q) << 5)), op[4 * q], op[4 * q + 1], op[4 * q + 2], op[4 * q + 3]);
            }
            fence_async_smem();
            __syncwarp();
            arrive_one(BAR(B_OWN + pp));
            if (warp == 0) TS(20 + pp);
        }
        const uint32_t ooff = sb + OFF_OUT + (srow >> 3) * 1024u + aoff;
        {
            float acc[64];
            const uint32_t vchk = lane * 32u + g * 4u;
            const uint64_t da0 = mk_desc(sb + OFF_DA + wgi * 8192u, 16, 1024, 1), db0 = mk_desc(sb + OFF_DB, 8192, 1024, 1);
            #pragma unroll 1
            for (int n = 0; n < 16; n++) {
                const uint32_t s = (SLOT_A >> (4 * n)) & 7, sB = (SLOT_B >> (4 * n)) & 7;
                WT0();
                mbar_wait(BAR(B_FB + sB), (PAR_B >> n) & 1);
                WTJ(16 + n);
                mbar_wait(BAR(n < 2 ? B_OWN + n : B_FA + s), (PAR_A >> n) & 1);
                WTJ(n);
                {
                    const uint32_t ra = sb + OFF_DA + s * 16384u + warp * 2048u;
                    if (__any_sync(0xffffffffu, max(lds32(ra + vchk), lds32(ra + vchk + 1024)) == EMPTY)) {
                        #pragma unroll 1
                        for (int i = 0; i < 4; i++) {
                            uint4 v;
                            #pragma unroll 1
                            for (int it = 0; it < POLL_MAX; it++) {
                                v = ld_ll(p.s->os + (rb * 16 + d_block(hg, n)) * 1024 + warp * 128 + i * 32 + lane);
                                if (umax4(v) != EMPTY) break;
                            }
                            sts128(ra + i * 512 + lane * 16, v);
                        }
                        fence_async_smem();
                        __syncwarp();
                    }
                }
                TR(32 + 16 * wgi + n);
                const uint64_t da = desc_add(da0, s * 16384u), db = desc_add(db0, sB * 16384u);
                wg_fence();
                #pragma unroll
                for (int ks = 0; ks < 4; ks++) wgmma_n128_ss<0, 1>(acc, desc_add(da, ks * 32), desc_add(db, ks * 2048), ks ? 1 : n);
                wg_commit();
                wg_wait<1>();
                if (MCB) arrive_both_if(BAR(B_ED - 1 + n), n); else arrive_if(BAR(B_ED - 1 + n), n);
            }
            mbar_wait(BAR(B_PAR), 0);
            uint32_t gar[16], bfr[16];
            #pragma unroll
            for (int j = 0; j < 16; j++) {
                gar[j] = lds32(sb + OFF_PAR + j * 64 + c * 16 + 12);
                const uint32_t bq = lds32(sb + OFF_BQ + j * 16 + c * 4);
                bfr[j] = (g & 1) ? bq : ONE2;
            }
            wg_wait<0>();
            acc_fence(acc);
            bar_arrive(6 + wgi, 256);
            if (warp == 0) TS(9);
            float sd[2][4], q1[2][4], q2[2][4];
            #pragma unroll
            for (int e = 0; e < 4; e++) { sd[0][e] = sd[1][e] = q1[0][e] = q1[1][e] = q2[0][e] = q2[1][e] = 0.f; }
            #pragma unroll
            for (int s = 0; s < 8; s++) {
                #pragma unroll
                for (int e = 0; e < 4; e++) { const int j = 2 * s + (e >> 1), h = e & 1; x2[j][h] = hadd2(x2[j][h], hmul2(gar[j], pack2(acc[4 * j + 2 * h], acc[4 * j + 2 * h + 1]))); }
                mma16816(sd[s & 1], x2[2 * s][0], x2[2 * s][1], x2[2 * s + 1][0], x2[2 * s + 1][1], bfr[2 * s], bfr[2 * s + 1]);
                mma16816(q1[s & 1], x2[2 * s][0], x2[2 * s][1], x2[2 * s + 1][0], x2[2 * s + 1][1], x2[2 * s][0], x2[2 * s + 1][0]);
                mma16816(q2[s & 1], x2[2 * s][0], x2[2 * s][1], x2[2 * s + 1][0], x2[2 * s + 1][1], x2[2 * s][1], x2[2 * s + 1][1]);
            }
            if (c == (g >> 1)) {
                uint4* d = p.s->st2 + rb * 128 + warp * 16 + g;
                red_add4(d, sd[0][0] + sd[1][0], (g & 1) ? q1[0][1] + q1[1][1] : q1[0][0] + q1[1][0], sd[0][1] + sd[1][1], 1.0f);
                red_add4(d + 8, sd[0][2] + sd[1][2], (g & 1) ? q2[0][3] + q2[1][3] : q2[0][2] + q2[1][2], sd[0][3] + sd[1][3], 1.0f);
            }
            if (warp == 0) TS(22);
            bar_sync(7 - wgi, 256);
            #pragma unroll
            for (int q = 0; q < 8; q++) stsm4((ooff + (q >> 2) * 1024u) ^ ((q & 3) << 5), x2[2 * q][0], x2[2 * q][1], x2[2 * q + 1][0], x2[2 * q + 1][1]);
            __syncwarp();
            arrive_one(BAR(B_X2));
        }
        if (ffn) {
            mbar_wait(BAR(B_GU), 0);
            if (warp == 0) TS(38);
            #pragma unroll
            for (int q = 8; q < 16; q++) ldsm4t(gf[4 * q], gf[4 * q + 1], gf[4 * q + 2], gf[4 * q + 3], sb + OFF_GB + (q - 8) * 4096u + woff);
        }
        {
            mbar_wait(BAR(B_ST2), 0);
            const uint2 s0 = lds64(sb + OFF_ST2 + (warp * 16 + g) * 8), s1 = lds64(sb + OFF_ST2 + (warp * 16 + g + 8) * 8);
            const Recip r0 = split_recip(__uint_as_float(s0.y)), r1 = split_recip(__uint_as_float(s1.y));
            #pragma unroll
            for (int j = 0; j < 16; j++) {
                const uint4 pa = lds128(sb + OFF_PAR + j * 64 + c * 16);
                x2[j][0] = hadd2(x2[j][0], hmul2(pa.z, ln_pair(x2[j][0], s0.x, r0, pa.x, pa.y)));
                x2[j][1] = hadd2(x2[j][1], hmul2(pa.z, ln_pair(x2[j][1], s1.x, r1, pa.x, pa.y)));
            }
            mbar_wait(BAR(B_RD), 0);
            #pragma unroll
            for (int q = 0; q < 8; q++) stsm4((ooff + (q >> 2) * 1024u) ^ ((q & 3) << 5), x2[2 * q][0], x2[2 * q][1], x2[2 * q + 1][0], x2[2 * q + 1][1]);
            fence_async_smem();
            __syncwarp();
            arrive_one(BAR(B_OUTW));
            if (warp == 0) TS(32);
        }
        if (ffn) {
            float acc[4][4];
            {
                uint32_t uf[64];
                #pragma unroll
                for (int q = 0; q < 16; q++) ldsm4t(uf[4 * q], uf[4 * q + 1], uf[4 * q + 2], uf[4 * q + 3], sb + (q < 8 ? OFF_UP0 : OFF_UP1 - 32768u) + q * 4096u + woff);
                #pragma unroll
                for (int i = 0; i < 4; i++) { acc[i][0] = acc[i][1] = acc[i][2] = acc[i][3] = 0.f; }
                mbar_wait(BAR(B_WD), 0);
                mbar_wait(BAR(B_ROWS), 0);
                #pragma unroll
                for (int q = 0; q < 16; q++) {
                    uint32_t b0, b1, b2, b3;
                    ldsm4(b0, b1, b2, b3, sb + OFF_ROWS + (lane & 1) * 1040u + (lane >> 3) * 16u + q * 64u);
                    mma16816(acc[(2 * q) & 3], gf[4 * q], uf[4 * q], gf[4 * q + 1], uf[4 * q + 1], b0, b1);
                    mma16816(acc[(2 * q + 1) & 3], gf[4 * q + 2], uf[4 * q + 2], gf[4 * q + 3], uf[4 * q + 3], b2, b3);
                }
            }
            float s[4];
            #pragma unroll
            for (int e = 0; e < 4; e++) s[e] = (acc[0][e] + acc[1][e]) + (acc[2][e] + acc[3][e]);
            const uint32_t pxa = sb + OFF_PX + (warp * 8 + g) * 16u;
            if (c == 0) st_partner128(pxa, BAR(B_PX), rank ^ 1, s[0], s[1], s[2], s[3]);
            if (warp == 0) TS(34);
            uint32_t df[4][4][4];
            {
                const uint32_t da = sb + (wgi ? OFF_DN1 : OFF_DN0) + w4 * 8192u + ((lane & 7) + ((lane >> 4) << 3)) * 128u;
                #pragma unroll
                for (int tt = 0; tt < 4; tt++)
                    #pragma unroll
                    for (int ks = 0; ks < 4; ks++)
                        ldsm4t(df[tt][ks][0], df[tt][ks][1], df[tt][ks][2], df[tt][ks][3], da + ks * 2048u + (((2 * tt + ((lane >> 3) & 1)) ^ (lane & 7)) << 4));
            }
            mbar_wait(BAR(B_PX), 0);
            {
                const uint4 q = lds128(pxa);
                float gt = rbf((c & 1) ? s[1] + __uint_as_float(q.y) : s[0] + __uint_as_float(q.x));
                const float us = rbf((c & 1) ? s[3] + __uint_as_float(q.w) : s[2] + __uint_as_float(q.z));
                gt = rbf(gt * sigmoidf(gt));
                if (c < 2) sts16(sb + OFF_HID + c * 144 + (warp * 8 + g) * 2, pack2(gt * us, 0.f));
            }
            if (warp == 0) TS(26);
            bar_sync(1, 256);
            uint32_t bh[8];
            ldsm4(bh[0], bh[1], bh[2], bh[3], sb + OFF_HID + (lane & 1) * 144u + (lane >> 3) * 16u);
            ldsm4(bh[4], bh[5], bh[6], bh[7], sb + OFF_HID + (lane & 1) * 144u + (lane >> 3) * 16u + 64u);
            float y[4][4];
            #pragma unroll
            for (int tt = 0; tt < 4; tt++) { y[tt][0] = y[tt][1] = y[tt][2] = y[tt][3] = 0.f; }
            #pragma unroll
            for (int ks = 0; ks < 4; ks++)
                #pragma unroll
                for (int tt = 0; tt < 4; tt++) mma16816(y[tt], df[tt][ks][0], df[tt][ks][1], df[tt][ks][2], df[tt][ks][3], bh[2 * ks], bh[2 * ks + 1]);
            float e[4];
            #pragma unroll
            for (int i = 0; i < 4; i++) e[i] = (c & 2) ? ((c & 1) ? y[3][i] : y[2][i]) : ((c & 1) ? y[1][i] : y[0][i]);
            char* d = (char*)(p.s->yp + pr * 512 + rank * 128 + (warp * 4 + c) * 4) + g * 8;
            st_ll8(d, __float_as_uint(e[0]), low_bits(e[2], tag2));
            st_ll8(d + 4096, __float_as_uint(e[1]), low_bits(e[3], tag2));
            if (warp == 0) TS(27);
        }
    }
}

typedef CUresult (*EncodeFn)(CUtensorMap*, CUtensorMapDataType, cuuint32_t, void*, const cuuint64_t*, const cuuint64_t*, const cuuint32_t*,
                             const cuuint32_t*, CUtensorMapInterleave, CUtensorMapSwizzle, CUtensorMapL2promotion, CUtensorMapFloatOOBfill);

CUtensorMap make_map(EncodeFn enc, const void* ptr, uint64_t cols, uint64_t rows, uint32_t bc, uint32_t br, CUtensorMapSwizzle swz, CUtensorMapL2promotion promo) {
    CUtensorMap m;
    cuuint64_t dims[2] = {cols, rows}, strides[1] = {cols * 2};
    cuuint32_t box[2] = {bc, br}, es[2] = {1, 1};
    enc(&m, CU_TENSOR_MAP_DATA_TYPE_BFLOAT16, 2, const_cast<void*>(ptr), dims, strides, box, es, CU_TENSOR_MAP_INTERLEAVE_NONE, swz, promo,
        CU_TENSOR_MAP_FLOAT_OOB_FILL_NONE);
    return m;
}
CUtensorMap make_block_map(EncodeFn enc, const void* ptr, uint32_t sections, uint64_t rows, uint32_t br, CUtensorMapL2promotion promo) {
    CUtensorMap m;
    cuuint64_t dims[4] = {64, rows, 16, sections}, strides[3] = {sections * 2048ull, 128, 2048};
    cuuint32_t box[4] = {64, br, 2, sections}, es[4] = {1, 1, 1, 1};
    enc(&m, CU_TENSOR_MAP_DATA_TYPE_BFLOAT16, sections > 1 ? 4 : 3, const_cast<void*>(ptr), dims, strides, box, es, CU_TENSOR_MAP_INTERLEAVE_NONE,
        CU_TENSOR_MAP_SWIZZLE_128B, promo, CU_TENSOR_MAP_FLOAT_OOB_FILL_NONE);
    return m;
}

}

extern "C" void kernel_launch(void* const* d_in, const int* in_sizes, int n_in, void* d_out, int out_size) {
    (void)in_sizes; (void)n_in; (void)out_size;
    void* fn = nullptr; cudaDriverEntryPointQueryResult qr;
    cudaGetDriverEntryPoint("cuTensorMapEncodeTiled", &fn, cudaEnableDefault, &qr);
    EncodeFn enc = (EncodeFn)fn;
    void* hs = nullptr;
    cudaGetSymbolAddress(&hs, g_scratch);
    const CUtensorMapL2promotion P256 = CU_TENSOR_MAP_L2_PROMOTION_L2_256B, P128 = CU_TENSOR_MAP_L2_PROMOTION_L2_128B;
    CUtensorMap tmW = make_block_map(enc, d_in[1], 3, 1024, 64, P256);
    CUtensorMap tmWo = make_map(enc, d_in[3], 1024, 1024, 64, 64, CU_TENSOR_MAP_SWIZZLE_128B, P256);
    CUtensorMap tmPhi = make_map(enc, d_in[2], 32, 1024, 32, 128, CU_TENSOR_MAP_SWIZZLE_64B, P128);
    CUtensorMap tmG = make_map(enc, d_in[6], 3584, 1024, 64, 128, CU_TENSOR_MAP_SWIZZLE_128B, P128);
    CUtensorMap tmU = make_map(enc, d_in[7], 3584, 1024, 64, 128, CU_TENSOR_MAP_SWIZZLE_128B, P128);
    CUtensorMap tmD = make_block_map(enc, d_in[8], 1, 3584, 64, P128);
    CUtensorMap tmX = make_map(enc, d_in[0], 1024, 2048, 64, 128, CU_TENSOR_MAP_SWIZZLE_128B, P128);
    CUtensorMap tmO = make_block_map(enc, d_out, 1, 2048, 8, P128);
    CUtensorMap tmM = make_map(enc, d_in[10], 6144, 1024, 64, 64, CU_TENSOR_MAP_SWIZZLE_128B, P128);
    CUtensorMap tmR = make_map(enc, d_in[10], 6144, 1024, 32, 64, CU_TENSOR_MAP_SWIZZLE_NONE, P128);
    CUtensorMap tmG8 = make_map(enc, d_in[6], 3584, 1024, 8, 64, CU_TENSOR_MAP_SWIZZLE_NONE, P128);
    CUtensorMap tmU8 = make_map(enc, d_in[7], 3584, 1024, 8, 64, CU_TENSOR_MAP_SWIZZLE_NONE, P128);
    CUtensorMap tmD8 = make_map(enc, d_in[8], 1024, 3584, 8, 64, CU_TENSOR_MAP_SWIZZLE_NONE, P128);
    Ptrs p;
    p.x = (const bf16*)d_in[0]; p.c = (const bf16*)d_in[9]; p.wmod = (const bf16*)d_in[10]; p.wr = (const bf16*)d_in[5];
    p.wg = (const bf16*)d_in[6]; p.wu = (const bf16*)d_in[7]; p.wd = (const bf16*)d_in[8]; p.out = (bf16*)d_out; p.s = (Scratch*)hs;
    p.wqkv = (const bf16*)d_in[1]; p.wo = (const bf16*)d_in[3];
    cudaFuncSetAttribute(fused_kernel, cudaFuncAttributeMaxDynamicSharedMemorySize, SMEM_BYTES);
    fused_kernel<<<128, NTHREADS, SMEM_BYTES, cudaStreamPerThread>>>(p, tmW, tmWo, tmPhi, tmG, tmU, tmD, tmX, tmO, tmM, tmR, tmG8, tmU8, tmD8);
}
```

```cpp
#include <cuda_runtime.h>
#include <cuda.h>
#include <cuda_bf16.h>
#include <stdint.h>

namespace {

typedef __nv_bfloat16 bf16;

constexpr int NTHREADS = 384;
constexpr int POLL_MAX = 400000;
constexpr uint32_t EMPTY = 0xffffffffu;

constexpr uint32_t OFF_RING = 0;
constexpr uint32_t OFF_XS   = 131072;
constexpr uint32_t OFF_WST  = 163840;
constexpr uint32_t OFF_XT   = 0;
constexpr uint32_t OFF_GA   = 32768;
constexpr uint32_t OFF_PHI0 = 163840, OFF_PHI1 = 98304;
constexpr uint32_t OFF_V    = 131072;
constexpr uint32_t OFF_KVS  = 131072;
constexpr uint32_t OFF_DB   = 0;
constexpr uint32_t OFF_DA   = 98304;
constexpr uint64_t SLOT_A   = 0x5432105432105432ull, SLOT_B = 0x1054321054321054ull;
constexpr uint32_t PAR_A    = 0x3f00, PAR_B = 0x0fc0;
constexpr uint32_t OFF_OWN  = OFF_DA + 32768;
constexpr uint32_t OFF_OUT  = OFF_DA + 65536;
constexpr uint32_t OFF_UP0  = OFF_DA, OFF_UP1 = OFF_DB + 32768, OFF_DN0 = OFF_DA + 32768, OFF_DN1 = OFF_DB + 65536;
constexpr uint32_t OFF_WPHI = 196608;
constexpr uint32_t OFF_SP   = 204800;
constexpr uint32_t OFF_Z    = 221184;
constexpr uint32_t OFF_ONES = 225280;
constexpr uint32_t OFF_MODS = 226304;
constexpr uint32_t OFF_GB   = 196608;
constexpr uint32_t OFF_BQ   = 229376;
constexpr uint32_t OFF_ATOT = OFF_BQ + 256;
constexpr uint32_t OFF_BAR  = 230400;
constexpr uint32_t OFF_SEEN = OFF_BAR + 632;
constexpr uint32_t OFF_PAR  = OFF_BAR + 640;
constexpr uint32_t SMEM_BYTES = 232448;
constexpr uint32_t OFF_SILU = OFF_Z;
constexpr uint32_t OFF_RED0 = OFF_Z + 2048;
constexpr uint32_t OFF_ST2  = OFF_DB;
constexpr uint32_t OFF_SEL  = OFF_ST2 + 1024;
constexpr uint32_t OFF_ROWS = OFF_ST2 + 2048;
constexpr uint32_t OFF_PX   = OFF_ROWS + 4608;
constexpr uint32_t OFF_HID  = OFF_PX + 2048;

enum {
    B_F1 = 0, B_E1 = 3, B_STFREE = 6, B_WPHI = 7, B_FA = 8, B_FB = 14, B_RF = 20, B_KVD = 24, B_PAR = 26, B_S0 = 27, B_GU = 28, B_WD = 29,
    B_X2 = 30, B_ST2 = 31, B_CAND = 32,
    B_MP = 33, B_MOD = 34, B_PX = 50, B_S0FREE = 51, B_PHI = 52, B_OUTW = 56, B_PUB = 57, B_KVF = 59, B_OWN = 61, B_REL = 63, B_ROWS = 64, B_SEL = 65, B_YP = 66,
    B_XS = 67,
    B_WS = 71, B_COUNT = 75,
    B_ED = B_MOD, B_KVS = B_XS, B_OGO = B_XS + 2, B_PF = B_XS + 3
};

struct Scratch {
    uint4 os[256 * 1024];
    uint4 kvp[32 * 256 * 32];
    uint4 kvf[32 * 288];
    uint4 st1[2048];
    uint4 mp[128 * 16];
    uint4 rest[1024];
    uint4 flo[256 * 2];
    uint4 st2[2048];
    uint4 cand[64 * 2];
    uint4 rowh[128 * 128];
    uint4 rowx[128 * 128];
    uint4 rsc[64 * 8 * 2];
    uint4 yp[56 * 512];
    unsigned done[4];
};
__device__ __align__(1024) Scratch g_scratch;
#define TS(i) do {} while (0)
#define TR(i)
#define TRL(i)
#define WT0()
#define WTJ(j)

__device__ __forceinline__ uint32_t smem_u32(const void* p) { return (uint32_t)__cvta_generic_to_shared(p); }
__device__ __forceinline__ int lane_id() { int l; asm volatile("mov.u32 %0, %%laneid;" : "=r"(l)); return l; }
__device__ __forceinline__ uint32_t clk32() { uint32_t c; asm volatile("mov.u32 %0, %%clock;" : "=r"(c) :: "memory"); return c; }
__device__ __forceinline__ void arrive_one(uint32_t bar) {
    asm volatile("{\n.reg .pred p;\nelect.sync _|p, 0xffffffff;\n@p mbarrier.arrive.shared::cta.b64 _, [%0];\n}" :: "r"(bar) : "memory");
}
__device__ __forceinline__ void arrive_many(uint32_t bar, uint32_t n) {
    asm volatile("{\n.reg .pred p;\nelect.sync _|p, 0xffffffff;\n@p mbarrier.arrive.shared::cta.b64 _, [%0], %1;\n}" :: "r"(bar), "r"(n) : "memory");
}
__device__ __forceinline__ void arrive_if(uint32_t bar, uint32_t on) {
    asm volatile("{\n.reg .pred q, p;\nelect.sync _|q, 0xffffffff;\nsetp.ne.and.u32 p, %1, 0, q;\n@p mbarrier.arrive.shared::cta.b64 _, [%0];\n}" :: "r"(bar), "r"(on) : "memory");
}
__device__ __forceinline__ void arrive_both_if(uint32_t bar, uint32_t on) {
    asm volatile("{\n.reg .pred q, p;\n.reg .b32 r0, r1;\nelect.sync _|q, 0xffffffff;\nsetp.ne.and.u32 p, %1, 0, q;\n"
        "mapa.shared::cluster.u32 r0, %0, 0;\nmapa.shared::cluster.u32 r1, %0, 1;\n"
        "@p mbarrier.arrive.shared::cluster.b64 _, [r0];\n@p mbarrier.arrive.shared::cluster.b64 _, [r1];\n}" :: "r"(bar), "r"(on) : "memory");
}
__device__ __forceinline__ void st_partner64(uint32_t a, uint32_t bar, uint32_t cta, float x, float y) {
    asm volatile("{\n.reg .b32 ra, rb;\nmapa.shared::cluster.u32 ra, %0, %2;\nmapa.shared::cluster.u32 rb, %1, %2;\n"
        "st.async.weak.shared::cluster.mbarrier::complete_tx::bytes.v2.f32 [ra], {%3, %4}, [rb];\n}" :: "r"(a), "r"(bar), "r"(cta), "f"(x), "f"(y) : "memory");
}
__device__ __forceinline__ void mbar_wait(uint32_t bar, uint32_t parity) {
    asm volatile("{\n.reg .pred P1;\n.reg .u32 cnt;\nmov.u32 cnt, 0;\nLAB_WAIT:\n"
        "mbarrier.try_wait.parity.shared::cta.b64 P1, [%0], %1;\n@P1 bra DONE;\n"
        "add.u32 cnt, cnt, 1;\nsetp.lt.u32 P1, cnt, 1000000;\n@P1 bra LAB_WAIT;\ntrap;\nDONE:\n}" :: "r"(bar), "r"(parity) : "memory");
}
__device__ __forceinline__ uint64_t policy_evict_first() { uint64_t p; asm("createpolicy.fractional.L2::evict_first.b64 %0, 1.0;" : "=l"(p)); return p; }
#define EF_W 1
#define EF_WO 1
#define EF_F 1
#define EF_M 1
__device__ __forceinline__ void bulk_commit() { asm volatile("cp.async.bulk.commit_group;" ::: "memory"); }
__device__ __forceinline__ void bulk_wait() { asm volatile("cp.async.bulk.wait_group 0;" ::: "memory"); }
__device__ __forceinline__ void tmap_prefetch(const CUtensorMap* tm) { asm volatile("prefetch.tensormap [%0];" :: "l"(tm) : "memory"); }
#define EL "{\n.reg .pred e;\nelect.sync _|e, 0xffffffff;\n@e "
__device__ __forceinline__ void expect_tx_e(uint32_t bar, uint32_t bytes) { asm volatile(EL "mbarrier.arrive.expect_tx.shared::cta.b64 _, [%0], %1;\n}" :: "r"(bar), "r"(bytes) : "memory"); }
__device__ __forceinline__ void tma2_e(uint32_t dst, const CUtensorMap* tm, int c0, int c1, uint32_t bar) {
    asm volatile(EL "cp.async.bulk.tensor.2d.shared::cluster.global.mbarrier::complete_tx::bytes [%0], [%1, {%3, %4}], [%2];\n}"
        :: "r"(dst), "l"(tm), "r"(bar), "r"(c0), "r"(c1) : "memory");
}
__device__ __forceinline__ void tma2_ef_e(uint32_t dst, const CUtensorMap* tm, int c0, int c1, uint32_t bar) {
    asm volatile(EL "cp.async.bulk.tensor.2d.shared::cluster.global.mbarrier::complete_tx::bytes.L2::cache_hint [%0], [%1, {%3, %4}], [%2], %5;\n}"
        :: "r"(dst), "l"(tm), "r"(bar), "r"(c0), "r"(c1), "l"(policy_evict_first()) : "memory");
}
__device__ __forceinline__ void tma2_mc_e(uint32_t dst, const CUtensorMap* tm, int c0, int c1, uint32_t bar) {
    if (!EF_WO) asm volatile(EL "cp.async.bulk.tensor.2d.shared::cluster.global.mbarrier::complete_tx::bytes.multicast::cluster [%0], [%1, {%3, %4}], [%2], %5;\n}"
        :: "r"(dst), "l"(tm), "r"(bar), "r"(c0), "r"(c1), "h"((uint16_t)3) : "memory");
    else
    asm volatile(EL "cp.async.bulk.tensor.2d.shared::cluster.global.mbarrier::complete_tx::bytes.multicast::cluster.L2::cache_hint [%0], [%1, {%3, %4}], [%2], %5, %6;\n}"
        :: "r"(dst), "l"(tm), "r"(bar), "r"(c0), "r"(c1), "h"((uint16_t)3), "l"(policy_evict_first()) : "memory");
}
__device__ __forceinline__ void tma3_ef_e(uint32_t dst, const CUtensorMap* tm, int row, int blk, uint32_t bar) {
    if (!EF_F) asm volatile(EL "cp.async.bulk.tensor.3d.shared::cluster.global.mbarrier::complete_tx::bytes [%0], [%1, {0, %3, %4}], [%2];\n}"
        :: "r"(dst), "l"(tm), "r"(bar), "r"(row), "r"(blk) : "memory");
    else
    asm volatile(EL "cp.async.bulk.tensor.3d.shared::cluster.global.mbarrier::complete_tx::bytes.L2::cache_hint [%0], [%1, {0, %3, %4}], [%2], %5;\n}"
        :: "r"(dst), "l"(tm), "r"(bar), "r"(row), "r"(blk), "l"(policy_evict_first()) : "memory");
}
__device__ __forceinline__ void tma4_ef_e(uint32_t dst, const CUtensorMap* tm, int row, int blk, uint32_t bar) {
    if (!EF_W) asm volatile(EL "cp.async.bulk.tensor.4d.shared::cluster.global.mbarrier::complete_tx::bytes [%0], [%1, {0, %3, %4, 0}], [%2];\n}"
        :: "r"(dst), "l"(tm), "r"(bar), "r"(row), "r"(blk) : "memory");
    else
    asm volatile(EL "cp.async.bulk.tensor.4d.shared::cluster.global.mbarrier::complete_tx::bytes.L2::cache_hint [%0], [%1, {0, %3, %4, 0}], [%2], %5;\n}"
        :: "r"(dst), "l"(tm), "r"(bar), "r"(row), "r"(blk), "l"(policy_evict_first()) : "memory");
}
__device__ __forceinline__ void bulk_load_e(uint32_t dst, const void* src, uint32_t bytes, uint32_t bar) {
    asm volatile(EL "cp.async.bulk.shared::cluster.global.mbarrier::complete_tx::bytes [%0], [%1], %2, [%3];\n}" :: "r"(dst), "l"(src), "r"(bytes), "r"(bar) : "memory");
}
__device__ __forceinline__ void bulk_store_e(void* dst, uint32_t src, uint32_t bytes) {
    asm volatile(EL "cp.async.bulk.global.shared::cta.bulk_group [%0], [%1], %2;\n}" :: "l"(dst), "r"(src), "r"(bytes) : "memory");
}
__device__ __forceinline__ void st_flag_e(void* p, unsigned v) { asm volatile(EL "st.relaxed.gpu.global.u32 [%0], %1;\n}" :: "l"(p), "r"(v) : "memory"); }
__device__ __forceinline__ void mbar_init(uint32_t bar, uint32_t cnt) { asm volatile("mbarrier.init.shared::cta.b64 [%0], %1;" :: "r"(bar), "r"(cnt) : "memory"); }
__device__ __forceinline__ bool elect_one() {
    uint32_t p;
    asm volatile("{\n.reg .pred P;\nelect.sync _|P, 0xffffffff;\nselp.u32 %0, 1, 0, P;\n}" : "=r"(p));
    return p;
}
__device__ __forceinline__ void wg_fence() { asm volatile("wgmma.fence.sync.aligned;" ::: "memory"); }
__device__ __forceinline__ void wg_commit() { asm volatile("wgmma.commit_group.sync.aligned;" ::: "memory"); }
template<int N> __device__ __forceinline__ void wg_wait() { asm volatile("wgmma.wait_group.sync.aligned %0;" :: "n"(N) : "memory"); }
template<int N> __device__ __forceinline__ void acc_fence(float (&d)[N]) {
    #pragma unroll
    for (int i = 0; i < N; i++) asm volatile("" : "+f"(d[i]) :: "memory");
}
__device__ __forceinline__ uint64_t mk_desc(uint32_t addr, uint32_t lbo, uint32_t sbo, uint32_t swz) {
    uint32_t lo = ((addr & 0x3FFFF) >> 4) | (((lbo & 0x3FFFF) >> 4) << 16);
    uint32_t hi = (sbo >> 4) | (swz << 30);
    return ((uint64_t)hi << 32) | lo;
}
__device__ __forceinline__ uint64_t desc_add(uint64_t d, uint32_t bytes) { return (d & 0xffffffff00000000ull) | (uint32_t)((uint32_t)d + (bytes >> 4)); }
__device__ __forceinline__ uint64_t desc_raw(uint64_t d, uint32_t inc) { return (d & 0xffffffff00000000ull) | (uint32_t)((uint32_t)d + inc); }
__device__ __forceinline__ void fence_async_smem() { asm volatile("fence.proxy.async.shared::cta;" ::: "memory"); }
__device__ __forceinline__ void bar_sync(int id, int n) { asm volatile("bar.sync %0, %1;" :: "r"(id), "r"(n) : "memory"); }
__device__ __forceinline__ void bar_arrive(int id, int n) { asm volatile("bar.arrive %0, %1;" :: "r"(id), "r"(n) : "memory"); }
template<int R> __device__ __forceinline__ void reg_inc() { asm volatile("setmaxnreg.inc.sync.aligned.u32 %0;" :: "n"(R)); }
template<int R> __device__ __forceinline__ void reg_dec() { asm volatile("setmaxnreg.dec.sync.aligned.u32 %0;" :: "n"(R)); }
__device__ __forceinline__ void cluster_arrive() { asm volatile("barrier.cluster.arrive.relaxed.aligned;" ::: "memory"); }
__device__ __forceinline__ void cluster_wait() { asm volatile("barrier.cluster.wait.acquire.aligned;" ::: "memory"); }

__device__ __forceinline__ void stsm4(uint32_t addr, uint32_t r0, uint32_t r1, uint32_t r2, uint32_t r3) {
    asm volatile("stmatrix.sync.aligned.m8n8.x4.shared.b16 [%0], {%1,%2,%3,%4};" :: "r"(addr), "r"(r0), "r"(r1), "r"(r2), "r"(r3) : "memory");
}
__device__ __forceinline__ void ldsm4(uint32_t& r0, uint32_t& r1, uint32_t& r2, uint32_t& r3, uint32_t addr) {
    asm volatile("ldmatrix.sync.aligned.m8n8.x4.shared.b16 {%0,%1,%2,%3}, [%4];" : "=r"(r0), "=r"(r1), "=r"(r2), "=r"(r3) : "r"(addr) : "memory");
}
__device__ __forceinline__ void ldsm4t(uint32_t& r0, uint32_t& r1, uint32_t& r2, uint32_t& r3, uint32_t addr) {
    asm volatile("ldmatrix.sync.aligned.m8n8.x4.trans.shared.b16 {%0,%1,%2,%3}, [%4];" : "=r"(r0), "=r"(r1), "=r"(r2), "=r"(r3) : "r"(addr) : "memory");
}
__device__ __forceinline__ void mma16816(float (&d)[4], uint32_t a0, uint32_t a1, uint32_t a2, uint32_t a3, uint32_t b0, uint32_t b1) {
    asm("mma.sync.aligned.m16n8k16.row.col.f32.bf16.bf16.f32 {%0,%1,%2,%3}, {%4,%5,%6,%7}, {%8,%9}, {%0,%1,%2,%3};"
        : "+f"(d[0]), "+f"(d[1]), "+f"(d[2]), "+f"(d[3]) : "r"(a0), "r"(a1), "r"(a2), "r"(a3), "r"(b0), "r"(b1));
}
__device__ __forceinline__ void mma1688(float (&d)[4], uint32_t a0, uint32_t a1, uint32_t b0) {
    asm("mma.sync.aligned.m16n8k8.row.col.f32.bf16.bf16.f32 {%0,%1,%2,%3}, {%4,%5}, {%6}, {%0,%1,%2,%3};"
        : "+f"(d[0]), "+f"(d[1]), "+f"(d[2]), "+f"(d[3]) : "r"(a0), "r"(a1), "r"(b0));
}
__device__ __forceinline__ uint4 lds128(uint32_t a) { uint4 v; asm volatile("ld.shared.v4.b32 {%0,%1,%2,%3}, [%4];" : "=r"(v.x), "=r"(v.y), "=r"(v.z), "=r"(v.w) : "r"(a) : "memory"); return v; }
__device__ __forceinline__ uint2 lds64(uint32_t a) { uint2 v; asm volatile("ld.shared.v2.b32 {%0,%1}, [%2];" : "=r"(v.x), "=r"(v.y) : "r"(a) : "memory"); return v; }
__device__ __forceinline__ uint32_t lds32(uint32_t a) { uint32_t v; asm volatile("ld.shared.b32 %0, [%1];" : "=r"(v) : "r"(a) : "memory"); return v; }
__device__ __forceinline__ float ldsf(uint32_t a) { float v; asm volatile("ld.shared.f32 %0, [%1];" : "=f"(v) : "r"(a) : "memory"); return v; }
__device__ __forceinline__ uint32_t lds16(uint32_t a) { uint16_t v; asm volatile("ld.shared.b16 %0, [%1];" : "=h"(v) : "r"(a) : "memory"); return v; }
__device__ __forceinline__ void sts128(uint32_t a, uint4 v) { asm volatile("st.shared.v4.b32 [%0], {%1,%2,%3,%4};" :: "r"(a), "r"(v.x), "r"(v.y), "r"(v.z), "r"(v.w) : "memory"); }
__device__ __forceinline__ void sts64(uint32_t a, uint32_t x, uint32_t y) { asm volatile("st.shared.v2.b32 [%0], {%1,%2};" :: "r"(a), "r"(x), "r"(y) : "memory"); }
__device__ __forceinline__ void sts32(uint32_t a, uint32_t x) { asm volatile("st.shared.b32 [%0], %1;" :: "r"(a), "r"(x) : "memory"); }
__device__ __forceinline__ void stsf(uint32_t a, float x) { asm volatile("st.shared.f32 [%0], %1;" :: "r"(a), "f"(x) : "memory"); }
__device__ __forceinline__ void sts16(uint32_t a, uint32_t x) { asm volatile("st.shared.b16 [%0], %1;" :: "r"(a), "h"((uint16_t)x) : "memory"); }

__device__ __forceinline__ uint4 ldg128(const void* p) { uint4 v; asm volatile("ld.global.nc.v4.b32 {%0,%1,%2,%3}, [%4];" : "=r"(v.x), "=r"(v.y), "=r"(v.z), "=r"(v.w) : "l"(p)); return v; }
__device__ __forceinline__ uint2 ldg64(const void* p) { uint2 v; asm volatile("ld.global.nc.v2.b32 {%0,%1}, [%2];" : "=r"(v.x), "=r"(v.y) : "l"(p)); return v; }
__device__ __forceinline__ void stg128(void* p, uint4 v) { asm volatile("st.global.v4.b32 [%0], {%1,%2,%3,%4};" :: "l"(p), "r"(v.x), "r"(v.y), "r"(v.z), "r"(v.w) : "memory"); }
__device__ __forceinline__ void stg_fill(void* p, uint32_t v) { asm volatile("st.global.v4.b32 [%0], {%1,%1,%1,%1};" :: "l"(p), "r"(v) : "memory"); }
__device__ __forceinline__ void st_ll(void* p, uint32_t x, uint32_t y, uint32_t z, uint32_t w) {
    asm volatile("{\n.reg .b128 t;\n.reg .b64 a, b;\nmov.b64 a, {%1, %2};\nmov.b64 b, {%3, %4};\nmov.b128 t, {a, b};\nst.relaxed.gpu.global.b128 [%0], t;\n}"
        :: "l"(p), "r"(x), "r"(y), "r"(z), "r"(w) : "memory");
}
__device__ __forceinline__ uint4 ld_ll(const void* p) {
    uint4 v;
    asm volatile("{\n.reg .b128 t;\n.reg .b64 a, b;\nld.relaxed.gpu.global.b128 t, [%4];\nmov.b128 {a, b}, t;\nmov.b64 {%0, %1}, a;\nmov.b64 {%2, %3}, b;\n}"
        : "=r"(v.x), "=r"(v.y), "=r"(v.z), "=r"(v.w) : "l"(p) : "memory");
    return v;
}
__device__ __forceinline__ void ld_ll_if(uint4& v, const void* p, bool go) {
    asm volatile("{\n.reg .b128 t;\n.reg .b64 a, b;\n.reg .pred q;\nsetp.ne.u32 q, %5, 0;\nmov.b64 a, {%0, %1};\nmov.b64 b, {%2, %3};\nmov.b128 t, {a, b};\n"
        "@q ld.relaxed.gpu.global.b128 t, [%4];\nmov.b128 {a, b}, t;\nmov.b64 {%0, %1}, a;\nmov.b64 {%2, %3}, b;\n}"
        : "+r"(v.x), "+r"(v.y), "+r"(v.z), "+r"(v.w) : "l"(p), "r"((uint32_t)go) : "memory");
}
__device__ __forceinline__ void st_ll8(void* p, uint32_t x, uint32_t y) {
    asm volatile("{\n.reg .b64 a;\nmov.b64 a, {%1, %2};\nst.relaxed.gpu.global.b64 [%0], a;\n}" :: "l"(p), "r"(x), "r"(y) : "memory");
}
__device__ __forceinline__ void st_ll4(void* p, uint32_t x) { asm volatile("st.relaxed.gpu.global.b32 [%0], %1;" :: "l"(p), "r"(x) : "memory"); }
__device__ __forceinline__ unsigned ld_rlx(const void* p) { unsigned v; asm volatile("ld.relaxed.gpu.global.u32 %0, [%1];" : "=r"(v) : "l"(p) : "memory"); return v; }
__device__ __forceinline__ void red_add4(void* p, float x, float y, float z, float w) {
    asm volatile("red.relaxed.gpu.global.add.v4.f32 [%0], {%1, %2, %3, %4};" :: "l"(p), "f"(x), "f"(y), "f"(z), "f"(w) : "memory");
}
__device__ __forceinline__ void fence_rel_gpu() { asm volatile("fence.proxy.async.global;\nfence.release.gpu;" ::: "memory"); }
__device__ __forceinline__ void fence_acq_gpu() { asm volatile("fence.acquire.gpu;" ::: "memory"); }
template<int N> __device__ __forceinline__ void poll_words(uint4 (&v)[N], const uint4* p, int stride, uint32_t tag) {
    #pragma unroll 1
    for (int it = 0; it < POLL_MAX; it++) {
        bool ok = true;
        #pragma unroll
        for (int i = 0; i < N; i++) v[i] = ld_ll(p + i * stride);
        #pragma unroll
        for (int i = 0; i < N; i++) ok = ok && (v[i].w == tag);
        if (__all_sync(0xffffffffu, ok)) break;
    }
}
template<int B> __device__ __forceinline__ uint32_t low_byte(float v, uint32_t src) { return __byte_perm(__float_as_uint(v), src, 0x3214 + B); }
__device__ __forceinline__ uint32_t low_bits(float v, uint32_t tag2) { return (__float_as_uint(v) & ~3u) | tag2; }
__device__ __forceinline__ bool tagged2(uint32_t w, uint32_t tag2) { return (w & 3u) == tag2; }
__device__ __forceinline__ uint32_t umax4(uint4 v) { return max(max(v.x, v.y), max(v.z, v.w)); }
constexpr uint32_t ONE2 = 0x3F803F80u;
__device__ __forceinline__ uint32_t pack2(float lo, float hi) { uint32_t d; asm("cvt.rn.bf16x2.f32 %0, %1, %2;" : "=r"(d) : "f"(hi), "f"(lo)); return d; }
__device__ __forceinline__ float bf_lo(uint32_t v) { return __uint_as_float(v << 16); }
__device__ __forceinline__ float bf_lo_after(uint32_t v, float nonneg) { float d; asm("prmt.b32 %0, %1, %2, 0x10ff;" : "=f"(d) : "r"(v), "f"(nonneg)); return d; }
__device__ __forceinline__ float bf_hi_after(uint32_t v, float nonneg) { float d; asm("prmt.b32 %0, %1, %2, 0x32ff;" : "=f"(d) : "r"(v), "f"(nonneg)); return d; }
__device__ __forceinline__ float bf_hi(uint32_t v) { return __uint_as_float(v & 0xffff0000u); }
__device__ __forceinline__ float rbf(float x) { return bf_lo(pack2(x, 0.f)); }
__device__ __forceinline__ uint32_t hsub2(uint32_t a, uint32_t b) { uint32_t d; asm("sub.rn.bf16x2 %0, %1, %2;" : "=r"(d) : "r"(a), "r"(b)); return d; }
__device__ __forceinline__ uint32_t hadd2(uint32_t a, uint32_t b) { uint32_t d; asm("add.rn.bf16x2 %0, %1, %2;" : "=r"(d) : "r"(a), "r"(b)); return d; }
__device__ __forceinline__ uint32_t hmul2(uint32_t a, uint32_t b) { uint32_t d; asm("mul.rn.bf16x2 %0, %1, %2;" : "=r"(d) : "r"(a), "r"(b)); return d; }
__device__ __forceinline__ uint32_t hmax2(uint32_t a, uint32_t b) { uint32_t d; asm("max.bf16x2 %0, %1, %2;" : "=r"(d) : "r"(a), "r"(b)); return d; }
__device__ __forceinline__ uint32_t hmin2(uint32_t a, uint32_t b) { uint32_t d; asm("min.bf16x2 %0, %1, %2;" : "=r"(d) : "r"(a), "r"(b)); return d; }
__device__ __forceinline__ float ex2(float x) { float y; asm("ex2.approx.ftz.f32 %0, %1;" : "=f"(y) : "f"(x)); return y; }
__device__ __forceinline__ float rcp(float x) { float y; asm("rcp.approx.ftz.f32 %0, %1;" : "=f"(y) : "f"(x)); return y; }
__device__ __forceinline__ float shfl_x(float v, int m) { return __shfl_xor_sync(0xffffffffu, v, m); }
constexpr float LOG2E = 1.4426950408889634f;
__device__ __forceinline__ float sigmoidf(float x) { return rcp(1.0f + ex2(-LOG2E * x)); }
__device__ __forceinline__ uint32_t ln_pair(uint32_t x, uint32_t m2, float rinv, uint32_t a, uint32_t s) {
    uint32_t d = hsub2(x, m2);
    uint32_t n = pack2(bf_lo(d) * rinv, bf_hi(d) * rinv);
    return hadd2(hmul2(n, a), s);
}
struct Recip { uint32_t hi, lo; };
__device__ __forceinline__ Recip split_recip(float r) { Recip q; q.hi = pack2(r, r); const float l = r - bf_hi(q.hi); q.lo = pack2(l, l); return q; }
__device__ __forceinline__ uint32_t hdiv2(uint32_t n, Recip r) { uint32_t d; asm("fma.rn.bf16x2 %0, %1, %2, %3;" : "=r"(d) : "r"(n), "r"(r.hi), "r"(hmul2(n, r.lo))); return d; }
__device__ __forceinline__ uint32_t ln_pair(uint32_t x, uint32_t m2, Recip r, uint32_t a, uint32_t s) { return hadd2(hmul2(hdiv2(hsub2(x, m2), r), a), s); }
__device__ __forceinline__ void ln_final(float s1, float s2, uint32_t& m2, float& rinv) {
    const float mean = s1 * (1.0f / 1024.0f), var = fmaf(-mean, mean, s2 * (1.0f / 1024.0f));
    m2 = pack2(mean, mean);
    float sd;
    asm("sqrt.approx.ftz.f32 %0, %1;" : "=f"(sd) : "f"(rbf(rbf(fmaxf(var, 0.f)) + 1e-5f)));
    rinv = rcp(rbf(sd));
}
__device__ __forceinline__ uint32_t f2key(float f) { uint32_t u = __float_as_uint(f); return (u & 0x80000000u) ? ~u : (u | 0x80000000u); }

__device__ __forceinline__ void fm_extrema(const uint32_t (&p)[16], float& cp, float& cn) {
    uint32_t mx = p[0], mn = p[0];
    #pragma unroll
    for (int k = 1; k < 15; k += 2) { mx = hmax2(hmax2(mx, p[k]), p[k + 1]); mn = hmin2(hmin2(mn, p[k]), p[k + 1]); }
    mx = hmax2(mx, p[15]); mn = hmin2(mn, p[15]);
    cp = -fmaxf(bf_lo(mx), bf_hi(mx)) * LOG2E; cn = fminf(bf_lo(mn), bf_hi(mn)) * LOG2E;
}
template<int TB> __device__ __forceinline__ void wgmma_n32_rs(float (&d)[16], uint32_t a0, uint32_t a1, uint32_t a2, uint32_t a3, uint64_t db, int sc) {
  asm volatile("{\n.reg .pred p;\nsetp.ne.b32 p, %21, 0;\n"
    "wgmma.mma_async.sync.aligned.m64n32k16.f32.bf16.bf16 {%0, %1, %2, %3, %4, %5, %6, %7, %8, %9, %10, %11, %12, %13, %14, %15}, {%16,%17,%18,%19}, %20, p, 1, 1, %22;\n}\n"
    : "+f"(d[0]), "+f"(d[1]), "+f"(d[2]), "+f"(d[3]), "+f"(d[4]), "+f"(d[5]), "+f"(d[6]), "+f"(d[7]), "+f"(d[8]), "+f"(d[9]), "+f"(d[10]), "+f"(d[11]), "+f"(d[12]), "+f"(d[13]), "+f"(d[14]), "+f"(d[15])
    : "r"(a0), "r"(a1), "r"(a2), "r"(a3), "l"(db), "r"(sc), "n"(TB));
}
template<int TA, int TB> __device__ __forceinline__ void wgmma_n40_ss(float (&d)[20], uint64_t da, uint64_t db, int sc) {
  asm volatile("{\n.reg .pred p;\nsetp.ne.b32 p, %22, 0;\n"
    "wgmma.mma_async.sync.aligned.m64n40k16.f32.bf16.bf16 {%0, %1, %2, %3, %4, %5, %6, %7, %8, %9, %10, %11, %12, %13, %14, %15, %16, %17, %18, %19}, %20, %21, p, 1, 1, %23, %24;\n}\n"
    : "+f"(d[0]), "+f"(d[1]), "+f"(d[2]), "+f"(d[3]), "+f"(d[4]), "+f"(d[5]), "+f"(d[6]), "+f"(d[7]), "+f"(d[8]), "+f"(d[9]), "+f"(d[10]), "+f"(d[11]), "+f"(d[12]), "+f"(d[13]), "+f"(d[14]), "+f"(d[15]), "+f"(d[16]), "+f"(d[17]), "+f"(d[18]), "+f"(d[19])
    : "l"(da), "l"(db), "r"(sc), "n"(TA), "n"(TB));
}
template<int TA, int TB> __device__ __forceinline__ void wgmma_n128_ss(float (&d)[64], uint64_t da, uint64_t db, int sc) {
  asm volatile("{\n.reg .pred p;\nsetp.ne.b32 p, %66, 0;\n"
    "wgmma.mma_async.sync.aligned.m64n128k16.f32.bf16.bf16 {%0, %1, %2, %3, %4, %5, %6, %7, %8, %9, %10, %11, %12, %13, %14, %15, %16, %17, %18, %19, %20, %21, %22, %23, %24, %25, %26, %27, %28, %29, %30, %31, %32, %33, %34, %35, %36, %37, %38, %39, %40, %41, %42, %43, %44, %45, %46, %47, %48, %49, %50, %51, %52, %53, %54, %55, %56, %57, %58, %59, %60, %61, %62, %63}, %64, %65, p, 1, 1, %67, %68;\n}\n"
    : "+f"(d[0]), "+f"(d[1]), "+f"(d[2]), "+f"(d[3]), "+f"(d[4]), "+f"(d[5]), "+f"(d[6]), "+f"(d[7]), "+f"(d[8]), "+f"(d[9]), "+f"(d[10]), "+f"(d[11]), "+f"(d[12]), "+f"(d[13]), "+f"(d[14]), "+f"(d[15]), "+f"(d[16]), "+f"(d[17]), "+f"(d[18]), "+f"(d[19]), "+f"(d[20]), "+f"(d[21]), "+f"(d[22]), "+f"(d[23]), "+f"(d[24]), "+f"(d[25]), "+f"(d[26]), "+f"(d[27]), "+f"(d[28]), "+f"(d[29]), "+f"(d[30]), "+f"(d[31]), "+f"(d[32]), "+f"(d[33]), "+f"(d[34]), "+f"(d[35]), "+f"(d[36]), "+f"(d[37]), "+f"(d[38]), "+f"(d[39]), "+f"(d[40]), "+f"(d[41]), "+f"(d[42]), "+f"(d[43]), "+f"(d[44]), "+f"(d[45]), "+f"(d[46]), "+f"(d[47]), "+f"(d[48]), "+f"(d[49]), "+f"(d[50]), "+f"(d[51]), "+f"(d[52]), "+f"(d[53]), "+f"(d[54]), "+f"(d[55]), "+f"(d[56]), "+f"(d[57]), "+f"(d[58]), "+f"(d[59]), "+f"(d[60]), "+f"(d[61]), "+f"(d[62]), "+f"(d[63])
    : "l"(da), "l"(db), "r"(sc), "n"(TA), "n"(TB));
}
template<int TB> __device__ __forceinline__ void wgmma_n128_rs(float (&d)[64], uint32_t a0, uint32_t a1, uint32_t a2, uint32_t a3, uint64_t db, int sc) {
  asm volatile("{\n.reg .pred p;\nsetp.ne.b32 p, %69, 0;\n"
    "wgmma.mma_async.sync.aligned.m64n128k16.f32.bf16.bf16 {%0, %1, %2, %3, %4, %5, %6, %7, %8, %9, %10, %11, %12, %13, %14, %15, %16, %17, %18, %19, %20, %21, %22, %23, %24, %25, %26, %27, %28, %29, %30, %31, %32, %33, %34, %35, %36, %37, %38, %39, %40, %41, %42, %43, %44, %45, %46, %47, %48, %49, %50, %51, %52, %53, %54, %55, %56, %57, %58, %59, %60, %61, %62, %63}, {%64,%65,%66,%67}, %68, p, 1, 1, %70;\n}\n"
    : "+f"(d[0]), "+f"(d[1]), "+f"(d[2]), "+f"(d[3]), "+f"(d[4]), "+f"(d[5]), "+f"(d[6]), "+f"(d[7]), "+f"(d[8]), "+f"(d[9]), "+f"(d[10]), "+f"(d[11]), "+f"(d[12]), "+f"(d[13]), "+f"(d[14]), "+f"(d[15]), "+f"(d[16]), "+f"(d[17]), "+f"(d[18]), "+f"(d[19]), "+f"(d[20]), "+f"(d[21]), "+f"(d[22]), "+f"(d[23]), "+f"(d[24]), "+f"(d[25]), "+f"(d[26]), "+f"(d[27]), "+f"(d[28]), "+f"(d[29]), "+f"(d[30]), "+f"(d[31]), "+f"(d[32]), "+f"(d[33]), "+f"(d[34]), "+f"(d[35]), "+f"(d[36]), "+f"(d[37]), "+f"(d[38]), "+f"(d[39]), "+f"(d[40]), "+f"(d[41]), "+f"(d[42]), "+f"(d[43]), "+f"(d[44]), "+f"(d[45]), "+f"(d[46]), "+f"(d[47]), "+f"(d[48]), "+f"(d[49]), "+f"(d[50]), "+f"(d[51]), "+f"(d[52]), "+f"(d[53]), "+f"(d[54]), "+f"(d[55]), "+f"(d[56]), "+f"(d[57]), "+f"(d[58]), "+f"(d[59]), "+f"(d[60]), "+f"(d[61]), "+f"(d[62]), "+f"(d[63])
    : "r"(a0), "r"(a1), "r"(a2), "r"(a3), "l"(db), "r"(sc), "n"(TB));
}
template<int TB> __device__ __forceinline__ void wgmma_n256_rs(float (&d)[128], uint32_t a0, uint32_t a1, uint32_t a2, uint32_t a3, uint64_t db, int sc) {
  asm volatile("{\n.reg .pred p;\nsetp.ne.b32 p, %133, 0;\n"
    "wgmma.mma_async.sync.aligned.m64n256k16.f32.bf16.bf16 {%0, %1, %2, %3, %4, %5, %6, %7, %8, %9, %10, %11, %12, %13, %14, %15, %16, %17, %18, %19, %20, %21, %22, %23, %24, %25, %26, %27, %28, %29, %30, %31, %32, %33, %34, %35, %36, %37, %38, %39, %40, %41, %42, %43, %44, %45, %46, %47, %48, %49, %50, %51, %52, %53, %54, %55, %56, %57, %58, %59, %60, %61, %62, %63, %64, %65, %66, %67, %68, %69, %70, %71, %72, %73, %74, %75, %76, %77, %78, %79, %80, %81, %82, %83, %84, %85, %86, %87, %88, %89, %90, %91, %92, %93, %94, %95, %96, %97, %98, %99, %100, %101, %102, %103, %104, %105, %106, %107, %108, %109, %110, %111, %112, %113, %114, %115, %116, %117, %118, %119, %120, %121, %122, %123, %124, %125, %126, %127}, {%128,%129,%130,%131}, %132, p, 1, 1, %134;\n}\n"
    : "+f"(d[0]), "+f"(d[1]), "+f"(d[2]), "+f"(d[3]), "+f"(d[4]), "+f"(d[5]), "+f"(d[6]), "+f"(d[7]), "+f"(d[8]), "+f"(d[9]), "+f"(d[10]), "+f"(d[11]), "+f"(d[12]), "+f"(d[13]), "+f"(d[14]), "+f"(d[15]), "+f"(d[16]), "+f"(d[17]), "+f"(d[18]), "+f"(d[19]), "+f"(d[20]), "+f"(d[21]), "+f"(d[22]), "+f"(d[23]), "+f"(d[24]), "+f"(d[25]), "+f"(d[26]), "+f"(d[27]), "+f"(d[28]), "+f"(d[29]), "+f"(d[30]), "+f"(d[31]), "+f"(d[32]), "+f"(d[33]), "+f"(d[34]), "+f"(d[35]), "+f"(d[36]), "+f"(d[37]), "+f"(d[38]), "+f"(d[39]), "+f"(d[40]), "+f"(d[41]), "+f"(d[42]), "+f"(d[43]), "+f"(d[44]), "+f"(d[45]), "+f"(d[46]), "+f"(d[47]), "+f"(d[48]), "+f"(d[49]), "+f"(d[50]), "+f"(d[51]), "+f"(d[52]), "+f"(d[53]), "+f"(d[54]), "+f"(d[55]), "+f"(d[56]), "+f"(d[57]), "+f"(d[58]), "+f"(d[59]), "+f"(d[60]), "+f"(d[61]), "+f"(d[62]), "+f"(d[63]), "+f"(d[64]), "+f"(d[65]), "+f"(d[66]), "+f"(d[67]), "+f"(d[68]), "+f"(d[69]), "+f"(d[70]), "+f"(d[71]), "+f"(d[72]), "+f"(d[73]), "+f"(d[74]), "+f"(d[75]), "+f"(d[76]), "+f"(d[77]), "+f"(d[78]), "+f"(d[79]), "+f"(d[80]), "+f"(d[81]), "+f"(d[82]), "+f"(d[83]), "+f"(d[84]), "+f"(d[85]), "+f"(d[86]), "+f"(d[87]), "+f"(d[88]), "+f"(d[89]), "+f"(d[90]), "+f"(d[91]), "+f"(d[92]), "+f"(d[93]), "+f"(d[94]), "+f"(d[95]), "+f"(d[96]), "+f"(d[97]), "+f"(d[98]), "+f"(d[99]), "+f"(d[100]), "+f"(d[101]), "+f"(d[102]), "+f"(d[103]), "+f"(d[104]), "+f"(d[105]), "+f"(d[106]), "+f"(d[107]), "+f"(d[108]), "+f"(d[109]), "+f"(d[110]), "+f"(d[111]), "+f"(d[112]), "+f"(d[113]), "+f"(d[114]), "+f"(d[115]), "+f"(d[116]), "+f"(d[117]), "+f"(d[118]), "+f"(d[119]), "+f"(d[120]), "+f"(d[121]), "+f"(d[122]), "+f"(d[123]), "+f"(d[124]), "+f"(d[125]), "+f"(d[126]), "+f"(d[127])
    : "r"(a0), "r"(a1), "r"(a2), "r"(a3), "l"(db), "r"(sc), "n"(TB));
}

#define T_S0 3300
#define T_S1 5800
#define G1W 1
#define LNP 1
#define CG1 232
#define JU 2
#define WPF 0
#define FPF 0
#define KW 8
#define DEP 2
#define STAG 0
#define KVSH 0
#define KVDLY 1200
#define PREWAIT 1
#define OUN 4
#define DNE 8
#define YGATE B_YP
#define YDLY 0
#define OUTGATE B_CAND
#define SGATE 2
#define T_P0 1500
#define T_P1 3000
#define LATEFREE 1
#define NC 2
#define T_W1 2800
#define T_WD 0
#define NW0 32
#define PFN 3
#define PFJ 2
#define PFM 4
#define WOJ 10
#define WON 1
#define NLD 1
#define VFIRST 2
#define T_X0 450
#define T_XD 600
#define MCB 1
#define ORIENT 2
#define PFORDER 0x51634
#define PFORDER2 0x51
#define PFW0 2
#define CLRJ 3
#define CLRK 8
#define JPF 0
#define CLRGATE (B_FB + 4)
#define KVC0 0
#define CLRS 50
#define OGATE 5
#define PFD 0
#define GBN 6
#define BG1 99
#define BG2 99
#define BG3 99
#define BG4 99
#define BG5 99
#define SYNCQ 640
#define SYNCG 4
#define BSP 0
#define T_INI 500
#define T_WLATE 4000
#define T_REST 7000
#define T_COL 3000
#define PF_START 9000
#define PF_FIRST 2
#define PFP 400
#define CREG 208
#define TMA_WO tma2_ef_e
#define TMA_M tma2_ef_e
#define TMA_F tma2_ef_e
#define JUN 4
constexpr int JUU = JUN, OUU = OUN;
struct Ptrs { const bf16 *x, *c, *wmod, *wr, *wg, *wu, *wd, *wqkv, *wo; bf16* out; Scratch* s; };

#define BAR(i) (sb + OFF_BAR + 8u * (i))

__device__ __forceinline__ int d_block(int hg, int n) {
    const int m = n - (n >= 9 ? 9 : 2);
    return n < 2 ? 2 * hg + n : 2 * (m + (m >= hg)) + (n >= 9);
}
__host__ __device__ constexpr uint32_t bar_count(int i) {
    return (MCB && i >= B_ED && i < B_ED + 16) ? 16 : ((i >= B_E1 && i < B_E1 + 3) || (i >= B_S0FREE && i < B_PHI + 4) || i == B_OWN || i == B_OWN + 1 || (i >= B_ED && i < B_ED + 16)
            || i == B_STFREE || i == B_X2 || i == B_OUTW || i == B_YP) ? 8
         : ((i >= B_KVD && i < B_KVD + 2) || i == B_ST2) ? 4 : (i == B_KVF || i == B_KVF + 1 ) ? 2 : 1;
}
template<int I0, int I1> __device__ __forceinline__ void init_barriers(uint32_t sb) {
    #pragma unroll
    for (int i = I0; i < I1; i++) mbar_init(BAR(i), bar_count(i));
}
template<int N> __device__ __forceinline__ uint32_t pop_max(uint32_t (&k)[N]) {
    uint32_t m = k[0];
    #pragma unroll
    for (int i = 1; i < N; i++) m = max(m, k[i]);
    m = __reduce_max_sync(0xffffffffu, m);
    #pragma unroll
    for (int i = 0; i < N; i++) k[i] = (k[i] == m) ? 0u : k[i];
    return m;
}
__device__ __forceinline__ uint32_t mod_pos(int step, int g) { return step * 64 + (g >> 1) * 16 + (g & 1) * 4; }
__device__ __forceinline__ void fma8(float (&a)[8], uint4 w, float s) {
    a[0] = fmaf(bf_lo(w.x), s, a[0]); a[1] = fmaf(bf_hi(w.x), s, a[1]); a[2] = fmaf(bf_lo(w.y), s, a[2]); a[3] = fmaf(bf_hi(w.y), s, a[3]);
    a[4] = fmaf(bf_lo(w.z), s, a[4]); a[5] = fmaf(bf_hi(w.z), s, a[5]); a[6] = fmaf(bf_lo(w.w), s, a[6]); a[7] = fmaf(bf_hi(w.w), s, a[7]);
}
__device__ __forceinline__ float reduce8(const float (&v)[8], int lane) {
    const bool b3 = lane & 16, b2 = lane & 8, b1 = lane & 4;
    float a[4], b[2];
    #pragma unroll
    for (int i = 0; i < 4; i++) { float keep = b3 ? v[4 + i] : v[i], send = b3 ? v[i] : v[4 + i]; a[i] = keep + shfl_x(send, 16); }
    #pragma unroll
    for (int i = 0; i < 2; i++) { float keep = b2 ? a[2 + i] : a[i], send = b2 ? a[i] : a[2 + i]; b[i] = keep + shfl_x(send, 8); }
    float keep = b1 ? b[1] : b[0], send = b1 ? b[0] : b[1];
    return keep + shfl_x(send, 4);
}
__device__ __forceinline__ bool mod_collect(uint4 w0, uint4 w1, uint4 w2, uint4 w3, uint32_t sb, int jb, int lane, uint32_t tag2) {
    const uint32_t add = lane < 16 ? ONE2 : 0u;
    const uint32_t lo = pack2((__uint_as_float(w0.x) + __uint_as_float(w1.x)) + (__uint_as_float(w2.x) + __uint_as_float(w3.x)),
                              (__uint_as_float(w0.y) + __uint_as_float(w1.y)) + (__uint_as_float(w2.y) + __uint_as_float(w3.y)));
    const uint32_t hi = pack2((__uint_as_float(w0.z) + __uint_as_float(w1.z)) + (__uint_as_float(w2.z) + __uint_as_float(w3.z)),
                              (__uint_as_float(w0.w) + __uint_as_float(w1.w)) + (__uint_as_float(w2.w) + __uint_as_float(w3.w)));
    sts64(sb + OFF_MODS + jb * 256 + (lane & 15) * 16 + (lane >> 4) * 8, hadd2(lo, add), hadd2(hi, add));
    return tagged2(w0.w, tag2) && tagged2(w1.w, tag2) && tagged2(w2.w, tag2) && tagged2(w3.w, tag2);
}
__device__ __forceinline__ void phi_issue(float (&pp)[2][16], const uint32_t* a, uint32_t sb, int pair) {
    const uint64_t dw = mk_desc(sb + OFF_WPHI + pair * 4096, 16, 512, 2);
    wg_fence();
    #pragma unroll
    for (int ks = 0; ks < 2; ks++)
        #pragma unroll
        for (int h = 0; h < 2; h++) wgmma_n32_rs<1>(pp[h], a[8 * h + 4 * ks], a[8 * h + 4 * ks + 1], a[8 * h + 4 * ks + 2], a[8 * h + 4 * ks + 3], desc_add(dw, h * 2048 + ks * 1024), ks);
    wg_commit();
}
__device__ __forceinline__ void phi_transpose(float (&pp)[2][16], uint32_t (&pt)[16], uint32_t wr, uint32_t rd) {
    wg_wait<0>();
    acc_fence(pp[0]); acc_fence(pp[1]);
    #pragma unroll
    for (int q = 0; q < 4; q++) {
        const float (&a)[16] = pp[q >> 1]; const int o = 8 * (q & 1);
        stsm4(wr ^ (q << 5), pack2(a[o], a[o + 1]), pack2(a[o + 2], a[o + 3]), pack2(a[o + 4], a[o + 5]), pack2(a[o + 6], a[o + 7]));
    }
    __syncwarp();
    #pragma unroll
    for (int i = 0; i < 4; i++) { const uint4 v = lds128(rd ^ (i << 4)); pt[4 * i] = v.x; pt[4 * i + 1] = v.y; pt[4 * i + 2] = v.z; pt[4 * i + 3] = v.w; }
    __syncwarp();
}

__global__ void __cluster_dims__(2, 1, 1) __launch_bounds__(NTHREADS, 1)
fused_kernel(const Ptrs p, const __grid_constant__ CUtensorMap tmW, const __grid_constant__ CUtensorMap tmWo, const __grid_constant__ CUtensorMap tmPhi,
             const __grid_constant__ CUtensorMap tmG, const __grid_constant__ CUtensorMap tmU, const __grid_constant__ CUtensorMap tmD,
             const __grid_constant__ CUtensorMap tmX, const __grid_constant__ CUtensorMap tmO, const __grid_constant__ CUtensorMap tmM,
             const __grid_constant__ CUtensorMap tmR, const __grid_constant__ CUtensorMap tmG8, const __grid_constant__ CUtensorMap tmU8,
             const __grid_constant__ CUtensorMap tmD8)
{
    extern __shared__ __align__(1024) uint8_t smem_raw[];
    const uint32_t sb = smem_u32(smem_raw);
    const int tid = threadIdx.x, lane = tid & 31, warp = __shfl_sync(0xffffffffu, tid >> 5, 0);
    const int b = blockIdx.x;
    const int pr = b >> 1, rank = b & 1;
    const int cls = pr < 4 ? 15 : pr < 36 ? 2 * ((pr - 4) & 7) : 2 * ((pr - 36) % 7) + 1, mem = pr < 4 ? pr : pr < 36 ? (pr - 4) >> 3 : (pr - 36) / 7;
    const int hg = (((cls + 1) >> 1) & 1) * 4 + mem, rb = (cls >> 1) * 2 + rank;
    const bool ffn = b < 112;
    const uint32_t cstart = clk32();

    if (warp >= 8) {
        const int t = tid & 127, w4 = warp & 3, g = lane >> 2, c = lane & 3;
        if (w4 == 0) TS(40);
        reg_dec<504 - 2 * CG1>();
        if (w4 == 2) TS(41);
        if (w4 == 0) { tmap_prefetch(&tmX); tmap_prefetch(&tmW); }
        if (w4 == 3) tmap_prefetch(&tmM);
        if (w4 < 2) while (clk32() - cstart < T_INI) {}
        if (elect_one()) {
            if (w4 & 2) { if (w4 & 1) init_barriers<B_WS, B_COUNT>(sb); else init_barriers<B_XS, B_WS>(sb); }
            else { if (w4 & 1) init_barriers<B_MP, B_XS>(sb); else init_barriers<0, B_MP>(sb); }
        }
        __syncwarp();
        if (w4 == 1) {
            asm volatile("fence.mbarrier_init.release.cluster;" ::: "memory");
            expect_tx_e(BAR(B_PX), 2048); sts32(sb + OFF_SEEN, 0);
        }
        if (w4 == 0) TS(42);
        bar_arrive(0, 384);
        if (w4 == 2) {
            #pragma unroll 1
            for (int i = 0; i < 4; i++) {
                while (clk32() - cstart < T_X0 + i * T_XD) {}
                bulk_load_e(sb + OFF_XS + i * 8192u, p.x + (size_t)(b * 16 + i * 4) * 1024, 8192, BAR(B_XS + i));
                expect_tx_e(BAR(B_XS + i), 8192);
                if (i == 0) TS(43);
            }
        }
        if (w4 == 3 && b < 32 * NC) {
            while (b >= NW0 && clk32() - cstart < T_W1 + (b >> 5) * T_WD) {}
            #pragma unroll 1
            for (int i = 0; i < 4; i++) {
                tma2_ef_e(sb + OFF_WST + i * 8192u, &tmM, (((b >> 2) & 1) ? 0 : 1024) + (b >> 3) * 64, (b & 3) * 256 + i * 64, BAR(B_WS + i));
                expect_tx_e(BAR(B_WS + i), 8192);
            }
            TS(44);
        }
        cluster_arrive();
        const uint32_t tag = ld_rlx(p.s->done) + 1, tag2 = tag % 3u;
        if (w4 == 0) {
            int piece = ffn ? 0 : 20;
            uint4* clr = p.s->kvp + (hg * 1024 + KVC0 * 128 + rb) * 32 + lane;
            #pragma unroll 1
            for (int j = 0; j < 3; j++) {
                while (clk32() - cstart < (j ? T_P1 : T_P0)) {}
                if (lane < 24) asm volatile("prefetch.global.L2 [%0];" :: "l"((const char*)p.wqkv + ((j * 128 + b) * 24 + lane) * 128));
            }
            int s = 0;
            #pragma unroll 1
            for (int j = 0; j < 17; j++) {
                if (j >= 3) mbar_wait(BAR(B_E1 + s), ((j / 3) - 1) & 1);
                else if (j >= SGATE) mbar_wait(BAR(B_STFREE), 0);
                else while (clk32() - cstart < (j ? T_S1 : T_S0)) {}
                const uint32_t st = sb + OFF_RING + s * 65536u;
                if (j < 16) {
                    expect_tx_e(BAR(B_F1 + s), 65536);
                    tma4_ef_e(st + 16384u, &tmW, j * 64, hg * 2, BAR(B_F1 + s));
                    tma2_e(st, &tmX, j * 64, rb * 128, BAR(B_F1 + s));
                } else {
                    #pragma unroll 1
                    for (int n = 0; n < 4; n++) {
                        if (!(n & 1)) expect_tx_e(BAR(B_FB + 4 + (n >> 1)), 16384);
                        TMA_WO(st + n * 8192u, &tmWo, hg * 128 + (n & 1) * 64, (2 * hg + (n >> 1)) * 64, BAR(B_FB + 4 + (n >> 1)));
                    }
                }
                if (j == 1) TS(50);
                s = s == 2 ? 0 : s + 1;
                if (j == 3) expect_tx_e(BAR(B_PF), ffn ? 20480 : 0);
                #pragma unroll 1
                for (; j >= 3 && piece < min(20, j < 16 ? (j - PFJ) * PFM / 4 : 20); piece++)
                    tma2_e(sb + OFF_PAR, piece < 8 ? &tmD8 : (piece & 1) ? &tmU8 : &tmG8, piece < 8 ? rank * 512 + piece * 64 : pr * 64,
                           piece < 8 ? pr * 64 : rank * 512 + (11 - (piece >> 1)) * 64, BAR(B_PF));
                if (j >= WOJ && j < WOJ + 4 * WON) asm volatile("prefetch.global.L2 [%0];" :: "l"((const char*)p.wo + ((j - WOJ) & 3) * 524288 + (b * 32 + lane) * 128));
                if (j >= CLRJ && j < CLRJ + 8 - KVC0) {
                    #pragma unroll
                    for (int i = 0; i < 8; i++) stg_fill(clr + i * 512, EMPTY);
                    clr += 4096;
                }
            }
            mbar_wait(BAR(B_E1 + 0), 1);
            expect_tx_e(BAR(B_S0), ffn ? 65536 : 32768);
            tma2_ef_e(sb + OFF_XT, &tmX, hg * 128, rb * 128, BAR(B_S0)); tma2_ef_e(sb + OFF_XT + 16384u, &tmX, hg * 128 + 64, rb * 128, BAR(B_S0));
            #pragma unroll 1
            for (int i = 0; i < (ffn ? 2 : 0); i++) tma2_ef_e(sb + OFF_GA + i * 16384u, i ? &tmU : &tmG, pr * 64, rank * 512, BAR(B_S0));
        } else if (w4 == 1) {
            while (clk32() - cstart < T_COL) {}
            #pragma unroll 1
            for (int it = 0, jb = 0, ph = 0; it < POLL_MAX && jb < 16; it++) {
                const int n = jb < NLD ? 1 : min(4, 16 - jb);
                if (jb >= NLD) {
                    expect_tx_e(BAR(B_MP), n * 2048);
                    bulk_load_e(sb + OFF_WPHI, p.s->mp + jb * 128, n * 2048, BAR(B_MP));
                    mbar_wait(BAR(B_MP), ph);
                    ph ^= 1;
                }
                #pragma unroll 1
                for (int q = 0; q < n; q++) {
                    uint4 w[4];
                    if (jb < NLD) {
                        #pragma unroll
                        for (int i = 0; i < 4; i++) w[i] = ld_ll(p.s->mp + (jb * 8 + (lane >> 4) * 4 + i) * 16 + (lane & 15));
                    } else {
                        #pragma unroll
                        for (int i = 0; i < 4; i++) w[i] = lds128(sb + OFF_WPHI + q * 2048 + (lane >> 4) * 1024 + (lane & 15) * 16 + i * 256);
                    }
                    if (!__all_sync(0xffffffffu, mod_collect(w[0], w[1], w[2], w[3], sb, jb, lane, tag2))) { if (jb >= 4) __nanosleep(300); break; }
                    arrive_many(BAR(B_MOD + jb), bar_count(B_MOD));
                    if (jb == 0) TS(51);
                    if (jb == 4) TS(5);
                    if (jb == 15) TS(8);
                    jb++;
                }
            }
            fence_async_smem();
            __syncwarp();
            expect_tx_e(BAR(B_WPHI), 8192);
            tma2_e(sb + OFF_WPHI, &tmPhi, 0, hg * 128, BAR(B_WPHI));
            #pragma unroll 1
            for (int i = 0; i < 4; i++) {
                uint4* rw = p.s->rowh + (rb * 8 + i * 2 + (lane >> 4)) * 128 + hg * 16 + (lane & 15);
                stg_fill(rw, EMPTY); stg_fill(rw + 16384, EMPTY);
                if (lane < 18) stg_fill(p.s->kvf + (hg * 4 + i) * 288 + (lane < 16 ? (rb >> 2) * 64 + (rb & 3) * 8 + (lane >> 3) * 32 + (lane & 7) : 240 + rb * 2 + lane), EMPTY);
            }
            if (hg == 0 && lane < 8) stg_fill(p.s->cand + rb * 8 + lane, 0);
            if (lane < 28) stg_fill(lane < 16 ? p.s->st2 + rb * 128 + hg * 16 + lane : lane < 20 ? p.s->flo + (rb * 16 + hg * 2) * 2 + lane - 16
                                    : p.s->rsc + ((rb * 4 + ((lane - 20) >> 1)) * 8 + hg) * 2 + (lane & 1), 0);
            fence_rel_gpu();
            #pragma unroll 1
            for (int i = 0; i < (ffn ? 9 : 8); i++) {
                uint4* d = (i < 8 ? p.s->os + (rb * 16 + 2 * hg) * 1024 + i * 256 : p.s->yp + pr * 512 + rank * 128) + lane;
                #pragma unroll
                for (int q = 0; q < 4; q++) { stg_fill(d + q * 32, EMPTY); stg_fill(d + (i < 8 ? 128 : 256) + q * 32, EMPTY); }
            }
            TS(36);
        } else {
            const int hw = w4 & 1;
            const uint32_t fb = BAR(B_RF + 2 * hw);
            if (w4 == 2) {
                if (lane < 8) stg_fill(p.s->rest + b * 8 + lane, 0);
                else if (lane < 24 && b >= 32 * NC) stg_fill(p.s->mp + b * 16 + lane - 8, EMPTY);
            }
            bar_sync(3, 320);
            const uint32_t buf = sb + OFF_SP + hw * 8192u;
            #pragma unroll 1
            for (int job = b < 32 * NC; job < 2; job++) {
                const int nr = job ? 8 : 4;
                const int c0 = job ? 2048 + b * 32 : (((b >> 2) & 1) ? 0 : 1024) + (b >> 3) * 64 + hw * 32;
                const int row0 = job ? hw * 512 : (b & 3) * 256;
                while (clk32() - cstart < (job ? T_REST : T_WLATE)) __nanosleep(100);
                float macc[8] = {0.f, 0.f, 0.f, 0.f, 0.f, 0.f, 0.f, 0.f};
                #pragma unroll 1
                for (int q = -2; q < nr; q++) {
                    if (q >= 0) {
                        mbar_wait(fb + (q & 1) * 8, (q >> 1) & 1);
                        const uint32_t sv0 = sb + OFF_SILU + (row0 + q * 64 + g) * 2, wa = buf + (q & 1) * 4096u + lane * 16u;
                        #pragma unroll JUU
                        for (int i = 0; i < 8; i += 2) {
                            const uint32_t s0 = lds16(sv0 + i * 16), s1 = lds16(sv0 + i * 16 + 16);
                            const uint4 w0 = lds128(wa + i * 512u), w1 = lds128(wa + i * 512u + 512u);
                            fma8(macc, w0, bf_lo(s0)); fma8(macc, w1, bf_lo(s1));
                        }
                    }
                    __syncwarp();
                    if (q + 2 < nr) {
                        expect_tx_e(fb + (q & 1) * 8, 4096);
                        TMA_M(buf + (q & 1) * 4096u, &tmR, c0, row0 + (q + 2) * 64, fb + (q & 1) * 8);
                    }
                }
                stsf(sb + OFF_RED0 + (job ? hw * 256 + (c * 8 + g) * 4 : mod_pos(hw * 2 + (c >> 1), g) + (c & 1) * 8), reduce8(macc, lane));
                bar_sync(4, 64);
                if (w4 == 2) {
                    const uint4 u0 = lds128(sb + OFF_RED0 + (lane & 15) * 16), u1 = lds128(sb + OFF_RED0 + 256 + (lane & 15) * 16);
                    const float v0 = __uint_as_float(u0.x) + __uint_as_float(u1.x), v1 = __uint_as_float(u0.y) + __uint_as_float(u1.y);
                    const float v2 = __uint_as_float(u0.z) + __uint_as_float(u1.z), v3 = __uint_as_float(u0.w) + __uint_as_float(u1.w);
                    const uint32_t add = (b >> 5) == 2 ? ONE2 : 0u;
                    if (job == 0) { if (lane < 16) st_ll(p.s->mp + b * 16 + lane, u0.x, u0.y, u0.z, low_bits(__uint_as_float(u0.w), tag2)); TS(13); }
                    else { if (lane < 8) st_ll(p.s->rest + b * 8 + lane, hadd2(pack2(v0, v1), add), hadd2(pack2(v2, v3), add), 0, tag); TS(33); }
                }
                bar_sync(4, 64);
            }
            tmap_prefetch(hw ? &tmWo : &tmG); tmap_prefetch(hw ? &tmU : &tmD); tmap_prefetch(hw ? &tmPhi : &tmO);
        }
        __syncwarp();
        cluster_wait();
        bar_sync(2, 128);
        reg_inc<504 - 2 * CREG>();
        if (w4 == 0) TS(6);
        #pragma unroll 1
        for (int pp = 0; pp < 2; pp++) {
            mbar_wait(BAR(B_PHI + pp), 0);
            if (w4 == 0) TS(pp ? 59 : 52);
            fence_async_smem();
            float o[2][20];
            const uint32_t vb = OFF_V + pp * 16384u;
            const uint64_t dp = mk_desc(sb + (pp ? OFF_PHI1 : OFF_PHI0), 16, 1024, 1), dv = mk_desc(sb + vb, OFF_ONES - vb, 512, 2);
            wg_fence();
            #pragma unroll
            for (int hh = 0; hh < 2; hh++) {
                #pragma unroll
                for (int ks = 0; ks < 8; ks++)
                    wgmma_n40_ss<1, 1>(o[hh], desc_add(dp, hh * 16384 + ks * 2048), desc_raw(dv, (hh * 8 + ks) * (64 - (64 << 16))), ks);
                wg_commit();
            }
            #pragma unroll
            for (int hh = 0; hh < 2; hh++) {
                if (hh) wg_wait<0>(); else wg_wait<1>();
                acc_fence(o[hh]);
                if (hh) arrive_one(BAR(B_KVD + pp));
                if (hh == KVSH && pp && w4 < 2) {
                    mbar_wait(BAR(B_KVD), 0);
                    bulk_load_e(sb + OFF_KVS + w4 * 8192u, p.s->kvp + ((hg * 4 + w4) * 16 + rb) * 512, 8192, BAR(B_KVS + w4));
                    expect_tx_e(BAR(B_KVS + w4), 8192);
                }
                uint4* dst = p.s->kvp + (((hg * 4 + 2 * pp + hh) * 16 + (t >> 3)) * 16 + rb) * 32 + (t & 7);
                const float (&a)[20] = o[hh];
                #pragma unroll
                for (int k = 0; k < 2; k++) {
                    const uint32_t z = __float_as_uint(a[16 + 2 * k]);
                    st_ll(dst + k * 8, low_byte<1>(a[4 * k], z), low_byte<2>(a[4 * k + 1], z), low_byte<3>(a[4 * k + 2], z), low_bits(a[4 * k + 3], tag2));
                    st_ll(dst + 16 + k * 8, __float_as_uint(a[8 + 4 * k]), __float_as_uint(a[9 + 4 * k]), __float_as_uint(a[10 + 4 * k]), low_bits(a[11 + 4 * k], tag2));
                }
            }
        }
        if (w4 == 0) TS(17);
        {
            uint4* const fin = p.s->kvf + (hg * 4 + w4) * 288;
            {
                const uint4* src = p.s->kvp + ((hg * 4 + w4) * 16 + rb) * 512 + lane;
                uint4 w[16];
                if (KVSH < 2 && w4 < 2) {
                    mbar_wait(BAR(B_KVS + w4), 1);
                    #pragma unroll
                    for (int i = 0; i < 16; i++) w[i] = lds128(sb + OFF_KVS + w4 * 8192u + i * 512u + lane * 16u);
                } else {
                    if (KVDLY) { const uint32_t c0 = clk32(); while (clk32() - c0 < KVDLY) {} }
                    #pragma unroll
                    for (int i = 0; i < 16; i++) w[i].w = EMPTY;
                }
                #pragma unroll 1
                for (int it = 0; it < POLL_MAX; it++) {
                    bool ok = true;
                    #pragma unroll
                    for (int i = 0; i < 16; i++) { const bool miss = !tagged2(w[i].w, tag2); ok = ok && !miss; ld_ll_if(w[i], src + i * 32, miss); }
                    if (__all_sync(0xffffffffu, ok)) break;
                }
                if (w4 == 0) TS(18);
                if (w4 == 3) TS(10);
                float s[5], s2[5];
                #pragma unroll
                for (int i = 0; i < 16; i++) {
                    const float z = __uint_as_float(__byte_perm(__byte_perm(w[i].x, w[i].y, 0x0400), w[i].z, 0x4210));
                    float (&a)[5] = (i & 1) ? s2 : s;
                    if (i < 2) { a[0] = __uint_as_float(w[i].x); a[1] = __uint_as_float(w[i].y); a[2] = __uint_as_float(w[i].z); a[3] = __uint_as_float(w[i].w); a[4] = z; }
                    else { a[0] += __uint_as_float(w[i].x); a[1] += __uint_as_float(w[i].y); a[2] += __uint_as_float(w[i].z); a[3] += __uint_as_float(w[i].w); a[4] += z; }
                }
                #pragma unroll
                for (int i = 0; i < 5; i++) s[i] += s2[i];
                char* d = (char*)fin + ((rb >> 2) * 16 + (rb & 3) * 2 + (g & 1)) * 64 + (((lane >> 3) ^ (rb & 3)) << 4) + c * 4;
                st_ll4(d, pack2(s[0], s[1]));
                st_ll4(d + 512, pack2(s[2], s[3]));
                if (lane < 16 && c < 2) st_ll4((char*)fin + 4096 + rb * 32 + (g * 2 + c) * 4, pack2(s[4], s[4]));
            }
            fence_acq_gpu();
            uint4 v[9];
            #pragma unroll 1
            for (int it = 0; it < POLL_MAX; it++) {
                uint32_t m = 0;
                #pragma unroll
                for (int k = 0; k < 9; k++) v[k] = ld_ll(fin + k * 32 + lane);
                #pragma unroll
                for (int k = 0; k < 9; k++) m = max(m, umax4(v[k]));
                if (__all_sync(0xffffffffu, m != EMPTY)) break;
            }
            #pragma unroll
            for (int k = 0; k < 8; k++) sts128(sb + OFF_SP + w4 * 4096u + k * 512u + lane * 16u, v[k]);
            const uint32_t za = sb + OFF_Z + ((lane >> 3) * 16 + ((lane >> 1) & 3) * 2 + (lane & 1) * 8) * 64u + ((w4 ^ ((lane >> 1) & 3)) << 4);
            sts128(za, make_uint4(v[8].x, v[8].x, v[8].x, v[8].x)); sts128(za + 64, make_uint4(v[8].z, v[8].z, v[8].z, v[8].z));
            __syncwarp();
            arrive_one(BAR(B_KVF + (w4 >> 1)));
            if (w4 == 0) TS(19);
            if (w4 == 3) TS(1);
        }
        if (w4 == 0) {
            const unsigned* f = (const unsigned*)(p.s->flo + (rb * 16 + d_block(hg, lane & 15)) * 2);
            const uint4* const a0 = p.s->os + rb * 16384;
            uint32_t seen = 0;
            uint32_t kb = hg ? 0 : 2, s = 4, freeb = BAR(B_OWN), par = 0;
            fence_rel_gpu();
            arrive_one(BAR(B_REL));
            mbar_wait(BAR(B_OWN), 0);
            #pragma unroll 1
            for (int n = 2; n < 16; n++) {
                if (!((seen >> n) & 1)) {
                    if (n >= 8) asm volatile("ld.acquire.cta.shared.u32 %0, [%1];" : "=r"(seen) : "r"(sb + OFF_SEEN) : "memory");
                    #pragma unroll 1
                    for (int it = 0; it < POLL_MAX && !((seen >> n) & 1); it++) { seen = __ballot_sync(0xffffffffu, ld_rlx(f) == tag); fence_acq_gpu(); }
                }
                mbar_wait(freeb, par);
                TR(64 + n);
                bulk_load_e(sb + OFF_DA + s * 16384u, a0 + kb * 1024, 16384, BAR(B_FA + s));
                expect_tx_e(BAR(B_FA + s), 16384);
                if (n == 2) TS(2);
                TR(16 + n);
                if (n == OGATE) arrive_one(BAR(B_OGO));
                if (n == 5 || n == 6) mbar_wait(BAR(B_PUB + n - 5), 0);
                kb = n == 8 ? 1 : kb + 2;
                if ((kb >> 1) == hg) kb += 2;
                s = (SLOT_A >> (4 * n + 4)) & 7;
                if (n >= 5) { freeb = BAR(B_ED + n - 5); par = 1; } else if (n == 3) freeb = BAR(B_OWN + 1);
            }
        } else if (w4 == 1) {
            if (ffn) { expect_tx_e(BAR(B_GU), 98304); expect_tx_e(BAR(B_WD), 65536); }
            mbar_wait(BAR(B_S0FREE), 0);
            #pragma unroll 1
            for (int n = 2; n < (ffn ? 20 : 16); n++) {
                if (n == BG1) mbar_wait(BAR(B_KVF + 1), 0);
                if (n == BG2) mbar_wait(BAR(B_PUB), 0);
                if (n == BG5) mbar_wait(BAR(B_OGO), 1);
                if (n >= 6) mbar_wait(BAR(B_ED + n - 6), 1);
                if (n < 16) {
                    const uint32_t s = (SLOT_B >> (4 * n)) & 7, bar = BAR(B_FB + s), dst = sb + OFF_DB + s * 16384u;
                    expect_tx_e(bar, 16384);
                    if (MCB && n >= 6) tma2_mc_e(dst + rank * 8192u, &tmWo, hg * 128 + rank * 64, d_block(hg, n) * 64, bar);
                    else { TMA_WO(dst, &tmWo, hg * 128, d_block(hg, n) * 64, bar); TMA_WO(dst + 8192u, &tmWo, hg * 128 + 64, d_block(hg, n) * 64, bar); }
                    if (ffn && n >= GBN && n < GBN + 2) TMA_F(sb + OFF_GB + (n - GBN) * 16384u, n > GBN ? &tmU : &tmG, pr * 64, rank * 512 + 128, BAR(B_GU));
                } else if (n < 18) {
                    if (n == 16) TS(49);
                    TMA_F(sb + OFF_UP0 + (n & 1) * 16384u, (n & 1) ? &tmU : &tmG, pr * 64, rank * 512 + 256, BAR(B_GU));
                    TMA_F(sb + OFF_UP1 + (n & 1) * 16384u, (n & 1) ? &tmU : &tmG, pr * 64, rank * 512 + 384, BAR(B_GU));
                } else {
                    tma3_ef_e(sb + OFF_DN0 + (n & 1) * 16384u, &tmD, pr * 64, rank * 8 + (n & 1) * 2, BAR(B_WD));
                    tma3_ef_e(sb + OFF_DN1 + (n & 1) * 16384u, &tmD, pr * 64, rank * 8 + 4 + (n & 1) * 2, BAR(B_WD));
                }
            }
        } else if (w4 == 3) {
            const unsigned* f = (const unsigned*)(p.s->flo + (rb * 16 + d_block(hg, lane & 15)) * 2);
            uint32_t seen = 0xffff0003u;
            mbar_wait(BAR(B_PUB + 1), 0);
            #pragma unroll 1
            for (int it = 0; it < POLL_MAX && seen != 0xffffffffu; it++) {
                const uint32_t m = seen | __ballot_sync(0xffffffffu, !((seen >> lane) & 1) && ld_rlx(f) == tag);
                if (m != seen) {
                    seen = m;
                    fence_acq_gpu();
                    __syncwarp();
                    asm volatile(EL "st.release.cta.shared.u32 [%0], %1;\n}" :: "r"(sb + OFF_SEEN), "r"(seen) : "memory");
                }
            }
        } else {
            asm volatile("fence.proxy.async.global;" ::: "memory");
            #pragma unroll 1
            for (int q = 0; q < 2; q++) {
                if (q) mbar_wait(BAR(B_OGO), 1);
                mbar_wait(BAR(B_OWN + q), 0);
                fence_async_smem();
                bulk_store_e(p.s->os + (rb * 16 + 2 * hg + q) * 1024, sb + OFF_OWN + q * 16384u, 16384);
                bulk_commit();
                bulk_wait();
                mbar_wait(BAR(B_REL), 0);
                st_flag_e(p.s->flo + (rb * 16 + 2 * hg + q) * 2, tag);
                arrive_one(BAR(B_PUB + q));
                if (q == 0) TS(3);
                TR(q);
            }
            mbar_wait(BAR(B_PF), 1);
            {
                uint4 w[4];
                poll_words<4>(w, p.s->rest + hg * 32 + lane, 256, tag);
                sts128(sb + OFF_PAR + lane * 32, make_uint4(w[2].x, w[1].x, w[3].x, w[0].x));
                sts128(sb + OFF_PAR + lane * 32 + 16, make_uint4(w[2].y, w[1].y, w[3].y, w[0].y));
                const uint2 wr = ldg64(p.wr + hg * 128 + lane * 4);
                sts64(sb + OFF_BQ + lane * 8, hmul2(w[2].x, wr.x), hmul2(w[2].y, wr.y));
            }
            float s = 0.f;
            #pragma unroll 1
            for (int i = 0; i < 2; i++) {
                uint4 w[4]; uint2 wr[4];
                #pragma unroll
                for (int q = 0; q < 4; q++) wr[q] = ldg64(p.wr + (lane + 32 * q + 128 * i) * 4);
                poll_words<4>(w, p.s->rest + 512 + i * 128 + lane, 32, tag);
                #pragma unroll
                for (int q = 0; q < 4; q++) { const uint32_t r0 = hmul2(w[q].x, wr[q].x), r1 = hmul2(w[q].y, wr[q].y); s += (bf_lo(r0) + bf_hi(r0)) + (bf_lo(r1) + bf_hi(r1)); }
            }
            __syncwarp();
            #pragma unroll
            for (int m = 16; m >= 1; m >>= 1) s += shfl_x(s, m);
            if (lane == 0) stsf(sb + OFF_ATOT, s);
            __syncwarp();
            arrive_one(BAR(B_PAR));
        }
        __syncwarp();
        {
            mbar_wait(BAR(B_PAR), 0);
            uint2 pa[4];
            #pragma unroll
            for (int i = 0; i < 4; i++) pa[i] = lds64(sb + OFF_PAR + (lane & 15) * 64 + i * 16);
            const uint4 wr = ldg128(p.wr + hg * 128 + (lane & 15) * 8);
            const float atot = ldsf(sb + OFF_ATOT);
            mbar_wait(BAR(B_X2), 0);
            uint4 w;
            #pragma unroll 1
            for (int it = 0; it < POLL_MAX; it++) {
                w = ld_ll(p.s->st2 + rb * 128 + t);
                if (__all_sync(0xffffffffu, __uint_as_float(w.w) == 8.0f)) break;
            }
            if (w4 == 0) TS(31);
            uint32_t m2; float rinv;
            ln_final(__uint_as_float(w.x), __uint_as_float(w.y), m2, rinv);
            uint32_t k[1] = {(f2key(fmaf(-bf_lo(m2), atot, __uint_as_float(w.z)) * rinv) & ~0xfffu) | ((2047 - rb * 128 - t) << 1)};
            const uint32_t best0 = pop_max(k), best1 = pop_max(k) | 1u, grp = rb * 4 + w4;
            if (hg == 0 && lane < 2) st_ll(p.s->cand + grp * 2 + lane, best0, best1, 0, tag);
            if (w4 == 3) TS(23);
            const uint32_t row = 127 - (((lane < 16 ? best0 : best1) >> 1) & 127u);
            const uint4 xv = lds128(sb + OFF_OUT + (row >> 3) * 2048u + ((lane >> 3) & 1) * 1024u + (row & 7) * 128u + (((lane ^ row) & 7) << 4));
            sts64(sb + OFF_ST2 + t * 8, m2, __float_as_uint(rinv));
            __syncwarp();
            arrive_one(BAR(B_ST2));
            const uint32_t rm = __shfl_sync(0xffffffffu, m2, row & 31);
            const Recip rr = split_recip(__shfl_sync(0xffffffffu, rinv, row & 31));
            const uint32_t h0 = ln_pair(xv.x, rm, rr, pa[0].x, pa[0].y), h1 = ln_pair(xv.y, rm, rr, pa[1].x, pa[1].y);
            const uint32_t h2 = ln_pair(xv.z, rm, rr, pa[2].x, pa[2].y), h3 = ln_pair(xv.w, rm, rr, pa[3].x, pa[3].y);
            uint4* d = p.s->rowh + (grp * 2 + (lane >> 4)) * 128 + hg * 16 + (lane & 15);
            st_ll(d, h0, h1, h2, h3);
            st_ll(d + 16384, xv.x, xv.y, xv.z, xv.w);
            float r = (fmaf(bf_lo(h0), bf_lo(wr.x), bf_hi(h0) * bf_hi(wr.x)) + fmaf(bf_lo(h1), bf_lo(wr.y), bf_hi(h1) * bf_hi(wr.y)))
                    + (fmaf(bf_lo(h2), bf_lo(wr.z), bf_hi(h2) * bf_hi(wr.z)) + fmaf(bf_lo(h3), bf_lo(wr.w), bf_hi(h3) * bf_hi(wr.w)));
            #pragma unroll
            for (int m = 8; m >= 1; m >>= 1) r += shfl_x(r, m);
            if (!(lane & 15)) st_ll(p.s->rsc + (grp * 8 + hg) * 2 + (lane >> 4), __float_as_uint(r), 0, 0, tag);
            if (w4 == 3) TS(24);
        }
        if (w4 == 0) {
            uint4 cv[2];
            poll_words<2>(cv, p.s->cand + lane * 2, 64, tag);
            __syncwarp();
            TS(11);
            const uint32_t ka = min(cv[0].x, cv[1].x), kb = max(cv[0].y, cv[1].y);
            uint32_t k0 = max(cv[0].x, cv[1].x), k1 = max(ka, kb), k2 = min(ka, kb), k3 = min(cv[0].y, cv[1].y), id[4];
            uint4 hv[4][2], sc;
            const uint4* ha[4];
            #pragma unroll
            for (int i = 0; i < 4; i++) {
                const uint32_t m = __reduce_max_sync(0xffffffffu, k0);
                if (k0 == m) { k0 = k1; k1 = k2; k2 = k3; }
                id[i] = (m & 0xfffu) ^ 0xffeu;
                ha[i] = p.s->rowh + ((id[i] >> 6) * 2 + (id[i] & 1)) * 128 + rank * 64 + lane;
                hv[i][0] = ld_ll(ha[i]); hv[i][1] = ld_ll(ha[i] + 32);
            }
            const uint32_t myid = lane < 16 ? (lane < 8 ? id[0] : id[1]) : (lane < 24 ? id[2] : id[3]), row = myid >> 1;
            const uint4* sa = p.s->rsc + ((myid >> 6) * 8 + (lane & 7)) * 2 + (myid & 1);
            sc = ld_ll(sa);
            sts32(sb + OFF_SEL + 32 + (lane >> 3) * 4, row);
            __syncwarp();
            arrive_one(BAR(B_CAND));
            #pragma unroll 1
            for (int it = 0; it < POLL_MAX; it++) {
                uint32_t m = 0;
                #pragma unroll
                for (int i = 0; i < 4; i++) m = max(m, max(hv[i][0].x, hv[i][1].x));
                if (__all_sync(0xffffffffu, m != EMPTY && sc.w == tag)) break;
                #pragma unroll
                for (int i = 0; i < 4; i++) { hv[i][0] = ld_ll(ha[i]); hv[i][1] = ld_ll(ha[i] + 32); }
                sc = ld_ll(sa);
            }
            TS(12);
            #pragma unroll
            for (int i = 0; i < 4; i++) { sts128(sb + OFF_ROWS + i * 1056u + lane * 16u, hv[i][0]); sts128(sb + OFF_ROWS + i * 1056u + 528u + lane * 16u, hv[i][1]); }
            __syncwarp();
            arrive_one(BAR(B_ROWS));
            TS(25);
            float r = __uint_as_float(sc.x);
            r += shfl_x(r, 1); r += shfl_x(r, 2); r += shfl_x(r, 4);
            r = rbf(r);
            const uint32_t key = (f2key(r) & 0xffff0000u) | (0xffffu - row);
            uint32_t kq[1] = {key};
            const uint32_t best0 = pop_max(kq), best1 = pop_max(kq), tok = key == best0 ? 0 : key == best1 ? 1 : 2;
            sts32(sb + OFF_SEL + 48 + (lane >> 3) * 4, tok);
            if (tok < 2) sts128(sb + OFF_SEL + tok * 16, make_uint4(row, (myid >> 6) * 2 + (myid & 1), __float_as_uint(r), 0));
            __syncwarp();
            arrive_one(BAR(B_SEL));
        } else if (w4 == 1) {
            mbar_wait(BAR(B_SEL), 0);
            const uint4 sel = lds128(sb + OFF_SEL + rank * 16);
            const int col = pr * 16 + c * 2 + (lane >> 4) + (lane & 8);
            uint32_t xs, hs; uint4 gw;
            #pragma unroll 1
            for (int it = 0; it < POLL_MAX; it++) {
                const char* a = (const char*)(p.s->rowh + sel.y * 128) + (col >> 1) * 4;
                hs = ld_rlx(a); xs = ld_rlx(a + 262144); gw = ld_ll(p.s->rest + 768 + (col >> 2));
                if (__all_sync(0xffffffffu, hs != EMPTY && xs != EMPTY && gw.w == tag)) break;
            }
            const uint32_t gq = (col & 2) ? gw.y : gw.x;
            const float fx = (col & 1) ? bf_hi(xs) : bf_lo(xs), fh = (col & 1) ? bf_hi(hs) : bf_lo(hs), fg = (col & 1) ? bf_hi(gq) : bf_lo(gq);
            const float sg = rbf(sigmoidf(__uint_as_float(sel.z)));
            const uint4* src = p.s->yp + g * 512 + rank * 256 + pr * 4 + c;
            uint4 w[7];
            #pragma unroll
            for (int i = 0; i < 7; i++) w[i] = make_uint4(0, EMPTY, 0, EMPTY);
            if (ffn) mbar_wait(BAR(YGATE), 0);
            if (YDLY) { const uint32_t c0 = clk32(); while (clk32() - c0 < (ffn ? YDLY : YDLY + 1500)) {} }
            #pragma unroll 1
            for (int it = 0; it < POLL_MAX; it++) {
                bool ok = true;
                #pragma unroll
                for (int i = 0; i < 7; i++) ld_ll_if(w[i], src + i * 4096, !(tagged2(w[i].y, tag2) && tagged2(w[i].w, tag2)));
                #pragma unroll
                for (int i = 0; i < 7; i++) ok = ok && tagged2(w[i].y, tag2) && tagged2(w[i].w, tag2);
                if (__all_sync(0xffffffffu, ok)) break;
            }
            TS(29);
            float y0 = 0.f, y1 = 0.f, y2 = 0.f, y3 = 0.f;
            #pragma unroll
            for (int i = 0; i < 7; i++) { y0 += __uint_as_float(w[i].x); y1 += __uint_as_float(w[i].y); y2 += __uint_as_float(w[i].z); y3 += __uint_as_float(w[i].w); }
            const bool b4 = lane & 16, b3 = lane & 8;
            const float a0 = (b4 ? y2 : y0) + shfl_x(b4 ? y0 : y2, 16), a1 = (b4 ? y3 : y1) + shfl_x(b4 ? y1 : y3, 16);
            float y = (b3 ? a1 : a0) + shfl_x(b3 ? a0 : a1, 8);
            y += shfl_x(y, 4);
            const float upd = rbf(rbf(y) * sg);
            if (!(lane & 4)) p.out[(size_t)sel.x * 1024 + col] = __float2bfloat16(fx + rbf(fg * rbf(fh + upd)));
            if (b == 0 && lane == 0) p.s->done[0] = tag;
            TS(28);
        } else if (w4 == 2) {
            mbar_wait(BAR(OUTGATE), 0);
            const uint32_t cg = (lds32(sb + OFF_SEL + 32 + c * 4) >> 3) - rb * 16;
            uint32_t late = __reduce_or_sync(0xffffffffu, cg < 16 ? 1u << cg : 0u);
            mbar_wait(BAR(B_OUTW), 0);
            fence_async_smem();
            #pragma unroll 1
            for (uint32_t i = 0; i < 16; i++)
                if (!((late >> i) & 1))
                    asm volatile(EL "cp.async.bulk.tensor.3d.global.shared::cta.bulk_group [%0, {0, %2, %3}], [%1];\n}"
                        :: "l"(&tmO), "r"(sb + OFF_OUT + i * 2048u), "r"(rb * 128 + i * 8), "r"(hg * 2) : "memory");
            bulk_commit();
            mbar_wait(BAR(B_SEL), 0);
            const uint32_t row0 = lds32(sb + OFF_SEL) - rb * 128, row1 = lds32(sb + OFF_SEL + 16) - rb * 128;
            #pragma unroll 1
            for (; late; late &= late - 1) {
                const uint32_t i = __ffs(late) - 1;
                #pragma unroll 1
                for (uint32_t q = 0; q < 4; q++) {
                    const uint32_t r = q * 2 + (lane >> 4), ch = lane & 15;
                    const uint4 v = lds128(sb + OFF_OUT + i * 2048u + (ch >> 3) * 1024u + r * 128u + (((ch ^ r) & 7) << 4));
                    if (i * 8 + r != row0 && i * 8 + r != row1) stg128(p.out + (size_t)(rb * 128 + i * 8 + r) * 1024 + hg * 128 + ch * 8, v);
                }
            }
            bulk_wait();
            TS(35);
        }
    } else {
        const int w4 = warp & 3, wgi = warp >> 2;
        uint32_t m2[2]; float rinv[2];
        uint32_t tag2;
        {
            const int g = lane >> 2, c = lane & 3, xrow = b * 16 + warp * 2;
            if (b < NW0)
                asm volatile("prefetch.global.L2 [%0];" :: "l"(p.wmod + (size_t)((b & 3) * 256 + tid) * 6144 + (((b >> 2) & 1) ? 0 : 1024) + (b >> 3) * 64));
            const uint2 cv = ldg64(p.c + tid * 4);
            const uint32_t tag = ld_rlx(p.s->done) + 1;
            if (lane < 2) stg_fill(p.s->st1 + xrow + lane, 0);
            if (warp == 0 && lane < 16 && b < 32 * NC) stg_fill(p.s->mp + b * 16 + lane, EMPTY);
            if (tid < 64) { int s = tid >> 2; sts128(sb + OFF_ONES + tid * 16, make_uint4(((tid & 3) == ((s >> 1) & 3)) ? 0x3F80u : 0u, 0, 0, 0)); }
            cluster_arrive();
            reg_inc<CG1>();
            {
                const float c0 = bf_lo(cv.x), c1 = bf_hi(cv.x), c2 = bf_lo(cv.y), c3 = bf_hi(cv.y);
                sts64(sb + OFF_SILU + tid * 8, pack2(c0 * sigmoidf(c0), c1 * sigmoidf(c1)), pack2(c2 * sigmoidf(c2), c3 * sigmoidf(c3)));
            }
            tag2 = tag % 3u;
            bar_sync(0, 384);
            bar_arrive(3, 320);
            if (warp == 0) TS(47);
            #pragma unroll 1
            for (int part = 0; part < 2; part++)
            if (part == (b < NW0)) {
                mbar_wait(BAR(B_XS + (warp >> 1)), 0);
                if (warp == 7) TS(60);
                if (warp == 0) TS(54);
                float sd[2][4], q1[2][4], q2[2][4];
                #pragma unroll
                for (int e = 0; e < 4; e++) { sd[0][e] = sd[1][e] = q1[0][e] = q1[1][e] = q2[0][e] = q2[1][e] = 0.f; }
                #pragma unroll
                for (int i = 0; i < 4; i++) {
                    const uint4 u = lds128(sb + OFF_XS + warp * 4096u + (i * 32 + lane) * 16u), v = lds128(sb + OFF_XS + warp * 4096u + 2048u + (i * 32 + lane) * 16u);
                    mma16816(sd[0], u.x, v.x, u.y, v.y, ONE2, ONE2); mma16816(sd[1], u.z, v.z, u.w, v.w, ONE2, ONE2);
                    mma16816(q1[0], u.x, v.x, u.y, v.y, u.x, u.y); mma16816(q1[1], u.z, v.z, u.w, v.w, u.z, u.w);
                    mma16816(q2[0], u.x, v.x, u.y, v.y, v.x, v.y); mma16816(q2[1], u.z, v.z, u.w, v.w, v.z, v.w);
                }
                if (warp == 0) TS(30);
                const float d0 = __shfl_sync(0xffffffffu, (g & 1) ? q1[0][1] + q1[1][1] : q1[0][0] + q1[1][0], g * 4 + (g >> 1));
                const float d1 = __shfl_sync(0xffffffffu, (g & 1) ? q2[0][3] + q2[1][3] : q2[0][2] + q2[1][2], g * 4 + (g >> 1));
                float sk = (c & 1) ? sd[0][2] + sd[1][2] : sd[0][0] + sd[1][0], qk = (c & 1) ? d1 : d0;
                #pragma unroll
                for (int m = 4; m <= 16; m <<= 1) { sk += shfl_x(sk, m); qk += shfl_x(qk, m); }
                uint32_t mm; float ri;
                ln_final(sk, qk, mm, ri);
                if (lane < 2) st_ll(p.s->st1 + xrow + lane, mm, __float_as_uint(ri), 0, tag);
                if (warp == 0) TS(14);
                if (warp == 7) TS(61);
            } else if (b < 32 * NC) {
                float m[4][4];
                uint32_t sv[4];
                ldsm4(sv[0], sv[1], sv[2], sv[3], sb + OFF_SILU + ((b & 3) * 256 + warp * 32) * 2 + (lane >> 3) * 16);
                mbar_wait(BAR(B_WS + (warp >> 1)), 0);
                if (warp == 7) TS(55);
                #pragma unroll
                for (int tt = 0; tt < 4; tt++) {
                    m[tt][0] = m[tt][1] = m[tt][2] = m[tt][3] = 0.f;
                    #pragma unroll
                    for (int e = 0; e < 2; e++) {
                        uint32_t a0, a1, a2, a3;
                        ldsm4t(a0, a1, a2, a3, sb + OFF_WST + warp * 4096u + (e * 16 + (lane & 7) + ((lane >> 4) << 3)) * 128u + (((2 * tt + ((lane >> 3) & 1)) ^ (lane & 7)) << 4));
                        mma16816(m[tt], a0, a1, a2, a3, sv[2 * e], sv[2 * e + 1]);
                    }
                }
                if (warp == 0) TS(46);
                const uint32_t ra = sb + OFF_RED0 + warp * 256 + mod_pos(c, g);
                stsf(ra, (c & 2) ? ((c & 1) ? m[3][0] : m[2][0]) : ((c & 1) ? m[1][0] : m[0][0]));
                stsf(ra + 8, (c & 2) ? ((c & 1) ? m[3][2] : m[2][2]) : ((c & 1) ? m[1][2] : m[0][2]));
                if (warp != 7) bar_arrive(5, 256);
                else {
                    bar_sync(5, 256);
                    float v0 = 0.f, v1 = 0.f, v2 = 0.f, v3 = 0.f;
                    #pragma unroll
                    for (int w = 0; w < 4; w++) {
                        const uint4 u = lds128(sb + OFF_RED0 + w * 512 + lane * 16);
                        v0 += __uint_as_float(u.x); v1 += __uint_as_float(u.y); v2 += __uint_as_float(u.z); v3 += __uint_as_float(u.w);
                    }
                    v0 += shfl_x(v0, 16); v1 += shfl_x(v1, 16); v2 += shfl_x(v2, 16); v3 += shfl_x(v3, 16);
                    if (lane < 16) st_ll(p.s->mp + b * 16 + lane, __float_as_uint(v0), __float_as_uint(v1), __float_as_uint(v2), low_bits(v3, tag2));
                    TS(45);
                }
            }
            if (!LATEFREE) arrive_one(BAR(B_STFREE));
            cluster_wait();
            uint4 st[2];
            poll_words<2>(st, p.s->st1 + rb * 128 + warp * 16 + g, 8, tag);
            __syncwarp();
            m2[0] = st[0].x; rinv[0] = __uint_as_float(st[0].y); m2[1] = st[1].x; rinv[1] = __uint_as_float(st[1].y);
            if (LATEFREE) arrive_one(BAR(B_STFREE));
            if (warp == 0) TS(4);
        }
        const int lane = lane_id(), g = lane >> 2, c = lane & 3;
        const int srow = warp * 16 + (lane & 15);
        const uint32_t aoff = srow * 128u + ((((lane >> 4) ^ srow) & 7) << 4);
        uint32_t pt[16], qf[32];
        float pp[2][16];
        const uint32_t roff = srow * 128u + ((lane & 7) << 4);
        {
            float accKV[128], accQ[64];
            {
                uint32_t f[2][4], r[4];
                const Recip ri0 = split_recip(rinv[0]), ri1 = split_recip(rinv[1]);
                mbar_wait(BAR(B_F1), 0);
                if (warp == 0) TS(63);
                ldsm4(r[0], r[1], r[2], r[3], sb + OFF_RING + aoff);
                mbar_wait(BAR(B_MOD), 0);
                if (warp == 0) TS(15);
                uint4 md = lds128(sb + OFF_MODS + c * 16);
                int s = 0, sp = 2, par = 0;
                #pragma unroll 1
                for (int j = 0; j < 16; j++) {
                    const int sn = s == 2 ? 0 : s + 1;
                    par ^= s == 2;
                    const uint64_t db = mk_desc(sb + OFF_RING + s * 65536u + 16384u, 8192, 1024, 1);
                    #pragma unroll
                    for (int ks = 0; ks < 4; ks++) {
                        uint32_t (&ff)[4] = f[ks & 1];
                        ff[0] = ln_pair(r[0], m2[0], ri0, md.x, md.z); ff[1] = ln_pair(r[1], m2[1], ri1, md.x, md.z);
                        ff[2] = ln_pair(r[2], m2[0], ri0, md.y, md.w); ff[3] = ln_pair(r[3], m2[1], ri1, md.y, md.w);
                        const int kn = (ks + 1) & 3;
                        ldsm4(r[0], r[1], r[2], r[3], sb + OFF_RING + (ks == 3 ? sn : s) * 65536u + (aoff ^ (kn << 5)));
                        md = lds128(sb + OFF_MODS + ((ks == 3 ? j + 1 : j) * 4 + kn) * 64 + c * 16);
                        wg_fence();
                        wgmma_n256_rs<1>(accKV, ff[0], ff[1], ff[2], ff[3], desc_add(db, 16384 + ks * 2048), ks ? 1 : j);
                        wgmma_n128_rs<1>(accQ, ff[0], ff[1], ff[2], ff[3], desc_add(db, ks * 2048), ks ? 1 : j);
                        wg_commit();
                        if (ks == 1) mbar_wait(BAR(B_MOD + ((j + 1) & 15)), 0);
                        if (ks == 2) { WT0(); mbar_wait(BAR(j < 15 ? B_F1 + sn : B_WPHI), j < 15 ? par : 0);
                        }
                        wg_wait<1>();
                        if (ks == 0) arrive_if(BAR(B_E1 + sp), j);
                    }
                    sp = s; s = sn;
                }
            }
            mbar_wait(BAR(B_E1 + 2), 0);
            wg_wait<0>();
            acc_fence(accKV); acc_fence(accQ);
            arrive_one(BAR(B_E1));
            if (warp == 0) TS(16);
            uint32_t kf[32];
            #pragma unroll
            for (int h = 0; h < 4; h++) {
                if (h == VFIRST) {
                    #pragma unroll
                    for (int i = 0; i < 16; i++) kf[i] = pack2(accKV[2 * i], accKV[2 * i + 1]);
                    phi_issue(pp, kf, sb, 0);
                }
                #pragma unroll
                for (int q = 0; q < 2; q++) {
                    const int o = 64 + 16 * h + 8 * q;
                    stsm4(sb + OFF_V + h * 8192u + srow * 64u + (((2 * q + (lane >> 4)) ^ ((srow >> 1) & 3)) << 4),
                          pack2(accKV[o], accKV[o + 1]), pack2(accKV[o + 2], accKV[o + 3]), pack2(accKV[o + 4], accKV[o + 5]), pack2(accKV[o + 6], accKV[o + 7]));
                }
            }
            #pragma unroll
            for (int i = 16; i < 32; i++) kf[i] = pack2(accKV[2 * i], accKV[2 * i + 1]);
            phi_transpose(pp, pt, sb + OFF_PHI0 + aoff, sb + OFF_PHI0 + (roff ^ ((lane >> 4) << 6)));
            phi_issue(pp, kf + 16, sb, 1);
            #pragma unroll
            for (int i = 0; i < 32; i++) qf[i] = pack2(accQ[2 * i], accQ[2 * i + 1]);
            if (PREWAIT) { wg_wait<0>(); acc_fence(pp[0]); acc_fence(pp[1]); }
        }
        reg_dec<CREG>();
        if (warp == 0) TS(56);
        {
            float cp, cn;
            fm_extrema(pt, cp, cn);
            if (STAG && wgi) { const uint32_t c0 = clk32(); while (clk32() - c0 < STAG) {} }
            #pragma unroll 1
            for (int u = 0; u < 4; u++) {
                const uint32_t cur = sb + ((u & 1) ? OFF_PHI1 : OFF_PHI0);
                float e[64], s[4];
                uint32_t pn[16];
                #pragma unroll
                for (int k = 0; k < 16; k++) {
                    if (k == KW) phi_transpose(pp, pn, cur + aoff, cur + (roff ^ ((lane >> 4) << 6)));
                    const float dep = k >= DEP ? e[33 + 2 * (k >= DEP ? k - DEP : 0)] : 0.f, f0 = bf_lo_after(pt[k], dep), f1 = bf_hi_after(pt[k], dep);
                    e[2 * k] = ex2(fmaf(f0, LOG2E, cp)); e[2 * k + 1] = ex2(fmaf(f1, LOG2E, cp));
                    e[32 + 2 * k] = ex2(fmaf(f0, -LOG2E, cn)); e[33 + 2 * k] = ex2(fmaf(f1, -LOG2E, cn));
                    if (k == 0) { s[0] = e[0]; s[1] = e[1]; s[2] = e[32]; s[3] = e[33]; }
                    else { s[0] += e[2 * k]; s[1] += e[2 * k + 1]; s[2] += e[32 + 2 * k]; s[3] += e[33 + 2 * k]; }
                }
                fm_extrema(pn, cp, cn);
                #pragma unroll
                for (int i = 0; i < 16; i++) pt[i] = pn[i];
                const float sp = s[0] + s[1], sn = s[2] + s[3], r = rcp(sp * sn), rp = r * sn, rn = r * sp;
                #pragma unroll
                for (int i = 0; i < 8; i++) {
                    const float q = i < 4 ? rp : rn;
                    sts128((cur + (lane >> 4) * 16384u + roff) ^ (i << 4), make_uint4(pack2(e[8 * i] * q, e[8 * i + 1] * q), pack2(e[8 * i + 2] * q, e[8 * i + 3] * q),
                                                                                   pack2(e[8 * i + 4] * q, e[8 * i + 5] * q), pack2(e[8 * i + 6] * q, e[8 * i + 7] * q)));
                }
                __syncwarp();
                arrive_one(BAR(B_PHI + u));
                if (u == 0) phi_issue(pp, qf, sb, 0);
                else {
                    mbar_wait(BAR(B_KVD + (u != 1)), 0);
                    if (u == 1) phi_issue(pp, qf + 16, sb, 1);
                }
            }
            wg_wait<0>();
        }
        if (warp == 0) TS(57);
        uint32_t x2[16][2], wf[32][4];
        const uint32_t woff = ((lane >> 3) & 1) * 16384u + ((lane & 7) + ((lane >> 4) << 3)) * 128u + (((warp ^ lane) & 7) << 4);
        mbar_wait(BAR(B_S0), 0);
        #pragma unroll
        for (int q = 0; q < 8; q++) {
            ldsm4(x2[2 * q][0], x2[2 * q][1], x2[2 * q + 1][0], x2[2 * q + 1][1], sb + OFF_XT + (q >> 2) * 16384u + (aoff ^ ((q & 3) << 5)));
            ldsm4t(wf[q][0], wf[q][1], wf[q][2], wf[q][3], sb + OFF_GA + q * 2048u + woff);
        }
        __syncwarp();
        arrive_one(BAR(B_S0FREE));
        #pragma unroll 1
        for (int pp = 0; pp < 2; pp++) {
            float o0[20], o1[20];
            const uint64_t dk = mk_desc(sb + OFF_SP + pp * 8192u, OFF_Z - OFF_SP - pp * 8160u, 512, 2);
            const uint64_t dq = mk_desc(sb + (pp ? OFF_PHI1 : OFF_PHI0) + wgi * 8192u, 16, 1024, 1);
            mbar_wait(BAR(B_PHI + 2 + pp), 0);
            mbar_wait(BAR(B_KVF + pp), 0);
            fence_async_smem();
            wg_fence();
            #pragma unroll
            for (int ks = 0; ks < 4; ks++) {
                wgmma_n40_ss<0, 1>(o0, desc_add(dq, ks * 32), desc_add(dk, ks * 1024), ks);
                wgmma_n40_ss<0, 1>(o1, desc_add(dq, 16384 + ks * 32), desc_raw(dk, 256 + ks * 64 - (255 << 16)), ks);
            }
            wg_commit();
            wg_wait<0>();
            acc_fence(o0); acc_fence(o1);
            #pragma unroll
            for (int hh = 0; hh < 2; hh++) {
                const float (&o)[20] = hh ? o1 : o0;
                const Recip rd0 = split_recip(rcp(rbf(rbf(o[16]) + 1e-6f)));
                const Recip rd1 = split_recip(rcp(rbf(rbf(o[18]) + 1e-6f)));
                uint32_t op[8];
                #pragma unroll
                for (int j = 0; j < 4; j++) { op[2 * j] = hdiv2(pack2(o[4 * j], o[4 * j + 1]), rd0); op[2 * j + 1] = hdiv2(pack2(o[4 * j + 2], o[4 * j + 3]), rd1); }
                #pragma unroll
                for (int q = 0; q < 2; q++) stsm4(sb + OFF_OWN + pp * 16384u + (aoff ^ ((2 * hh + q) << 5)), op[4 * q], op[4 * q + 1], op[4 * q + 2], op[4 * q + 3]);
            }
            __syncwarp();
            arrive_one(BAR(B_OWN + pp));
            if (warp == 0) TS(20 + pp);
        }
        const uint32_t ooff = sb + OFF_OUT + (srow >> 3) * 1024u + aoff;
        {
            float acc[64];
            const uint32_t vchk = lane * 32u + g * 4u;
            mbar_wait(BAR(B_OWN + 1), 0);
            fence_async_smem();
            const uint64_t da0 = mk_desc(sb + OFF_DA + wgi * 8192u, 16, 1024, 1), db0 = mk_desc(sb + OFF_DB, 8192, 1024, 1);
            #pragma unroll 1
            for (int n = 0; n < 16; n++) {
                const uint32_t s = (SLOT_A >> (4 * n)) & 7, sB = (SLOT_B >> (4 * n)) & 7;
                WT0();
                mbar_wait(BAR(B_FB + sB), (PAR_B >> n) & 1);
                WTJ(16 + n);
                mbar_wait(BAR(n < 2 ? B_OWN + n : B_FA + s), (PAR_A >> n) & 1);
                WTJ(n);
                {
                    const uint32_t ra = sb + OFF_DA + s * 16384u + warp * 2048u;
                    if (__any_sync(0xffffffffu, max(lds32(ra + vchk), lds32(ra + vchk + 1024)) == EMPTY)) {
                        #pragma unroll 1
                        for (int i = 0; i < 4; i++) {
                            uint4 v;
                            #pragma unroll 1
                            for (int it = 0; it < POLL_MAX; it++) {
                                v = ld_ll(p.s->os + (rb * 16 + d_block(hg, n)) * 1024 + warp * 128 + i * 32 + lane);
                                if (umax4(v) != EMPTY) break;
                            }
                            sts128(ra + i * 512 + lane * 16, v);
                        }
                        fence_async_smem();
                        __syncwarp();
                    }
                }
                TR(32 + 16 * wgi + n);
                const uint64_t da = desc_add(da0, s * 16384u), db = desc_add(db0, sB * 16384u);
                wg_fence();
                #pragma unroll
                for (int ks = 0; ks < 4; ks++) wgmma_n128_ss<0, 1>(acc, desc_add(da, ks * 32), desc_add(db, ks * 2048), ks ? 1 : n);
                wg_commit();
                wg_wait<1>();
                if (MCB) arrive_both_if(BAR(B_ED - 1 + n), n); else arrive_if(BAR(B_ED - 1 + n), n);
            }
            mbar_wait(BAR(B_PAR), 0);
            uint32_t gar[16], bfr[16];
            #pragma unroll
            for (int j = 0; j < 16; j++) {
                gar[j] = lds32(sb + OFF_PAR + j * 64 + c * 16 + 12);
                const uint32_t bq = lds32(sb + OFF_BQ + j * 16 + c * 4);
                bfr[j] = (g & 1) ? bq : ONE2;
            }
            wg_wait<0>();
            acc_fence(acc);
            bar_arrive(6 + wgi, 256);
            if (warp == 0) TS(9);
            float sd[2][4], q1[2][4], q2[2][4];
            #pragma unroll
            for (int e = 0; e < 4; e++) { sd[0][e] = sd[1][e] = q1[0][e] = q1[1][e] = q2[0][e] = q2[1][e] = 0.f; }
            #pragma unroll
            for (int s = 0; s < 8; s++) {
                #pragma unroll
                for (int e = 0; e < 4; e++) { const int j = 2 * s + (e >> 1), h = e & 1; x2[j][h] = hadd2(x2[j][h], hmul2(gar[j], pack2(acc[4 * j + 2 * h], acc[4 * j + 2 * h + 1]))); }
                mma16816(sd[s & 1], x2[2 * s][0], x2[2 * s][1], x2[2 * s + 1][0], x2[2 * s + 1][1], bfr[2 * s], bfr[2 * s + 1]);
                #pragma unroll
                for (int e = 0; e < 2; e++) { mma1688(q1[e], x2[2 * s + e][0], x2[2 * s + e][1], x2[2 * s + e][0]); mma1688(q2[e], x2[2 * s + e][0], x2[2 * s + e][1], x2[2 * s + e][1]); }
            }
            if (c == (g >> 1)) {
                uint4* d = p.s->st2 + rb * 128 + warp * 16 + g;
                red_add4(d, sd[0][0] + sd[1][0], (g & 1) ? q1[0][1] + q1[1][1] : q1[0][0] + q1[1][0], sd[0][1] + sd[1][1], 1.0f);
                red_add4(d + 8, sd[0][2] + sd[1][2], (g & 1) ? q2[0][3] + q2[1][3] : q2[0][2] + q2[1][2], sd[0][3] + sd[1][3], 1.0f);
            }
            if (warp == 0) TS(22);
            bar_sync(7 - wgi, 256);
            #pragma unroll
            for (int q = 0; q < 8; q++) stsm4((ooff + (q >> 2) * 1024u) ^ ((q & 3) << 5), x2[2 * q][0], x2[2 * q][1], x2[2 * q + 1][0], x2[2 * q + 1][1]);
            __syncwarp();
            arrive_one(BAR(B_X2));
        }
        if (ffn) mbar_wait(BAR(B_GU), 0);
        if (warp == 0) TS(38);
        #pragma unroll
        for (int q = 8; q < 32; q++) ldsm4t(wf[q][0], wf[q][1], wf[q][2], wf[q][3], sb + (q < 16 ? OFF_GB : q < 24 ? OFF_UP0 : OFF_UP1) + (q & 7) * 2048u + woff);
        {
            mbar_wait(BAR(B_ST2), 0);
            const uint2 s0 = lds64(sb + OFF_ST2 + (warp * 16 + g) * 8), s1 = lds64(sb + OFF_ST2 + (warp * 16 + g + 8) * 8);
            const Recip r0 = split_recip(__uint_as_float(s0.y)), r1 = split_recip(__uint_as_float(s1.y));
            #pragma unroll 1
            for (int q0 = 0; q0 < 8; q0 += OUU) {
                uint32_t x[OUU][4]; uint4 pa[OUU][2];
                const uint32_t a = (ooff + (q0 >> 2) * 1024u) ^ ((q0 & 3) << 5);
                #pragma unroll
                for (int q = 0; q < OUU; q++) {
                    ldsm4(x[q][0], x[q][1], x[q][2], x[q][3], a ^ (q << 5));
                    pa[q][0] = lds128(sb + OFF_PAR + (q0 + q) * 128 + c * 16); pa[q][1] = lds128(sb + OFF_PAR + (q0 + q) * 128 + 64 + c * 16);
                }
                #pragma unroll
                for (int q = 0; q < OUU; q++) {
                    #pragma unroll
                    for (int e = 0; e < 4; e++) { const uint4 v = pa[q][e >> 1]; x[q][e] = hadd2(x[q][e], hmul2(v.z, ln_pair(x[q][e], (e & 1) ? s1.x : s0.x, (e & 1) ? r1 : r0, v.x, v.y))); }
                    stsm4(a ^ (q << 5), x[q][0], x[q][1], x[q][2], x[q][3]);
                }
            }
            __syncwarp();
            arrive_one(BAR(B_OUTW));
            if (warp == 0) TS(32);
        }
        if (ffn) {
            float acc[4][4];
            uint32_t df[4][4][4];
            {
                #pragma unroll
                for (int i = 0; i < 4; i++) { acc[i][0] = acc[i][1] = acc[i][2] = acc[i][3] = 0.f; }
                const uint32_t da = sb + (wgi ? OFF_DN1 : OFF_DN0) + w4 * 8192u + ((lane & 7) + ((lane >> 4) << 3)) * 128u;
                mbar_wait(BAR(B_WD), 0);
                #pragma unroll
                for (int q = 0; q < DNE; q++)
                    ldsm4t(df[q >> 2][q & 3][0], df[q >> 2][q & 3][1], df[q >> 2][q & 3][2], df[q >> 2][q & 3][3], da + (q & 3) * 2048u + (((2 * (q >> 2) + ((lane >> 3) & 1)) ^ (lane & 7)) << 4));
                mbar_wait(BAR(B_ROWS), 0);
                #pragma unroll
                for (int q = 0; q < 8; q++) {
                    uint32_t b0, b1, b2, b3;
                    ldsm4(b0, b1, b2, b3, sb + OFF_ROWS + (lane & 7) * 528u + (lane >> 3) * 16u + q * 64u);
                    #pragma unroll
                    for (int hf = 0; hf < 2; hf++) {
                        const int k = 16 * hf + 2 * q;
                        mma16816(acc[2 * hf], wf[k][0], wf[k][1], wf[k][2], wf[k][3], b0, b1);
                        mma16816(acc[2 * hf + 1], wf[k + 1][0], wf[k + 1][1], wf[k + 1][2], wf[k + 1][3], b2, b3);
                    }
                }
                const float gs = (acc[0][0] + acc[1][0]) + (acc[2][1] + acc[3][1]), us = (acc[0][2] + acc[1][2]) + (acc[2][3] + acc[3][3]);
                st_partner64(sb + OFF_PX + warp * 256 + lane * 8, BAR(B_PX), rank ^ 1, gs, us);
                if (warp == 0) TS(34);
                #pragma unroll
                for (int q = DNE; q < 16; q++)
                    ldsm4t(df[q >> 2][q & 3][0], df[q >> 2][q & 3][1], df[q >> 2][q & 3][2], df[q >> 2][q & 3][3], da + (q & 3) * 2048u + (((2 * (q >> 2) + ((lane >> 3) & 1)) ^ (lane & 7)) << 4));
                mbar_wait(BAR(B_SEL), 0);
                const uint32_t tok = lds32(sb + OFF_SEL + 48 + c * 4);
                mbar_wait(BAR(B_PX), 0);
                const uint2 q = lds64(sb + OFF_PX + warp * 256 + lane * 8);
                float gt = rbf(gs + __uint_as_float(q.x));
                gt = rbf(gt * sigmoidf(gt));
                if (tok < 2) sts16(sb + OFF_HID + tok * 144 + (warp * 8 + g) * 2, pack2(gt * rbf(us + __uint_as_float(q.y)), 0.f));
            }
            if (warp == 0) TS(26);
            bar_sync(1, 256);
            uint32_t bh[8];
            ldsm4(bh[0], bh[1], bh[2], bh[3], sb + OFF_HID + (lane & 1) * 144u + (lane >> 3) * 16u);
            ldsm4(bh[4], bh[5], bh[6], bh[7], sb + OFF_HID + (lane & 1) * 144u + (lane >> 3) * 16u + 64u);
            float y[4][4];
            #pragma unroll
            for (int tt = 0; tt < 4; tt++) { y[tt][0] = y[tt][1] = y[tt][2] = y[tt][3] = 0.f; }
            #pragma unroll
            for (int ks = 0; ks < 4; ks++)
                #pragma unroll
                for (int tt = 0; tt < 4; tt++) mma16816(y[tt], df[tt][ks][0], df[tt][ks][1], df[tt][ks][2], df[tt][ks][3], bh[2 * ks], bh[2 * ks + 1]);
            float e[4];
            #pragma unroll
            for (int i = 0; i < 4; i++) e[i] = (c & 2) ? ((c & 1) ? y[3][i] : y[2][i]) : ((c & 1) ? y[1][i] : y[0][i]);
            char* d = (char*)(p.s->yp + pr * 512 + rank * 128 + (warp * 4 + c) * 4) + g * 8;
            st_ll8(d, __float_as_uint(e[0]), low_bits(e[2], tag2));
            st_ll8(d + 4096, __float_as_uint(e[1]), low_bits(e[3], tag2));
            arrive_one(BAR(B_YP));
            if (warp == 0) TS(27);
        }
    }
}

typedef CUresult (*EncodeFn)(CUtensorMap*, CUtensorMapDataType, cuuint32_t, void*, const cuuint64_t*, const cuuint64_t*, const cuuint32_t*,
                             const cuuint32_t*, CUtensorMapInterleave, CUtensorMapSwizzle, CUtensorMapL2promotion, CUtensorMapFloatOOBfill);

CUtensorMap make_map(EncodeFn enc, const void* ptr, uint64_t cols, uint64_t rows, uint32_t bc, uint32_t br, CUtensorMapSwizzle swz, CUtensorMapL2promotion promo) {
    CUtensorMap m;
    cuuint64_t dims[2] = {cols, rows}, strides[1] = {cols * 2};
    cuuint32_t box[2] = {bc, br}, es[2] = {1, 1};
    enc(&m, CU_TENSOR_MAP_DATA_TYPE_BFLOAT16, 2, const_cast<void*>(ptr), dims, strides, box, es, CU_TENSOR_MAP_INTERLEAVE_NONE, swz, promo,
        CU_TENSOR_MAP_FLOAT_OOB_FILL_NONE);
    return m;
}
CUtensorMap make_block_map(EncodeFn enc, const void* ptr, uint32_t sections, uint64_t rows, uint32_t br, CUtensorMapL2promotion promo) {
    CUtensorMap m;
    cuuint64_t dims[4] = {64, rows, 16, sections}, strides[3] = {sections * 2048ull, 128, 2048};
    cuuint32_t box[4] = {64, br, 2, sections}, es[4] = {1, 1, 1, 1};
    enc(&m, CU_TENSOR_MAP_DATA_TYPE_BFLOAT16, sections > 1 ? 4 : 3, const_cast<void*>(ptr), dims, strides, box, es, CU_TENSOR_MAP_INTERLEAVE_NONE,
        CU_TENSOR_MAP_SWIZZLE_128B, promo, CU_TENSOR_MAP_FLOAT_OOB_FILL_NONE);
    return m;
}

}

extern "C" void kernel_launch(void* const* d_in, const int* in_sizes, int n_in, void* d_out, int out_size) {
    (void)in_sizes; (void)n_in; (void)out_size;
    void* fn = nullptr; cudaDriverEntryPointQueryResult qr;
    cudaGetDriverEntryPoint("cuTensorMapEncodeTiled", &fn, cudaEnableDefault, &qr);
    EncodeFn enc = (EncodeFn)fn;
    void* hs = nullptr;
    cudaGetSymbolAddress(&hs, g_scratch);
    const CUtensorMapL2promotion P256 = CU_TENSOR_MAP_L2_PROMOTION_L2_256B, P128 = CU_TENSOR_MAP_L2_PROMOTION_L2_128B;
    CUtensorMap tmW = make_block_map(enc, d_in[1], 3, 1024, 64, P256);
    CUtensorMap tmWo = make_map(enc, d_in[3], 1024, 1024, 64, 64, CU_TENSOR_MAP_SWIZZLE_128B, P256);
    CUtensorMap tmPhi = make_map(enc, d_in[2], 32, 1024, 32, 128, CU_TENSOR_MAP_SWIZZLE_64B, P128);
    CUtensorMap tmG = make_map(enc, d_in[6], 3584, 1024, 64, 128, CU_TENSOR_MAP_SWIZZLE_128B, P128);
    CUtensorMap tmU = make_map(enc, d_in[7], 3584, 1024, 64, 128, CU_TENSOR_MAP_SWIZZLE_128B, P128);
    CUtensorMap tmD = make_block_map(enc, d_in[8], 1, 3584, 64, P128);
    CUtensorMap tmX = make_map(enc, d_in[0], 1024, 2048, 64, 128, CU_TENSOR_MAP_SWIZZLE_128B, P128);
    CUtensorMap tmO = make_block_map(enc, d_out, 1, 2048, 8, P128);
    CUtensorMap tmM = make_map(enc, d_in[10], 6144, 1024, 64, 64, CU_TENSOR_MAP_SWIZZLE_128B, P128);
    CUtensorMap tmR = make_map(enc, d_in[10], 6144, 1024, 32, 64, CU_TENSOR_MAP_SWIZZLE_NONE, P128);
    CUtensorMap tmG8 = make_map(enc, d_in[6], 3584, 1024, 8, 64, CU_TENSOR_MAP_SWIZZLE_NONE, P128);
    CUtensorMap tmU8 = make_map(enc, d_in[7], 3584, 1024, 8, 64, CU_TENSOR_MAP_SWIZZLE_NONE, P128);
    CUtensorMap tmD8 = make_map(enc, d_in[8], 1024, 3584, 8, 64, CU_TENSOR_MAP_SWIZZLE_NONE, P128);
    Ptrs p;
    p.x = (const bf16*)d_in[0]; p.c = (const bf16*)d_in[9]; p.wmod = (const bf16*)d_in[10]; p.wr = (const bf16*)d_in[5];
    p.wg = (const bf16*)d_in[6]; p.wu = (const bf16*)d_in[7]; p.wd = (const bf16*)d_in[8]; p.out = (bf16*)d_out; p.s = (Scratch*)hs;
    p.wqkv = (const bf16*)d_in[1]; p.wo = (const bf16*)d_in[3];
    cudaFuncSetAttribute(fused_kernel, cudaFuncAttributeMaxDynamicSharedMemorySize, SMEM_BYTES);
    fused_kernel<<<128, NTHREADS, SMEM_BYTES, cudaStreamPerThread>>>(p, tmW, tmWo, tmPhi, tmG, tmU, tmD, tmX, tmO, tmM, tmR, tmG8, tmU8, tmD8);
}
```

```cpp
#include <cuda_runtime.h>
#include <cuda.h>
#include <cuda_bf16.h>
#include <stdint.h>

namespace {

typedef __nv_bfloat16 bf16;

constexpr int NTHREADS = 384;
constexpr int POLL_MAX = 400000;
constexpr uint32_t EMPTY = 0xffffffffu;

constexpr uint32_t OFF_RING = 0;
constexpr uint32_t OFF_XS   = 131072;
constexpr uint32_t OFF_WST  = 163840;
constexpr uint32_t OFF_XT   = 0;
constexpr uint32_t OFF_GA   = 32768;
constexpr uint32_t OFF_PHI0 = 163840, OFF_PHI1 = 98304;
constexpr uint32_t OFF_V    = 131072;
constexpr uint32_t OFF_KVS  = 131072;
constexpr uint32_t OFF_DB   = 0;
constexpr uint32_t OFF_DA   = 98304;
constexpr uint64_t SLOT_A   = 0x5432105432105432ull, SLOT_B = 0x1054321054321054ull;
constexpr uint32_t PAR_A    = 0x3f00, PAR_B = 0x0fc0;
constexpr uint32_t OFF_OWN  = OFF_DA + 32768;
constexpr uint32_t OFF_OUT  = OFF_DA + 65536;
constexpr uint32_t OFF_UP0  = OFF_DA, OFF_UP1 = OFF_DB + 32768, OFF_DN0 = OFF_DA + 32768, OFF_DN1 = OFF_DB + 65536;
constexpr uint32_t OFF_WPHI = 196608;
constexpr uint32_t OFF_SP   = 204800;
constexpr uint32_t OFF_Z    = 221184;
constexpr uint32_t OFF_ONES = 225280;
constexpr uint32_t OFF_MODS = 226304;
constexpr uint32_t OFF_GB   = 196608;
constexpr uint32_t OFF_BQ   = 229376;
constexpr uint32_t OFF_ATOT = OFF_BQ + 256;
constexpr uint32_t OFF_BAR  = 230400;
constexpr uint32_t OFF_SEEN = OFF_BAR + 632;
constexpr uint32_t OFF_PAR  = OFF_BAR + 640;
constexpr uint32_t SMEM_BYTES = 232448;
constexpr uint32_t OFF_SILU = OFF_Z;
constexpr uint32_t OFF_RED0 = OFF_Z + 2048;
constexpr uint32_t OFF_ST2  = OFF_DB;
constexpr uint32_t OFF_SEL  = OFF_ST2 + 1024;
constexpr uint32_t OFF_ROWS = OFF_ST2 + 2048;
constexpr uint32_t OFF_PX   = OFF_ROWS + 4608;
constexpr uint32_t OFF_HID  = OFF_PX + 2048;

enum {
    B_F1 = 0, B_E1 = 3, B_STFREE = 6, B_WPHI = 7, B_FA = 8, B_FB = 14, B_RF = 20, B_KVD = 24, B_PAR = 26, B_S0 = 27, B_GU = 28, B_WD = 29,
    B_X2 = 30, B_ST2 = 31, B_CAND = 32,
    B_MP = 33, B_MOD = 34, B_PX = 50, B_S0FREE = 51, B_PHI = 52, B_OUTW = 56, B_PUB = 57, B_KVF = 59, B_OWN = 61, B_REL = 63, B_ROWS = 64, B_SEL = 65, B_YP = 66, B_RED = 67,
    B_XS = 68,
    B_WS = 72, B_COUNT = 76,
    B_ED = B_MOD, B_KVS = B_XS, B_OGO = B_XS + 2, B_PF = B_XS + 3
};

struct Scratch {
    uint4 os[256 * 1024];
    uint4 kvp[32 * 256 * 32];
    uint4 kvf[32 * 288];
    uint4 st1[2048];
    uint4 mp[128 * 16];
    uint4 rest[1024];
    uint4 flo[256 * 2];
    uint4 st2[2048];
    uint4 cand[64 * 2];
    uint4 rowh[128 * 128];
    uint4 rowx[128 * 128];
    uint4 rsc[64 * 8 * 2];
    uint4 yp[56 * 512];
    unsigned done[4];
};
__device__ __align__(1024) Scratch g_scratch;
#define TS(i) do {} while (0)
#undef GS
#define GS(i)
#define TR(i)
#define TRL(i)
#define WT0()
#define WTJ(j)

__device__ __forceinline__ uint32_t smem_u32(const void* p) { return (uint32_t)__cvta_generic_to_shared(p); }
__device__ __forceinline__ int lane_id() { int l; asm volatile("mov.u32 %0, %%laneid;" : "=r"(l)); return l; }
__device__ __forceinline__ uint32_t clk32() { uint32_t c; asm volatile("mov.u32 %0, %%clock;" : "=r"(c) :: "memory"); return c; }
__device__ __forceinline__ void arrive_one(uint32_t bar) {
    asm volatile("{\n.reg .pred p;\nelect.sync _|p, 0xffffffff;\n@p mbarrier.arrive.shared::cta.b64 _, [%0];\n}" :: "r"(bar) : "memory");
}
__device__ __forceinline__ void arrive_many(uint32_t bar, uint32_t n) {
    asm volatile("{\n.reg .pred p;\nelect.sync _|p, 0xffffffff;\n@p mbarrier.arrive.shared::cta.b64 _, [%0], %1;\n}" :: "r"(bar), "r"(n) : "memory");
}
__device__ __forceinline__ void arrive_if(uint32_t bar, uint32_t on) {
    asm volatile("{\n.reg .pred q, p;\nelect.sync _|q, 0xffffffff;\nsetp.ne.and.u32 p, %1, 0, q;\n@p mbarrier.arrive.shared::cta.b64 _, [%0];\n}" :: "r"(bar), "r"(on) : "memory");
}
__device__ __forceinline__ void arrive_both_if(uint32_t bar, uint32_t on) {
    asm volatile("{\n.reg .pred q, p;\n.reg .b32 r0, r1;\nelect.sync _|q, 0xffffffff;\nsetp.ne.and.u32 p, %1, 0, q;\n"
        "mapa.shared::cluster.u32 r0, %0, 0;\nmapa.shared::cluster.u32 r1, %0, 1;\n"
        "@p mbarrier.arrive.shared::cluster.b64 _, [r0];\n@p mbarrier.arrive.shared::cluster.b64 _, [r1];\n}" :: "r"(bar), "r"(on) : "memory");
}
__device__ __forceinline__ void st_partner64(uint32_t a, uint32_t bar, uint32_t cta, float x, float y) {
    asm volatile("{\n.reg .b32 ra, rb;\nmapa.shared::cluster.u32 ra, %0, %2;\nmapa.shared::cluster.u32 rb, %1, %2;\n"
        "st.async.weak.shared::cluster.mbarrier::complete_tx::bytes.v2.f32 [ra], {%3, %4}, [rb];\n}" :: "r"(a), "r"(bar), "r"(cta), "f"(x), "f"(y) : "memory");
}
__device__ __forceinline__ void mbar_wait(uint32_t bar, uint32_t parity) {
#define WAITV 1
    asm volatile("{\n.reg .pred P1;\n.reg .u32 cnt;\nmbarrier.try_wait.parity.shared::cta.b64 P1, [%0], %1;\n@P1 bra DONE;\nmov.u32 cnt, 0;\nLAB_WAIT:\n"
        "mbarrier.try_wait.parity.shared::cta.b64 P1, [%0], %1;\n@P1 bra DONE;\n"
        "add.u32 cnt, cnt, 1;\nsetp.lt.u32 P1, cnt, 1000000;\n@P1 bra LAB_WAIT;\ntrap;\nDONE:\n}" :: "r"(bar), "r"(parity) : "memory");
}
__device__ __forceinline__ uint64_t policy_evict_first() { uint64_t p; asm("createpolicy.fractional.L2::evict_first.b64 %0, 1.0;" : "=l"(p)); return p; }
#define EF_W 1
#define EF_WO 1
#define EF_F 1
#define EF_M 1
__device__ __forceinline__ void bulk_commit() { asm volatile("cp.async.bulk.commit_group;" ::: "memory"); }
__device__ __forceinline__ void bulk_wait() { asm volatile("cp.async.bulk.wait_group 0;" ::: "memory"); }
__device__ __forceinline__ void tmap_prefetch(const CUtensorMap* tm) { asm volatile("prefetch.tensormap [%0];" :: "l"(tm) : "memory"); }
#define EL "{\n.reg .pred e;\nelect.sync _|e, 0xffffffff;\n@e "
__device__ __forceinline__ void expect_tx_e(uint32_t bar, uint32_t bytes) { asm volatile(EL "mbarrier.arrive.expect_tx.shared::cta.b64 _, [%0], %1;\n}" :: "r"(bar), "r"(bytes) : "memory"); }
__device__ __forceinline__ void tma2_e(uint32_t dst, const CUtensorMap* tm, int c0, int c1, uint32_t bar) {
    asm volatile(EL "cp.async.bulk.tensor.2d.shared::cluster.global.mbarrier::complete_tx::bytes [%0], [%1, {%3, %4}], [%2];\n}"
        :: "r"(dst), "l"(tm), "r"(bar), "r"(c0), "r"(c1) : "memory");
}
__device__ __forceinline__ void tma2_ef_e(uint32_t dst, const CUtensorMap* tm, int c0, int c1, uint32_t bar) {
    asm volatile(EL "cp.async.bulk.tensor.2d.shared::cluster.global.mbarrier::complete_tx::bytes.L2::cache_hint [%0], [%1, {%3, %4}], [%2], %5;\n}"
        :: "r"(dst), "l"(tm), "r"(bar), "r"(c0), "r"(c1), "l"(policy_evict_first()) : "memory");
}
__device__ __forceinline__ void tma2_mc_e(uint32_t dst, const CUtensorMap* tm, int c0, int c1, uint32_t bar) {
    if (!EF_WO) asm volatile(EL "cp.async.bulk.tensor.2d.shared::cluster.global.mbarrier::complete_tx::bytes.multicast::cluster [%0], [%1, {%3, %4}], [%2], %5;\n}"
        :: "r"(dst), "l"(tm), "r"(bar), "r"(c0), "r"(c1), "h"((uint16_t)3) : "memory");
    else
    asm volatile(EL "cp.async.bulk.tensor.2d.shared::cluster.global.mbarrier::complete_tx::bytes.multicast::cluster.L2::cache_hint [%0], [%1, {%3, %4}], [%2], %5, %6;\n}"
        :: "r"(dst), "l"(tm), "r"(bar), "r"(c0), "r"(c1), "h"((uint16_t)3), "l"(policy_evict_first()) : "memory");
}
__device__ __forceinline__ void tma3_ef_e(uint32_t dst, const CUtensorMap* tm, int row, int blk, uint32_t bar) {
    if (!EF_F) asm volatile(EL "cp.async.bulk.tensor.3d.shared::cluster.global.mbarrier::complete_tx::bytes [%0], [%1, {0, %3, %4}], [%2];\n}"
        :: "r"(dst), "l"(tm), "r"(bar), "r"(row), "r"(blk) : "memory");
    else
    asm volatile(EL "cp.async.bulk.tensor.3d.shared::cluster.global.mbarrier::complete_tx::bytes.L2::cache_hint [%0], [%1, {0, %3, %4}], [%2], %5;\n}"
        :: "r"(dst), "l"(tm), "r"(bar), "r"(row), "r"(blk), "l"(policy_evict_first()) : "memory");
}
__device__ __forceinline__ void tma4_ef_e(uint32_t dst, const CUtensorMap* tm, int row, int blk, uint32_t bar) {
    if (!EF_W) asm volatile(EL "cp.async.bulk.tensor.4d.shared::cluster.global.mbarrier::complete_tx::bytes [%0], [%1, {0, %3, %4, 0}], [%2];\n}"
        :: "r"(dst), "l"(tm), "r"(bar), "r"(row), "r"(blk) : "memory");
    else
    asm volatile(EL "cp.async.bulk.tensor.4d.shared::cluster.global.mbarrier::complete_tx::bytes.L2::cache_hint [%0], [%1, {0, %3, %4, 0}], [%2], %5;\n}"
        :: "r"(dst), "l"(tm), "r"(bar), "r"(row), "r"(blk), "l"(policy_evict_first()) : "memory");
}
__device__ __forceinline__ void bulk_load_e(uint32_t dst, const void* src, uint32_t bytes, uint32_t bar) {
    asm volatile(EL "cp.async.bulk.shared::cluster.global.mbarrier::complete_tx::bytes [%0], [%1], %2, [%3];\n}" :: "r"(dst), "l"(src), "r"(bytes), "r"(bar) : "memory");
}
__device__ __forceinline__ void bulk_store_e(void* dst, uint32_t src, uint32_t bytes) {
    asm volatile(EL "cp.async.bulk.global.shared::cta.bulk_group [%0], [%1], %2;\n}" :: "l"(dst), "r"(src), "r"(bytes) : "memory");
}
__device__ __forceinline__ void st_flag_e(void* p, unsigned v) { asm volatile(EL "st.relaxed.gpu.global.u32 [%0], %1;\n}" :: "l"(p), "r"(v) : "memory"); }
__device__ __forceinline__ void mbar_init(uint32_t bar, uint32_t cnt) { asm volatile("mbarrier.init.shared::cta.b64 [%0], %1;" :: "r"(bar), "r"(cnt) : "memory"); }
__device__ __forceinline__ bool elect_one() {
    uint32_t p;
    asm volatile("{\n.reg .pred P;\nelect.sync _|P, 0xffffffff;\nselp.u32 %0, 1, 0, P;\n}" : "=r"(p));
    return p;
}
__device__ __forceinline__ void wg_fence() { asm volatile("wgmma.fence.sync.aligned;" ::: "memory"); }
__device__ __forceinline__ void wg_commit() { asm volatile("wgmma.commit_group.sync.aligned;" ::: "memory"); }
template<int N> __device__ __forceinline__ void wg_wait() { asm volatile("wgmma.wait_group.sync.aligned %0;" :: "n"(N) : "memory"); }
template<int N> __device__ __forceinline__ void acc_fence(float (&d)[N]) {
    #pragma unroll
    for (int i = 0; i < N; i++) asm volatile("" : "+f"(d[i]) :: "memory");
}
__device__ __forceinline__ uint64_t mk_desc(uint32_t addr, uint32_t lbo, uint32_t sbo, uint32_t swz) {
    uint32_t lo = ((addr & 0x3FFFF) >> 4) | (((lbo & 0x3FFFF) >> 4) << 16);
    uint32_t hi = (sbo >> 4) | (swz << 30);
    return ((uint64_t)hi << 32) | lo;
}
__device__ __forceinline__ uint64_t desc_add(uint64_t d, uint32_t bytes) { return (d & 0xffffffff00000000ull) | (uint32_t)((uint32_t)d + (bytes >> 4)); }
__device__ __forceinline__ uint64_t desc_raw(uint64_t d, uint32_t inc) { return (d & 0xffffffff00000000ull) | (uint32_t)((uint32_t)d + inc); }
__device__ __forceinline__ void fence_async_smem() { asm volatile("fence.proxy.async.shared::cta;" ::: "memory"); }
__device__ __forceinline__ void bar_sync(int id, int n) { asm volatile("bar.sync %0, %1;" :: "r"(id), "r"(n) : "memory"); }
__device__ __forceinline__ void bar_arrive(int id, int n) { asm volatile("bar.arrive %0, %1;" :: "r"(id), "r"(n) : "memory"); }
template<int R> __device__ __forceinline__ void reg_inc() { asm volatile("setmaxnreg.inc.sync.aligned.u32 %0;" :: "n"(R)); }
template<int R> __device__ __forceinline__ void reg_dec() { asm volatile("setmaxnreg.dec.sync.aligned.u32 %0;" :: "n"(R)); }
__device__ __forceinline__ void cluster_arrive() { asm volatile("barrier.cluster.arrive.relaxed.aligned;" ::: "memory"); }
__device__ __forceinline__ void cluster_wait() { asm volatile("barrier.cluster.wait.acquire.aligned;" ::: "memory"); }

__device__ __forceinline__ void stsm4(uint32_t addr, uint32_t r0, uint32_t r1, uint32_t r2, uint32_t r3) {
    asm volatile("stmatrix.sync.aligned.m8n8.x4.shared.b16 [%0], {%1,%2,%3,%4};" :: "r"(addr), "r"(r0), "r"(r1), "r"(r2), "r"(r3) : "memory");
}
__device__ __forceinline__ void ldsm4(uint32_t& r0, uint32_t& r1, uint32_t& r2, uint32_t& r3, uint32_t addr) {
    asm volatile("ldmatrix.sync.aligned.m8n8.x4.shared.b16 {%0,%1,%2,%3}, [%4];" : "=r"(r0), "=r"(r1), "=r"(r2), "=r"(r3) : "r"(addr) : "memory");
}
__device__ __forceinline__ void ldsm4t(uint32_t& r0, uint32_t& r1, uint32_t& r2, uint32_t& r3, uint32_t addr) {
    asm volatile("ldmatrix.sync.aligned.m8n8.x4.trans.shared.b16 {%0,%1,%2,%3}, [%4];" : "=r"(r0), "=r"(r1), "=r"(r2), "=r"(r3) : "r"(addr) : "memory");
}
__device__ __forceinline__ void mma16816(float (&d)[4], uint32_t a0, uint32_t a1, uint32_t a2, uint32_t a3, uint32_t b0, uint32_t b1) {
    asm("mma.sync.aligned.m16n8k16.row.col.f32.bf16.bf16.f32 {%0,%1,%2,%3}, {%4,%5,%6,%7}, {%8,%9}, {%0,%1,%2,%3};"
        : "+f"(d[0]), "+f"(d[1]), "+f"(d[2]), "+f"(d[3]) : "r"(a0), "r"(a1), "r"(a2), "r"(a3), "r"(b0), "r"(b1));
}
__device__ __forceinline__ void mma1688(float (&d)[4], uint32_t a0, uint32_t a1, uint32_t b0) {
    asm("mma.sync.aligned.m16n8k8.row.col.f32.bf16.bf16.f32 {%0,%1,%2,%3}, {%4,%5}, {%6}, {%0,%1,%2,%3};"
        : "+f"(d[0]), "+f"(d[1]), "+f"(d[2]), "+f"(d[3]) : "r"(a0), "r"(a1), "r"(b0));
}
__device__ __forceinline__ uint4 lds128(uint32_t a) { uint4 v; asm volatile("ld.shared.v4.b32 {%0,%1,%2,%3}, [%4];" : "=r"(v.x), "=r"(v.y), "=r"(v.z), "=r"(v.w) : "r"(a) : "memory"); return v; }
__device__ __forceinline__ uint2 lds64(uint32_t a) { uint2 v; asm volatile("ld.shared.v2.b32 {%0,%1}, [%2];" : "=r"(v.x), "=r"(v.y) : "r"(a) : "memory"); return v; }
__device__ __forceinline__ uint32_t lds32(uint32_t a) { uint32_t v; asm volatile("ld.shared.b32 %0, [%1];" : "=r"(v) : "r"(a) : "memory"); return v; }
__device__ __forceinline__ float ldsf(uint32_t a) { float v; asm volatile("ld.shared.f32 %0, [%1];" : "=f"(v) : "r"(a) : "memory"); return v; }
__device__ __forceinline__ uint32_t lds16(uint32_t a) { uint16_t v; asm volatile("ld.shared.b16 %0, [%1];" : "=h"(v) : "r"(a) : "memory"); return v; }
__device__ __forceinline__ void sts128(uint32_t a, uint4 v) { asm volatile("st.shared.v4.b32 [%0], {%1,%2,%3,%4};" :: "r"(a), "r"(v.x), "r"(v.y), "r"(v.z), "r"(v.w) : "memory"); }
__device__ __forceinline__ void sts64(uint32_t a, uint32_t x, uint32_t y) { asm volatile("st.shared.v2.b32 [%0], {%1,%2};" :: "r"(a), "r"(x), "r"(y) : "memory"); }
__device__ __forceinline__ void sts32(uint32_t a, uint32_t x) { asm volatile("st.shared.b32 [%0], %1;" :: "r"(a), "r"(x) : "memory"); }
__device__ __forceinline__ void stsf(uint32_t a, float x) { asm volatile("st.shared.f32 [%0], %1;" :: "r"(a), "f"(x) : "memory"); }
__device__ __forceinline__ void sts16(uint32_t a, uint32_t x) { asm volatile("st.shared.b16 [%0], %1;" :: "r"(a), "h"((uint16_t)x) : "memory"); }

__device__ __forceinline__ uint4 ldg128(const void* p) { uint4 v; asm volatile("ld.global.nc.v4.b32 {%0,%1,%2,%3}, [%4];" : "=r"(v.x), "=r"(v.y), "=r"(v.z), "=r"(v.w) : "l"(p)); return v; }
__device__ __forceinline__ uint2 ldg64(const void* p) { uint2 v; asm volatile("ld.global.nc.v2.b32 {%0,%1}, [%2];" : "=r"(v.x), "=r"(v.y) : "l"(p)); return v; }
__device__ __forceinline__ void stg128(void* p, uint4 v) { asm volatile("st.global.v4.b32 [%0], {%1,%2,%3,%4};" :: "l"(p), "r"(v.x), "r"(v.y), "r"(v.z), "r"(v.w) : "memory"); }
__device__ __forceinline__ void stg_fill(void* p, uint32_t v) { asm volatile("st.global.v4.b32 [%0], {%1,%1,%1,%1};" :: "l"(p), "r"(v) : "memory"); }
__device__ __forceinline__ void st_ll(void* p, uint32_t x, uint32_t y, uint32_t z, uint32_t w) {
    asm volatile("{\n.reg .b128 t;\n.reg .b64 a, b;\nmov.b64 a, {%1, %2};\nmov.b64 b, {%3, %4};\nmov.b128 t, {a, b};\nst.relaxed.gpu.global.b128 [%0], t;\n}"
        :: "l"(p), "r"(x), "r"(y), "r"(z), "r"(w) : "memory");
}
__device__ __forceinline__ uint4 ld_ll(const void* p) {
    uint4 v;
    asm volatile("{\n.reg .b128 t;\n.reg .b64 a, b;\nld.relaxed.gpu.global.b128 t, [%4];\nmov.b128 {a, b}, t;\nmov.b64 {%0, %1}, a;\nmov.b64 {%2, %3}, b;\n}"
        : "=r"(v.x), "=r"(v.y), "=r"(v.z), "=r"(v.w) : "l"(p) : "memory");
    return v;
}
__device__ __forceinline__ void ld_ll_if(uint4& v, const void* p, bool go) {
    asm volatile("{\n.reg .b128 t;\n.reg .b64 a, b;\n.reg .pred q;\nsetp.ne.u32 q, %5, 0;\nmov.b64 a, {%0, %1};\nmov.b64 b, {%2, %3};\nmov.b128 t, {a, b};\n"
        "@q ld.relaxed.gpu.global.b128 t, [%4];\nmov.b128 {a, b}, t;\nmov.b64 {%0, %1}, a;\nmov.b64 {%2, %3}, b;\n}"
        : "+r"(v.x), "+r"(v.y), "+r"(v.z), "+r"(v.w) : "l"(p), "r"((uint32_t)go) : "memory");
}
__device__ __forceinline__ void st_ll8(void* p, uint32_t x, uint32_t y) {
    asm volatile("{\n.reg .b64 a;\nmov.b64 a, {%1, %2};\nst.relaxed.gpu.global.b64 [%0], a;\n}" :: "l"(p), "r"(x), "r"(y) : "memory");
}
__device__ __forceinline__ void st_ll4(void* p, uint32_t x) { asm volatile("st.relaxed.gpu.global.b32 [%0], %1;" :: "l"(p), "r"(x) : "memory"); }
__device__ __forceinline__ unsigned ld_rlx(const void* p) { unsigned v; asm volatile("ld.relaxed.gpu.global.u32 %0, [%1];" : "=r"(v) : "l"(p) : "memory"); return v; }
__device__ __forceinline__ void red_add4(void* p, float x, float y, float z, float w) {
    asm volatile("red.relaxed.gpu.global.add.v4.f32 [%0], {%1, %2, %3, %4};" :: "l"(p), "f"(x), "f"(y), "f"(z), "f"(w) : "memory");
}
__device__ __forceinline__ void fence_rel_gpu() { asm volatile("fence.proxy.async.global;\nfence.release.gpu;" ::: "memory"); }
__device__ __forceinline__ void fence_acq_gpu() { asm volatile("fence.acquire.gpu;" ::: "memory"); }
template<int N> __device__ __forceinline__ void poll_words(uint4 (&v)[N], const uint4* p, int stride, uint32_t tag) {
    #pragma unroll 1
    for (int it = 0; it < POLL_MAX; it++) {
        bool ok = true;
        #pragma unroll
        for (int i = 0; i < N; i++) v[i] = ld_ll(p + i * stride);
        #pragma unroll
        for (int i = 0; i < N; i++) ok = ok && (v[i].w == tag);
        if (__all_sync(0xffffffffu, ok)) break;
    }
}
template<int B> __device__ __forceinline__ uint32_t low_byte(float v, uint32_t src) { return __byte_perm(__float_as_uint(v), src, 0x3214 + B); }
__device__ __forceinline__ uint32_t low_bits(float v, uint32_t tag2) { return (__float_as_uint(v) & ~3u) | tag2; }
__device__ __forceinline__ bool tagged2(uint32_t w, uint32_t tag2) { return (w & 3u) == tag2; }
__device__ __forceinline__ uint32_t umax4(uint4 v) { return max(max(v.x, v.y), max(v.z, v.w)); }
constexpr uint32_t ONE2 = 0x3F803F80u;
__device__ __forceinline__ uint32_t pack2(float lo, float hi) { uint32_t d; asm("cvt.rn.bf16x2.f32 %0, %1, %2;" : "=r"(d) : "f"(hi), "f"(lo)); return d; }
__device__ __forceinline__ float bf_lo(uint32_t v) { return __uint_as_float(v << 16); }
__device__ __forceinline__ float bf_lo_after(uint32_t v, float nonneg) { float d; asm("prmt.b32 %0, %1, %2, 0x10ff;" : "=f"(d) : "r"(v), "f"(nonneg)); return d; }
__device__ __forceinline__ float bf_hi_after(uint32_t v, float nonneg) { float d; asm("prmt.b32 %0, %1, %2, 0x32ff;" : "=f"(d) : "r"(v), "f"(nonneg)); return d; }
__device__ __forceinline__ float bf_hi(uint32_t v) { return __uint_as_float(v & 0xffff0000u); }
__device__ __forceinline__ float rbf(float x) { return bf_lo(pack2(x, 0.f)); }
__device__ __forceinline__ uint32_t hsub2(uint32_t a, uint32_t b) { uint32_t d; asm("sub.rn.bf16x2 %0, %1, %2;" : "=r"(d) : "r"(a), "r"(b)); return d; }
__device__ __forceinline__ uint32_t hadd2(uint32_t a, uint32_t b) { uint32_t d; asm("add.rn.bf16x2 %0, %1, %2;" : "=r"(d) : "r"(a), "r"(b)); return d; }
__device__ __forceinline__ uint32_t hmul2(uint32_t a, uint32_t b) { uint32_t d; asm("mul.rn.bf16x2 %0, %1, %2;" : "=r"(d) : "r"(a), "r"(b)); return d; }
__device__ __forceinline__ uint32_t hmax2(uint32_t a, uint32_t b) { uint32_t d; asm("max.bf16x2 %0, %1, %2;" : "=r"(d) : "r"(a), "r"(b)); return d; }
__device__ __forceinline__ uint32_t hmin2(uint32_t a, uint32_t b) { uint32_t d; asm("min.bf16x2 %0, %1, %2;" : "=r"(d) : "r"(a), "r"(b)); return d; }
__device__ __forceinline__ float ex2(float x) { float y; asm("ex2.approx.ftz.f32 %0, %1;" : "=f"(y) : "f"(x)); return y; }
__device__ __forceinline__ float rcp(float x) { float y; asm("rcp.approx.ftz.f32 %0, %1;" : "=f"(y) : "f"(x)); return y; }
__device__ __forceinline__ float shfl_x(float v, int m) { return __shfl_xor_sync(0xffffffffu, v, m); }
constexpr float LOG2E = 1.4426950408889634f;
__device__ __forceinline__ float sigmoidf(float x) { return rcp(1.0f + ex2(-LOG2E * x)); }
__device__ __forceinline__ uint32_t ln_pair(uint32_t x, uint32_t m2, float rinv, uint32_t a, uint32_t s) {
    uint32_t d = hsub2(x, m2);
    uint32_t n = pack2(bf_lo(d) * rinv, bf_hi(d) * rinv);
    return hadd2(hmul2(n, a), s);
}
struct Recip { uint32_t hi, lo; };
__device__ __forceinline__ Recip split_recip(float r) { Recip q; q.hi = pack2(r, r); const float l = r - bf_hi(q.hi); q.lo = pack2(l, l); return q; }
__device__ __forceinline__ uint32_t hdiv2(uint32_t n, Recip r) { uint32_t d; asm("fma.rn.bf16x2 %0, %1, %2, %3;" : "=r"(d) : "r"(n), "r"(r.hi), "r"(hmul2(n, r.lo))); return d; }
__device__ __forceinline__ uint32_t ln_pair(uint32_t x, uint32_t m2, Recip r, uint32_t a, uint32_t s) { return hadd2(hmul2(hdiv2(hsub2(x, m2), r), a), s); }
__device__ __forceinline__ void ln_final(float s1, float s2, uint32_t& m2, float& rinv) {
    const float mean = s1 * (1.0f / 1024.0f), var = fmaf(-mean, mean, s2 * (1.0f / 1024.0f));
    m2 = pack2(mean, mean);
    float sd;
    asm("sqrt.approx.ftz.f32 %0, %1;" : "=f"(sd) : "f"(rbf(rbf(fmaxf(var, 0.f)) + 1e-5f)));
    rinv = rcp(rbf(sd));
}
__device__ __forceinline__ uint32_t f2key(float f) { uint32_t u = __float_as_uint(f); return (u & 0x80000000u) ? ~u : (u | 0x80000000u); }

__device__ __forceinline__ void fm_extrema(const uint32_t (&p)[16], float& cp, float& cn) {
    uint32_t mx = p[0], mn = p[0];
    #pragma unroll
    for (int k = 1; k < 15; k += 2) { mx = hmax2(hmax2(mx, p[k]), p[k + 1]); mn = hmin2(hmin2(mn, p[k]), p[k + 1]); }
    mx = hmax2(mx, p[15]); mn = hmin2(mn, p[15]);
    cp = -fmaxf(bf_lo(mx), bf_hi(mx)) * LOG2E; cn = fminf(bf_lo(mn), bf_hi(mn)) * LOG2E;
}
template<int TB> __device__ __forceinline__ void wgmma_n32_rs(float (&d)[16], uint32_t a0, uint32_t a1, uint32_t a2, uint32_t a3, uint64_t db, int sc) {
  asm volatile("{\n.reg .pred p;\nsetp.ne.b32 p, %21, 0;\n"
    "wgmma.mma_async.sync.aligned.m64n32k16.f32.bf16.bf16 {%0, %1, %2, %3, %4, %5, %6, %7, %8, %9, %10, %11, %12, %13, %14, %15}, {%16,%17,%18,%19}, %20, p, 1, 1, %22;\n}\n"
    : "+f"(d[0]), "+f"(d[1]), "+f"(d[2]), "+f"(d[3]), "+f"(d[4]), "+f"(d[5]), "+f"(d[6]), "+f"(d[7]), "+f"(d[8]), "+f"(d[9]), "+f"(d[10]), "+f"(d[11]), "+f"(d[12]), "+f"(d[13]), "+f"(d[14]), "+f"(d[15])
    : "r"(a0), "r"(a1), "r"(a2), "r"(a3), "l"(db), "r"(sc), "n"(TB));
}
template<int TA, int TB> __device__ __forceinline__ void wgmma_n40_ss(float (&d)[20], uint64_t da, uint64_t db, int sc) {
  asm volatile("{\n.reg .pred p;\nsetp.ne.b32 p, %22, 0;\n"
    "wgmma.mma_async.sync.aligned.m64n40k16.f32.bf16.bf16 {%0, %1, %2, %3, %4, %5, %6, %7, %8, %9, %10, %11, %12, %13, %14, %15, %16, %17, %18, %19}, %20, %21, p, 1, 1, %23, %24;\n}\n"
    : "+f"(d[0]), "+f"(d[1]), "+f"(d[2]), "+f"(d[3]), "+f"(d[4]), "+f"(d[5]), "+f"(d[6]), "+f"(d[7]), "+f"(d[8]), "+f"(d[9]), "+f"(d[10]), "+f"(d[11]), "+f"(d[12]), "+f"(d[13]), "+f"(d[14]), "+f"(d[15]), "+f"(d[16]), "+f"(d[17]), "+f"(d[18]), "+f"(d[19])
    : "l"(da), "l"(db), "r"(sc), "n"(TA), "n"(TB));
}
template<int TA, int TB> __device__ __forceinline__ void wgmma_n128_ss(float (&d)[64], uint64_t da, uint64_t db, int sc) {
  asm volatile("{\n.reg .pred p;\nsetp.ne.b32 p, %66, 0;\n"
    "wgmma.mma_async.sync.aligned.m64n128k16.f32.bf16.bf16 {%0, %1, %2, %3, %4, %5, %6, %7, %8, %9, %10, %11, %12, %13, %14, %15, %16, %17, %18, %19, %20, %21, %22, %23, %24, %25, %26, %27, %28, %29, %30, %31, %32, %33, %34, %35, %36, %37, %38, %39, %40, %41, %42, %43, %44, %45, %46, %47, %48, %49, %50, %51, %52, %53, %54, %55, %56, %57, %58, %59, %60, %61, %62, %63}, %64, %65, p, 1, 1, %67, %68;\n}\n"
    : "+f"(d[0]), "+f"(d[1]), "+f"(d[2]), "+f"(d[3]), "+f"(d[4]), "+f"(d[5]), "+f"(d[6]), "+f"(d[7]), "+f"(d[8]), "+f"(d[9]), "+f"(d[10]), "+f"(d[11]), "+f"(d[12]), "+f"(d[13]), "+f"(d[14]), "+f"(d[15]), "+f"(d[16]), "+f"(d[17]), "+f"(d[18]), "+f"(d[19]), "+f"(d[20]), "+f"(d[21]), "+f"(d[22]), "+f"(d[23]), "+f"(d[24]), "+f"(d[25]), "+f"(d[26]), "+f"(d[27]), "+f"(d[28]), "+f"(d[29]), "+f"(d[30]), "+f"(d[31]), "+f"(d[32]), "+f"(d[33]), "+f"(d[34]), "+f"(d[35]), "+f"(d[36]), "+f"(d[37]), "+f"(d[38]), "+f"(d[39]), "+f"(d[40]), "+f"(d[41]), "+f"(d[42]), "+f"(d[43]), "+f"(d[44]), "+f"(d[45]), "+f"(d[46]), "+f"(d[47]), "+f"(d[48]), "+f"(d[49]), "+f"(d[50]), "+f"(d[51]), "+f"(d[52]), "+f"(d[53]), "+f"(d[54]), "+f"(d[55]), "+f"(d[56]), "+f"(d[57]), "+f"(d[58]), "+f"(d[59]), "+f"(d[60]), "+f"(d[61]), "+f"(d[62]), "+f"(d[63])
    : "l"(da), "l"(db), "r"(sc), "n"(TA), "n"(TB));
}
template<int TB> __device__ __forceinline__ void wgmma_n128_rs(float (&d)[64], uint32_t a0, uint32_t a1, uint32_t a2, uint32_t a3, uint64_t db, int sc) {
  asm volatile("{\n.reg .pred p;\nsetp.ne.b32 p, %69, 0;\n"
    "wgmma.mma_async.sync.aligned.m64n128k16.f32.bf16.bf16 {%0, %1, %2, %3, %4, %5, %6, %7, %8, %9, %10, %11, %12, %13, %14, %15, %16, %17, %18, %19, %20, %21, %22, %23, %24, %25, %26, %27, %28, %29, %30, %31, %32, %33, %34, %35, %36, %37, %38, %39, %40, %41, %42, %43, %44, %45, %46, %47, %48, %49, %50, %51, %52, %53, %54, %55, %56, %57, %58, %59, %60, %61, %62, %63}, {%64,%65,%66,%67}, %68, p, 1, 1, %70;\n}\n"
    : "+f"(d[0]), "+f"(d[1]), "+f"(d[2]), "+f"(d[3]), "+f"(d[4]), "+f"(d[5]), "+f"(d[6]), "+f"(d[7]), "+f"(d[8]), "+f"(d[9]), "+f"(d[10]), "+f"(d[11]), "+f"(d[12]), "+f"(d[13]), "+f"(d[14]), "+f"(d[15]), "+f"(d[16]), "+f"(d[17]), "+f"(d[18]), "+f"(d[19]), "+f"(d[20]), "+f"(d[21]), "+f"(d[22]), "+f"(d[23]), "+f"(d[24]), "+f"(d[25]), "+f"(d[26]), "+f"(d[27]), "+f"(d[28]), "+f"(d[29]), "+f"(d[30]), "+f"(d[31]), "+f"(d[32]), "+f"(d[33]), "+f"(d[34]), "+f"(d[35]), "+f"(d[36]), "+f"(d[37]), "+f"(d[38]), "+f"(d[39]), "+f"(d[40]), "+f"(d[41]), "+f"(d[42]), "+f"(d[43]), "+f"(d[44]), "+f"(d[45]), "+f"(d[46]), "+f"(d[47]), "+f"(d[48]), "+f"(d[49]), "+f"(d[50]), "+f"(d[51]), "+f"(d[52]), "+f"(d[53]), "+f"(d[54]), "+f"(d[55]), "+f"(d[56]), "+f"(d[57]), "+f"(d[58]), "+f"(d[59]), "+f"(d[60]), "+f"(d[61]), "+f"(d[62]), "+f"(d[63])
    : "r"(a0), "r"(a1), "r"(a2), "r"(a3), "l"(db), "r"(sc), "n"(TB));
}
template<int TB> __device__ __forceinline__ void wgmma_n256_rs(float (&d)[128], uint32_t a0, uint32_t a1, uint32_t a2, uint32_t a3, uint64_t db, int sc) {
  asm volatile("{\n.reg .pred p;\nsetp.ne.b32 p, %133, 0;\n"
    "wgmma.mma_async.sync.aligned.m64n256k16.f32.bf16.bf16 {%0, %1, %2, %3, %4, %5, %6, %7, %8, %9, %10, %11, %12, %13, %14, %15, %16, %17, %18, %19, %20, %21, %22, %23, %24, %25, %26, %27, %28, %29, %30, %31, %32, %33, %34, %35, %36, %37, %38, %39, %40, %41, %42, %43, %44, %45, %46, %47, %48, %49, %50, %51, %52, %53, %54, %55, %56, %57, %58, %59, %60, %61, %62, %63, %64, %65, %66, %67, %68, %69, %70, %71, %72, %73, %74, %75, %76, %77, %78, %79, %80, %81, %82, %83, %84, %85, %86, %87, %88, %89, %90, %91, %92, %93, %94, %95, %96, %97, %98, %99, %100, %101, %102, %103, %104, %105, %106, %107, %108, %109, %110, %111, %112, %113, %114, %115, %116, %117, %118, %119, %120, %121, %122, %123, %124, %125, %126, %127}, {%128,%129,%130,%131}, %132, p, 1, 1, %134;\n}\n"
    : "+f"(d[0]), "+f"(d[1]), "+f"(d[2]), "+f"(d[3]), "+f"(d[4]), "+f"(d[5]), "+f"(d[6]), "+f"(d[7]), "+f"(d[8]), "+f"(d[9]), "+f"(d[10]), "+f"(d[11]), "+f"(d[12]), "+f"(d[13]), "+f"(d[14]), "+f"(d[15]), "+f"(d[16]), "+f"(d[17]), "+f"(d[18]), "+f"(d[19]), "+f"(d[20]), "+f"(d[21]), "+f"(d[22]), "+f"(d[23]), "+f"(d[24]), "+f"(d[25]), "+f"(d[26]), "+f"(d[27]), "+f"(d[28]), "+f"(d[29]), "+f"(d[30]), "+f"(d[31]), "+f"(d[32]), "+f"(d[33]), "+f"(d[34]), "+f"(d[35]), "+f"(d[36]), "+f"(d[37]), "+f"(d[38]), "+f"(d[39]), "+f"(d[40]), "+f"(d[41]), "+f"(d[42]), "+f"(d[43]), "+f"(d[44]), "+f"(d[45]), "+f"(d[46]), "+f"(d[47]), "+f"(d[48]), "+f"(d[49]), "+f"(d[50]), "+f"(d[51]), "+f"(d[52]), "+f"(d[53]), "+f"(d[54]), "+f"(d[55]), "+f"(d[56]), "+f"(d[57]), "+f"(d[58]), "+f"(d[59]), "+f"(d[60]), "+f"(d[61]), "+f"(d[62]), "+f"(d[63]), "+f"(d[64]), "+f"(d[65]), "+f"(d[66]), "+f"(d[67]), "+f"(d[68]), "+f"(d[69]), "+f"(d[70]), "+f"(d[71]), "+f"(d[72]), "+f"(d[73]), "+f"(d[74]), "+f"(d[75]), "+f"(d[76]), "+f"(d[77]), "+f"(d[78]), "+f"(d[79]), "+f"(d[80]), "+f"(d[81]), "+f"(d[82]), "+f"(d[83]), "+f"(d[84]), "+f"(d[85]), "+f"(d[86]), "+f"(d[87]), "+f"(d[88]), "+f"(d[89]), "+f"(d[90]), "+f"(d[91]), "+f"(d[92]), "+f"(d[93]), "+f"(d[94]), "+f"(d[95]), "+f"(d[96]), "+f"(d[97]), "+f"(d[98]), "+f"(d[99]), "+f"(d[100]), "+f"(d[101]), "+f"(d[102]), "+f"(d[103]), "+f"(d[104]), "+f"(d[105]), "+f"(d[106]), "+f"(d[107]), "+f"(d[108]), "+f"(d[109]), "+f"(d[110]), "+f"(d[111]), "+f"(d[112]), "+f"(d[113]), "+f"(d[114]), "+f"(d[115]), "+f"(d[116]), "+f"(d[117]), "+f"(d[118]), "+f"(d[119]), "+f"(d[120]), "+f"(d[121]), "+f"(d[122]), "+f"(d[123]), "+f"(d[124]), "+f"(d[125]), "+f"(d[126]), "+f"(d[127])
    : "r"(a0), "r"(a1), "r"(a2), "r"(a3), "l"(db), "r"(sc), "n"(TB));
}

#define T_S0 3300
#define T_S1 5800
#define G1W 1
#define LNP 1
#define CG1 232
#define JU 2
#define WPF 0
#define FPF 0
#define KW 8
#define DEP 2
#define STAG 0
#define KVSH 0
#define KVDLY 1200
#define PREWAIT 1
#define OUN 4
#define DNE 8
#define YGATE B_YP
#define YDLY 0
#define OUTGATE B_CAND
#define NEARLY 32
#define LN2P 1
#define LPACE 0
#define XGATE B_RED
#define MCW 0
#define SGATE 2
#define T_P0 1500
#define T_P1 3000
#define LATEFREE 1
#define NC 2
#define T_W1 2800
#define T_WD 0
#define NW0 32
#define PFN 3
#define PFJ 2
#define PFM 4
#define WOJ 10
#define WON 1
#define NLD 1
#define VFIRST 2
#define T_X0 450
#define T_XD 600
#define MCB 1
#define ORIENT 2
#define PFORDER 0x51634
#define PFORDER2 0x51
#define PFW0 2
#define CLRJ 3
#define CLRK 8
#define JPF 0
#define CLRGATE (B_FB + 4)
#define KVC0 0
#define CLRS 50
#define OGATE 5
#define PFD 0
#define GBN 6
#define BG1 99
#define BG2 99
#define BG3 99
#define BG4 99
#define BG5 99
#define SYNCQ 640
#define SYNCG 4
#define BSP 0
#define T_INI 500
#define T_WLATE 4000
#define T_REST 7000
#define T_COL 3000
#define PF_START 9000
#define PF_FIRST 2
#define PFP 400
#define CREG 208
#define TMA_WO tma2_ef_e
#define TMA_M tma2_ef_e
#define TMA_F tma2_ef_e
#define JUN 4
constexpr int JUU = JUN, OUU = OUN;
constexpr bool GS2 = false;
struct Ptrs { const bf16 *x, *c, *wmod, *wr, *wg, *wu, *wd, *wqkv, *wo; bf16* out; Scratch* s; };

#define BAR(i) (sb + OFF_BAR + 8u * (i))

__device__ __forceinline__ int d_block(int hg, int n) {
    const int m = n - (n >= 9 ? 9 : 2);
    return n < 2 ? 2 * hg + n : 2 * (m + (m >= hg)) + (n >= 9);
}
__host__ __device__ constexpr uint32_t bar_count(int i) {
    return ((MCB && i >= B_ED && i < B_ED + 16) || (MCW && i >= B_E1 && i < B_E1 + 3)) ? 16 : ((i >= B_E1 && i < B_E1 + 3) || (i >= B_S0FREE && i < B_PHI + 4) || i == B_OWN || i == B_OWN + 1 || (i >= B_ED && i < B_ED + 16)
            || i == B_STFREE || i == B_X2 || i == B_OUTW || i == B_YP || i == B_RED) ? 8
         : ((i >= B_KVD && i < B_KVD + 2) || i == B_ST2) ? 4 : (i == B_KVF || i == B_KVF + 1 ) ? 2 : 1;
}
template<int I0, int I1> __device__ __forceinline__ void init_barriers(uint32_t sb) {
    #pragma unroll
    for (int i = I0; i < I1; i++) mbar_init(BAR(i), bar_count(i));
}
template<int N> __device__ __forceinline__ uint32_t pop_max(uint32_t (&k)[N]) {
    uint32_t m = k[0];
    #pragma unroll
    for (int i = 1; i < N; i++) m = max(m, k[i]);
    m = __reduce_max_sync(0xffffffffu, m);
    #pragma unroll
    for (int i = 0; i < N; i++) k[i] = (k[i] == m) ? 0u : k[i];
    return m;
}
__device__ __forceinline__ uint32_t mod_pos(int step, int g) { return step * 64 + (g >> 1) * 16 + (g & 1) * 4; }
__device__ __forceinline__ void fma8(float (&a)[8], uint4 w, float s) {
    a[0] = fmaf(bf_lo(w.x), s, a[0]); a[1] = fmaf(bf_hi(w.x), s, a[1]); a[2] = fmaf(bf_lo(w.y), s, a[2]); a[3] = fmaf(bf_hi(w.y), s, a[3]);
    a[4] = fmaf(bf_lo(w.z), s, a[4]); a[5] = fmaf(bf_hi(w.z), s, a[5]); a[6] = fmaf(bf_lo(w.w), s, a[6]); a[7] = fmaf(bf_hi(w.w), s, a[7]);
}
__device__ __forceinline__ float reduce8(const float (&v)[8], int lane) {
    const bool b3 = lane & 16, b2 = lane & 8, b1 = lane & 4;
    float a[4], b[2];
    #pragma unroll
    for (int i = 0; i < 4; i++) { float keep = b3 ? v[4 + i] : v[i], send = b3 ? v[i] : v[4 + i]; a[i] = keep + shfl_x(send, 16); }
    #pragma unroll
    for (int i = 0; i < 2; i++) { float keep = b2 ? a[2 + i] : a[i], send = b2 ? a[i] : a[2 + i]; b[i] = keep + shfl_x(send, 8); }
    float keep = b1 ? b[1] : b[0], send = b1 ? b[0] : b[1];
    return keep + shfl_x(send, 4);
}
__device__ __forceinline__ bool mod_collect(uint4 w0, uint4 w1, uint4 w2, uint4 w3, uint32_t sb, int jb, int lane, uint32_t tag2) {
    const uint32_t add = lane < 16 ? ONE2 : 0u;
    const uint32_t lo = pack2((__uint_as_float(w0.x) + __uint_as_float(w1.x)) + (__uint_as_float(w2.x) + __uint_as_float(w3.x)),
                              (__uint_as_float(w0.y) + __uint_as_float(w1.y)) + (__uint_as_float(w2.y) + __uint_as_float(w3.y)));
    const uint32_t hi = pack2((__uint_as_float(w0.z) + __uint_as_float(w1.z)) + (__uint_as_float(w2.z) + __uint_as_float(w3.z)),
                              (__uint_as_float(w0.w) + __uint_as_float(w1.w)) + (__uint_as_float(w2.w) + __uint_as_float(w3.w)));
    sts64(sb + OFF_MODS + jb * 256 + (lane & 15) * 16 + (lane >> 4) * 8, hadd2(lo, add), hadd2(hi, add));
    return tagged2(w0.w, tag2) && tagged2(w1.w, tag2) && tagged2(w2.w, tag2) && tagged2(w3.w, tag2);
}
__device__ __forceinline__ void phi_issue(float (&pp)[2][16], const uint32_t* a, uint32_t sb, int pair) {
    const uint64_t dw = mk_desc(sb + OFF_WPHI + pair * 4096, 16, 512, 2);
    wg_fence();
    #pragma unroll
    for (int ks = 0; ks < 2; ks++)
        #pragma unroll
        for (int h = 0; h < 2; h++) wgmma_n32_rs<1>(pp[h], a[8 * h + 4 * ks], a[8 * h + 4 * ks + 1], a[8 * h + 4 * ks + 2], a[8 * h + 4 * ks + 3], desc_add(dw, h * 2048 + ks * 1024), ks);
    wg_commit();
}
__device__ __forceinline__ void phi_transpose(float (&pp)[2][16], uint32_t (&pt)[16], uint32_t wr, uint32_t rd) {
    wg_wait<0>();
    acc_fence(pp[0]); acc_fence(pp[1]);
    #pragma unroll
    for (int q = 0; q < 4; q++) {
        const float (&a)[16] = pp[q >> 1]; const int o = 8 * (q & 1);
        stsm4(wr ^ (q << 5), pack2(a[o], a[o + 1]), pack2(a[o + 2], a[o + 3]), pack2(a[o + 4], a[o + 5]), pack2(a[o + 6], a[o + 7]));
    }
    __syncwarp();
    #pragma unroll
    for (int i = 0; i < 4; i++) { const uint4 v = lds128(rd ^ (i << 4)); pt[4 * i] = v.x; pt[4 * i + 1] = v.y; pt[4 * i + 2] = v.z; pt[4 * i + 3] = v.w; }
    __syncwarp();
}

__global__ void __cluster_dims__(2, 1, 1) __launch_bounds__(NTHREADS, 1)
fused_kernel(const Ptrs p, const __grid_constant__ CUtensorMap tmW, const __grid_constant__ CUtensorMap tmWo, const __grid_constant__ CUtensorMap tmPhi,
             const __grid_constant__ CUtensorMap tmG, const __grid_constant__ CUtensorMap tmU, const __grid_constant__ CUtensorMap tmD,
             const __grid_constant__ CUtensorMap tmX, const __grid_constant__ CUtensorMap tmO, const __grid_constant__ CUtensorMap tmM,
             const __grid_constant__ CUtensorMap tmR, const __grid_constant__ CUtensorMap tmG8, const __grid_constant__ CUtensorMap tmU8,
             const __grid_constant__ CUtensorMap tmD8, const __grid_constant__ CUtensorMap tmW2)
{
    extern __shared__ __align__(1024) uint8_t smem_raw[];
    const uint32_t sb = smem_u32(smem_raw);
    const int tid = threadIdx.x, lane = tid & 31, warp = __shfl_sync(0xffffffffu, tid >> 5, 0);
    const int b = blockIdx.x;
    const int pr = b >> 1, rank = b & 1;
    const int cls = pr < 4 ? 15 : pr < 36 ? 2 * ((pr - 4) & 7) : 2 * ((pr - 36) % 7) + 1, mem = pr < 4 ? pr : pr < 36 ? (pr - 4) >> 3 : (pr - 36) / 7;
    const int hg = (((cls + 1) >> 1) & 1) * 4 + mem, rb = (cls >> 1) * 2 + rank;
    const bool ffn = b < 112;
    const uint32_t cstart = clk32();

    if (warp >= 8) {
        const int t = tid & 127, w4 = warp & 3, g = lane >> 2, c = lane & 3;
        if (w4 == 0) TS(40);
        reg_dec<504 - 2 * CG1>();
        if (w4 == 2) TS(41);
        if (w4 == 0) { tmap_prefetch(&tmX); tmap_prefetch(&tmW); }
        if (w4 == 3) tmap_prefetch(&tmM);
        if (w4 < 2) while (clk32() - cstart < T_INI) {}
        if (elect_one()) {
            if (w4 & 2) { if (w4 & 1) init_barriers<B_WS, B_COUNT>(sb); else init_barriers<B_XS, B_WS>(sb); }
            else { if (w4 & 1) init_barriers<B_MP, B_XS>(sb); else init_barriers<0, B_MP>(sb); }
        }
        __syncwarp();
        if (w4 < 2) asm volatile("fence.mbarrier_init.release.cluster;" ::: "memory");
        if (w4 == 1) {
            expect_tx_e(BAR(B_PX), 2048); sts32(sb + OFF_SEEN, 0);
        }
        if (w4 == 0) TS(42);
        bar_arrive(0, 384);
        if (w4 == 2) {
            #pragma unroll 1
            for (int i = 0; i < 4; i++) {
                while (clk32() - cstart < T_X0 + i * T_XD) {}
                bulk_load_e(sb + OFF_XS + i * 8192u, p.x + (size_t)(b * 16 + i * 4) * 1024, 8192, BAR(B_XS + i));
                expect_tx_e(BAR(B_XS + i), 8192);
                if (i == 0) TS(43);
            }
        }
        if (w4 == 3 && b < 32 * NC) {
            while (b >= NW0 && clk32() - cstart < T_W1 + (b >> 5) * T_WD) {}
            #pragma unroll 1
            for (int i = 0; i < 4; i++) {
                tma2_ef_e(sb + OFF_WST + i * 8192u, &tmM, (((b >> 2) & 1) ? 0 : 1024) + (b >> 3) * 64, (b & 3) * 256 + i * 64, BAR(B_WS + i));
                expect_tx_e(BAR(B_WS + i), 8192);
            }
            TS(44);
        }
        cluster_arrive();
        const uint32_t tag = ld_rlx(p.s->done) + 1, tag2 = tag % 3u;
        if (w4 == 0) {
            int piece = ffn ? 0 : 20;
            uint4* clr = p.s->kvp + (hg * 1024 + KVC0 * 128 + rb) * 32 + lane;
            #pragma unroll 1
            for (int j = 0; j < 3; j++) {
                while (clk32() - cstart < (j ? T_P1 : T_P0)) {}
                if (lane < 24) asm volatile("prefetch.global.L2 [%0];" :: "l"((const char*)p.wqkv + ((j * 128 + b) * 24 + lane) * 128));
            }
            int s = 0;
            #pragma unroll 1
            for (int j = 0; j < 17; j++) {
                if (j >= 3) mbar_wait(BAR(B_E1 + s), ((j / 3) - 1) & 1);
                else if (j >= SGATE) mbar_wait(BAR(B_STFREE), 0);
                else while (clk32() - cstart < (j ? T_S1 : T_S0)) {}
                const uint32_t st = sb + OFF_RING + s * 65536u;
                if (j < 16) {
                    expect_tx_e(BAR(B_F1 + s), 65536);
                    tma4_ef_e(st + 16384u, &tmW, j * 64, hg * 2, BAR(B_F1 + s));
                    tma2_e(st, &tmX, j * 64, rb * 128, BAR(B_F1 + s));
                } else {
                    #pragma unroll 1
                    for (int n = 0; n < 4; n++) {
                        if (!(n & 1)) expect_tx_e(BAR(B_FB + 4 + (n >> 1)), 16384);
                        TMA_WO(st + n * 8192u, &tmWo, hg * 128 + (n & 1) * 64, (2 * hg + (n >> 1)) * 64, BAR(B_FB + 4 + (n >> 1)));
                    }
                }
                if (j == 1) TS(50);
                s = s == 2 ? 0 : s + 1;
                if (j == 3) expect_tx_e(BAR(B_PF), ffn ? 20480 : 0);
                #pragma unroll 1
                for (; j >= 3 && piece < min(20, j < 16 ? (j - PFJ) * PFM / 4 : 20); piece++)
                    tma2_e(sb + OFF_PAR, piece < 8 ? &tmD8 : (piece & 1) ? &tmU8 : &tmG8, piece < 8 ? rank * 512 + piece * 64 : pr * 64,
                           piece < 8 ? pr * 64 : rank * 512 + (11 - (piece >> 1)) * 64, BAR(B_PF));
                if (j >= WOJ && j < WOJ + 4 * WON) asm volatile("prefetch.global.L2 [%0];" :: "l"((const char*)p.wo + ((j - WOJ) & 3) * 524288 + (b * 32 + lane) * 128));
                if (j >= CLRJ && j < CLRJ + 8 - KVC0) {
                    #pragma unroll
                    for (int i = 0; i < 8; i++) stg_fill(clr + i * 512, EMPTY);
                    clr += 4096;
                }
            }
            mbar_wait(BAR(B_E1 + 0), 1);
            expect_tx_e(BAR(B_S0), ffn ? 65536 : 32768);
            tma2_ef_e(sb + OFF_XT, &tmX, hg * 128, rb * 128, BAR(B_S0)); tma2_ef_e(sb + OFF_XT + 16384u, &tmX, hg * 128 + 64, rb * 128, BAR(B_S0));
            #pragma unroll 1
            for (int i = 0; i < (ffn ? 2 : 0); i++) tma2_ef_e(sb + OFF_GA + i * 16384u, i ? &tmU : &tmG, pr * 64, rank * 512, BAR(B_S0));
        } else if (w4 == 1) {
            while (clk32() - cstart < T_COL) {}
            #pragma unroll 1
            for (int it = 0, jb = 0, ph = 0; it < POLL_MAX && jb < 16; it++) {
                const int n = jb < NLD ? 1 : min(4, 16 - jb);
                if (jb >= NLD) {
                    expect_tx_e(BAR(B_MP), n * 2048);
                    bulk_load_e(sb + OFF_WPHI, p.s->mp + jb * 128, n * 2048, BAR(B_MP));
                    mbar_wait(BAR(B_MP), ph);
                    ph ^= 1;
                }
                #pragma unroll 1
                for (int q = 0; q < n; q++) {
                    uint4 w[4];
                    if (jb < NLD) {
                        #pragma unroll
                        for (int i = 0; i < 4; i++) w[i] = ld_ll(p.s->mp + (jb * 8 + (lane >> 4) * 4 + i) * 16 + (lane & 15));
                    } else {
                        #pragma unroll
                        for (int i = 0; i < 4; i++) w[i] = lds128(sb + OFF_WPHI + q * 2048 + (lane >> 4) * 1024 + (lane & 15) * 16 + i * 256);
                    }
                    if (!__all_sync(0xffffffffu, mod_collect(w[0], w[1], w[2], w[3], sb, jb, lane, tag2))) { if (jb >= 4) __nanosleep(300); break; }
                    arrive_many(BAR(B_MOD + jb), bar_count(B_MOD));
                    if (jb == 0) TS(51);
                    if (jb == 4) TS(5);
                    if (jb == 15) TS(8);
                    jb++;
                }
            }
            fence_async_smem();
            __syncwarp();
            expect_tx_e(BAR(B_WPHI), 8192);
            tma2_e(sb + OFF_WPHI, &tmPhi, 0, hg * 128, BAR(B_WPHI));
            #pragma unroll 1
            for (int i = 0; i < 4; i++) {
                uint4* rw = p.s->rowh + (rb * 8 + i * 2 + (lane >> 4)) * 128 + hg * 16 + (lane & 15);
                stg_fill(rw, EMPTY); stg_fill(rw + 16384, EMPTY);
                if (lane < 18) stg_fill(p.s->kvf + (hg * 4 + i) * 288 + (lane < 16 ? (rb >> 2) * 64 + (rb & 3) * 8 + (lane >> 3) * 32 + (lane & 7) : 240 + rb * 2 + lane), EMPTY);
            }
            if (hg == 0 && lane < 8) stg_fill(p.s->cand + rb * 8 + lane, 0);
            if (lane < 28) stg_fill(lane < 16 ? p.s->st2 + rb * 128 + hg * 16 + lane : lane < 20 ? p.s->flo + (rb * 16 + hg * 2) * 2 + lane - 16
                                    : p.s->rsc + ((rb * 4 + ((lane - 20) >> 1)) * 8 + hg) * 2 + (lane & 1), 0);
            fence_rel_gpu();
            #pragma unroll 1
            for (int i = 0; i < (ffn ? 9 : 8); i++) {
                uint4* d = (i < 8 ? p.s->os + (rb * 16 + 2 * hg) * 1024 + i * 256 : p.s->yp + pr * 512 + rank * 128) + lane;
                #pragma unroll
                for (int q = 0; q < 4; q++) { stg_fill(d + q * 32, EMPTY); stg_fill(d + (i < 8 ? 128 : 256) + q * 32, EMPTY); }
            }
            TS(36);
        } else {
            const int hw = w4 & 1;
            const uint32_t fb = BAR(B_RF + 2 * hw);
            if (w4 == 2) {
                if (lane < 8) stg_fill(p.s->rest + b * 8 + lane, 0);
                else if (lane < 24 && b >= 32 * NC) stg_fill(p.s->mp + b * 16 + lane - 8, EMPTY);
            }
            bar_sync(3, 320);
            const uint32_t buf = sb + OFF_SP + hw * 8192u;
            #pragma unroll 1
            for (int job = b < 32 * NC; job < 2; job++) {
                const int nr = job ? 8 : 4;
                const int c0 = job ? 2048 + b * 32 : (((b >> 2) & 1) ? 0 : 1024) + (b >> 3) * 64 + hw * 32;
                const int row0 = job ? hw * 512 : (b & 3) * 256;
                while (clk32() - cstart < (job ? T_REST : T_WLATE)) __nanosleep(100);
                float macc[8] = {0.f, 0.f, 0.f, 0.f, 0.f, 0.f, 0.f, 0.f};
                #pragma unroll 1
                for (int q = -2; q < nr; q++) {
                    if (q >= 0) {
                        mbar_wait(fb + (q & 1) * 8, (q >> 1) & 1);
                        const uint32_t sv0 = sb + OFF_SILU + (row0 + q * 64 + g) * 2, wa = buf + (q & 1) * 4096u + lane * 16u;
                        #pragma unroll JUU
                        for (int i = 0; i < 8; i += 2) {
                            const uint32_t s0 = lds16(sv0 + i * 16), s1 = lds16(sv0 + i * 16 + 16);
                            const uint4 w0 = lds128(wa + i * 512u), w1 = lds128(wa + i * 512u + 512u);
                            fma8(macc, w0, bf_lo(s0)); fma8(macc, w1, bf_lo(s1));
                        }
                    }
                    __syncwarp();
                    if (q + 2 < nr) {
                        expect_tx_e(fb + (q & 1) * 8, 4096);
                        TMA_M(buf + (q & 1) * 4096u, &tmR, c0, row0 + (q + 2) * 64, fb + (q & 1) * 8);
                    }
                }
                stsf(sb + OFF_RED0 + (job ? hw * 256 + (c * 8 + g) * 4 : mod_pos(hw * 2 + (c >> 1), g) + (c & 1) * 8), reduce8(macc, lane));
                bar_sync(4, 64);
                if (w4 == 2) {
                    const uint4 u0 = lds128(sb + OFF_RED0 + (lane & 15) * 16), u1 = lds128(sb + OFF_RED0 + 256 + (lane & 15) * 16);
                    const float v0 = __uint_as_float(u0.x) + __uint_as_float(u1.x), v1 = __uint_as_float(u0.y) + __uint_as_float(u1.y);
                    const float v2 = __uint_as_float(u0.z) + __uint_as_float(u1.z), v3 = __uint_as_float(u0.w) + __uint_as_float(u1.w);
                    const uint32_t add = (b >> 5) == 2 ? ONE2 : 0u;
                    if (job == 0) { if (lane < 16) st_ll(p.s->mp + b * 16 + lane, u0.x, u0.y, u0.z, low_bits(__uint_as_float(u0.w), tag2)); TS(13); }
                    else { if (lane < 8) st_ll(p.s->rest + b * 8 + lane, hadd2(pack2(v0, v1), add), hadd2(pack2(v2, v3), add), 0, tag); TS(33); }
                }
                bar_sync(4, 64);
            }
            tmap_prefetch(hw ? &tmWo : &tmG); tmap_prefetch(hw ? &tmU : &tmD); tmap_prefetch(hw ? &tmPhi : &tmO);
        }
        __syncwarp();
        cluster_wait();
        bar_sync(2, 128);
        reg_inc<504 - 2 * CREG>();
        if (w4 == 0) TS(6);
        #pragma unroll 1
        for (int pp = 0; pp < 2; pp++) {
            mbar_wait(BAR(B_PHI + pp), 0);
            if (w4 == 0) TS(pp ? 59 : 52);
            fence_async_smem();
            float o[2][20];
            const uint32_t vb = OFF_V + pp * 16384u;
            const uint64_t dp = mk_desc(sb + (pp ? OFF_PHI1 : OFF_PHI0), 16, 1024, 1), dv = mk_desc(sb + vb, OFF_ONES - vb, 512, 2);
            wg_fence();
            #pragma unroll
            for (int hh = 0; hh < 2; hh++) {
                #pragma unroll
                for (int ks = 0; ks < 8; ks++)
                    wgmma_n40_ss<1, 1>(o[hh], desc_add(dp, hh * 16384 + ks * 2048), desc_raw(dv, (hh * 8 + ks) * (64 - (64 << 16))), ks);
                wg_commit();
            }
            #pragma unroll
            for (int hh = 0; hh < 2; hh++) {
                if (hh) wg_wait<0>(); else wg_wait<1>();
                acc_fence(o[hh]);
                if (hh) arrive_one(BAR(B_KVD + pp));
                if (hh == KVSH && pp && w4 < 2) {
                    mbar_wait(BAR(B_KVD), 0);
                    bulk_load_e(sb + OFF_KVS + w4 * 8192u, p.s->kvp + ((hg * 4 + w4) * 16 + rb) * 512, 8192, BAR(B_KVS + w4));
                    expect_tx_e(BAR(B_KVS + w4), 8192);
                }
                uint4* dst = p.s->kvp + (((hg * 4 + 2 * pp + hh) * 16 + (t >> 3)) * 16 + rb) * 32 + (t & 7);
                const float (&a)[20] = o[hh];
                #pragma unroll
                for (int k = 0; k < 2; k++) {
                    const uint32_t z = __float_as_uint(a[16 + 2 * k]);
                    st_ll(dst + k * 8, low_byte<1>(a[4 * k], z), low_byte<2>(a[4 * k + 1], z), low_byte<3>(a[4 * k + 2], z), low_bits(a[4 * k + 3], tag2));
                    st_ll(dst + 16 + k * 8, __float_as_uint(a[8 + 4 * k]), __float_as_uint(a[9 + 4 * k]), __float_as_uint(a[10 + 4 * k]), low_bits(a[11 + 4 * k], tag2));
                }
            }
        }
        if (w4 == 0) TS(17);
        {
            uint4* const fin = p.s->kvf + (hg * 4 + w4) * 288;
            {
                const uint4* src = p.s->kvp + ((hg * 4 + w4) * 16 + rb) * 512 + lane;
                uint4 w[16];
                if (KVSH < 2 && w4 < 2) {
                    mbar_wait(BAR(B_KVS + w4), 1);
                    #pragma unroll
                    for (int i = 0; i < 16; i++) w[i] = lds128(sb + OFF_KVS + w4 * 8192u + i * 512u + lane * 16u);
                } else {
                    if (KVDLY) { const uint32_t c0 = clk32(); while (clk32() - c0 < KVDLY) {} }
                    #pragma unroll
                    for (int i = 0; i < 16; i++) w[i].w = EMPTY;
                }
                #pragma unroll 1
                for (int it = 0; it < POLL_MAX; it++) {
                    bool ok = true;
                    #pragma unroll
                    for (int i = 0; i < 16; i++) { const bool miss = !tagged2(w[i].w, tag2); ok = ok && !miss; ld_ll_if(w[i], src + i * 32, miss); }
                    if (__all_sync(0xffffffffu, ok)) break;
                }
                if (w4 == 0) TS(18);
                if (w4 == 3) TS(10);
                float s[5], s2[5];
                #pragma unroll
                for (int i = 0; i < 16; i++) {
                    const float z = __uint_as_float(__byte_perm(__byte_perm(w[i].x, w[i].y, 0x0400), w[i].z, 0x4210));
                    float (&a)[5] = (i & 1) ? s2 : s;
                    if (i < 2) { a[0] = __uint_as_float(w[i].x); a[1] = __uint_as_float(w[i].y); a[2] = __uint_as_float(w[i].z); a[3] = __uint_as_float(w[i].w); a[4] = z; }
                    else { a[0] += __uint_as_float(w[i].x); a[1] += __uint_as_float(w[i].y); a[2] += __uint_as_float(w[i].z); a[3] += __uint_as_float(w[i].w); a[4] += z; }
                }
                #pragma unroll
                for (int i = 0; i < 5; i++) s[i] += s2[i];
                char* d = (char*)fin + ((rb >> 2) * 16 + (rb & 3) * 2 + (g & 1)) * 64 + (((lane >> 3) ^ (rb & 3)) << 4) + c * 4;
                st_ll4(d, pack2(s[0], s[1]));
                st_ll4(d + 512, pack2(s[2], s[3]));
                if (lane < 16 && c < 2) st_ll4((char*)fin + 4096 + rb * 32 + (g * 2 + c) * 4, pack2(s[4], s[4]));
            }
            fence_acq_gpu();
            uint4 v[9];
            #pragma unroll 1
            for (int it = 0; it < POLL_MAX; it++) {
                uint32_t m = 0;
                #pragma unroll
                for (int k = 0; k < 9; k++) v[k] = ld_ll(fin + k * 32 + lane);
                #pragma unroll
                for (int k = 0; k < 9; k++) m = max(m, umax4(v[k]));
                if (__all_sync(0xffffffffu, m != EMPTY)) break;
            }
            #pragma unroll
            for (int k = 0; k < 8; k++) sts128(sb + OFF_SP + w4 * 4096u + k * 512u + lane * 16u, v[k]);
            const uint32_t za = sb + OFF_Z + ((lane >> 3) * 16 + ((lane >> 1) & 3) * 2 + (lane & 1) * 8) * 64u + ((w4 ^ ((lane >> 1) & 3)) << 4);
            sts128(za, make_uint4(v[8].x, v[8].x, v[8].x, v[8].x)); sts128(za + 64, make_uint4(v[8].z, v[8].z, v[8].z, v[8].z));
            __syncwarp();
            arrive_one(BAR(B_KVF + (w4 >> 1)));
            if (w4 == 0) TS(19);
            if (w4 == 3) TS(1);
        }
        if (w4 == 0) {
            const unsigned* f = (const unsigned*)(p.s->flo + (rb * 16 + d_block(hg, lane & 15)) * 2);
            const uint4* const a0 = p.s->os + rb * 16384;
            uint32_t seen = 0;
            uint32_t kb = hg ? 0 : 2, s = 4, freeb = BAR(B_OWN), par = 0;
            fence_rel_gpu();
            arrive_one(BAR(B_REL));
            mbar_wait(BAR(B_OWN), 0);
            #pragma unroll 1
            for (int n = 2; n < 16; n++) {
                if (!((seen >> n) & 1)) {
                    if (n >= 8) asm volatile("ld.acquire.cta.shared.u32 %0, [%1];" : "=r"(seen) : "r"(sb + OFF_SEEN) : "memory");
                    #pragma unroll 1
                    for (int it = 0; it < POLL_MAX && !((seen >> n) & 1); it++) { seen = __ballot_sync(0xffffffffu, ld_rlx(f) == tag); fence_acq_gpu(); }
                }
                mbar_wait(freeb, par);
                TR(64 + n);
                bulk_load_e(sb + OFF_DA + s * 16384u, a0 + kb * 1024, 16384, BAR(B_FA + s));
                expect_tx_e(BAR(B_FA + s), 16384);
                if (n == 2) TS(2);
                TR(16 + n);
                if (n == OGATE) arrive_one(BAR(B_OGO));
                if (n == 5 || n == 6) mbar_wait(BAR(B_PUB + n - 5), 0);
                kb = n == 8 ? 1 : kb + 2;
                if ((kb >> 1) == hg) kb += 2;
                s = (SLOT_A >> (4 * n + 4)) & 7;
                if (n >= 5) { freeb = BAR(B_ED + n - 5); par = 1; } else if (n == 3) freeb = BAR(B_OWN + 1);
            }
        } else if (w4 == 1) {
            if (ffn) { expect_tx_e(BAR(B_GU), 98304); expect_tx_e(BAR(B_WD), 65536); }
            mbar_wait(BAR(B_S0FREE), 0);
            #pragma unroll 1
            for (int n = 2; n < (ffn ? 20 : 16); n++) {
                if (n == BG1) mbar_wait(BAR(B_KVF + 1), 0);
                if (n == BG2) mbar_wait(BAR(B_PUB), 0);
                if (n == BG5) mbar_wait(BAR(B_OGO), 1);
                if (n >= 6) mbar_wait(BAR(B_ED + n - 6), 1);
                if (n < 16) {
                    const uint32_t s = (SLOT_B >> (4 * n)) & 7, bar = BAR(B_FB + s), dst = sb + OFF_DB + s * 16384u;
                    expect_tx_e(bar, 16384);
                    if (MCB && n >= 6) tma2_mc_e(dst + rank * 8192u, &tmWo, hg * 128 + rank * 64, d_block(hg, n) * 64, bar);
                    else { TMA_WO(dst, &tmWo, hg * 128, d_block(hg, n) * 64, bar); TMA_WO(dst + 8192u, &tmWo, hg * 128 + 64, d_block(hg, n) * 64, bar); }
                    if (ffn && n >= GBN && n < GBN + 2) TMA_F(sb + OFF_GB + (n - GBN) * 16384u, n > GBN ? &tmU : &tmG, pr * 64, rank * 512 + 128, BAR(B_GU));
                } else if (n < 18) {
                    if (n == 16) TS(49);
                    TMA_F(sb + OFF_UP0 + (n & 1) * 16384u, (n & 1) ? &tmU : &tmG, pr * 64, rank * 512 + 256, BAR(B_GU));
                    TMA_F(sb + OFF_UP1 + (n & 1) * 16384u, (n & 1) ? &tmU : &tmG, pr * 64, rank * 512 + 384, BAR(B_GU));
                } else {
                    tma3_ef_e(sb + OFF_DN0 + (n & 1) * 16384u, &tmD, pr * 64, rank * 8 + (n & 1) * 2, BAR(B_WD));
                    tma3_ef_e(sb + OFF_DN1 + (n & 1) * 16384u, &tmD, pr * 64, rank * 8 + 4 + (n & 1) * 2, BAR(B_WD));
                }
            }
        } else if (w4 == 3) {
            const unsigned* f = (const unsigned*)(p.s->flo + (rb * 16 + d_block(hg, lane & 15)) * 2);
            uint32_t seen = 0xffff0003u;
            mbar_wait(BAR(B_PUB + 1), 0);
            #pragma unroll 1
            for (int it = 0; it < POLL_MAX && seen != 0xffffffffu; it++) {
                const uint32_t m = seen | __ballot_sync(0xffffffffu, !((seen >> lane) & 1) && ld_rlx(f) == tag);
                if (m != seen) {
                    seen = m;
                    fence_acq_gpu();
                    __syncwarp();
                    asm volatile(EL "st.release.cta.shared.u32 [%0], %1;\n}" :: "r"(sb + OFF_SEEN), "r"(seen) : "memory");
                }
            }
        } else {
            asm volatile("fence.proxy.async.global;" ::: "memory");
            #pragma unroll 1
            for (int q = 0; q < 2; q++) {
                if (q) mbar_wait(BAR(B_OGO), 1);
                mbar_wait(BAR(B_OWN + q), 0);
                fence_async_smem();
                bulk_store_e(p.s->os + (rb * 16 + 2 * hg + q) * 1024, sb + OFF_OWN + q * 16384u, 16384);
                bulk_commit();
                bulk_wait();
                mbar_wait(BAR(B_REL), 0);
                st_flag_e(p.s->flo + (rb * 16 + 2 * hg + q) * 2, tag);
                arrive_one(BAR(B_PUB + q));
                if (q == 0) TS(3);
                TR(q);
            }
            mbar_wait(BAR(B_PF), 1);
            {
                uint4 w[4];
                poll_words<4>(w, p.s->rest + hg * 32 + lane, 256, tag);
                sts64(sb + OFF_PAR + lane * 8, w[2].x, w[2].y); sts64(sb + OFF_PAR + 256 + lane * 8, w[1].x, w[1].y);
                sts64(sb + OFF_PAR + 512 + lane * 8, w[3].x, w[3].y); sts64(sb + OFF_PAR + 768 + lane * 8, w[0].x, w[0].y);
                const uint2 wr = ldg64(p.wr + hg * 128 + lane * 4);
                sts64(sb + OFF_BQ + lane * 8, hmul2(w[2].x, wr.x), hmul2(w[2].y, wr.y));
            }
            float s = 0.f;
            #pragma unroll 1
            for (int i = 0; i < 2; i++) {
                uint4 w[4]; uint2 wr[4];
                #pragma unroll
                for (int q = 0; q < 4; q++) wr[q] = ldg64(p.wr + (lane + 32 * q + 128 * i) * 4);
                poll_words<4>(w, p.s->rest + 512 + i * 128 + lane, 32, tag);
                #pragma unroll
                for (int q = 0; q < 4; q++) { const uint32_t r0 = hmul2(w[q].x, wr[q].x), r1 = hmul2(w[q].y, wr[q].y); s += (bf_lo(r0) + bf_hi(r0)) + (bf_lo(r1) + bf_hi(r1)); }
            }
            __syncwarp();
            #pragma unroll
            for (int m = 16; m >= 1; m >>= 1) s += shfl_x(s, m);
            if (lane == 0) { stsf(sb + OFF_ATOT, s); sts128(sb + OFF_BQ + 272, make_uint4(ONE2, ONE2, ONE2, ONE2)); }
            __syncwarp();
            arrive_one(BAR(B_PAR));
        }
        __syncwarp();
        {
            mbar_wait(BAR(B_PAR), 0);
            const uint4 pa = lds128(sb + OFF_PAR + (lane & 15) * 16), ps = lds128(sb + OFF_PAR + 256 + (lane & 15) * 16);
            const uint4 wr = ldg128(p.wr + hg * 128 + (lane & 15) * 8);
            const float atot = ldsf(sb + OFF_ATOT);
            mbar_wait(BAR(XGATE), 0);
            if (w4 == 0) TS(37);
            uint4 w;
            #pragma unroll 1
            for (int it = 0; it < POLL_MAX; it++) {
                w = ld_ll(p.s->st2 + rb * 128 + t);
                if (__all_sync(0xffffffffu, __uint_as_float(w.w) == 8.0f)) break;
            }
            if (w4 == 0) TS(31);
            uint32_t m2; float rinv;
            ln_final(__uint_as_float(w.x), __uint_as_float(w.y), m2, rinv);
            uint32_t k[1] = {(f2key(fmaf(-bf_lo(m2), atot, __uint_as_float(w.z)) * rinv) & ~0xfffu) | ((2047 - rb * 128 - t) << 1)};
            const uint32_t best0 = pop_max(k), best1 = pop_max(k) | 1u, grp = rb * 4 + w4;
            if (hg == 0 && lane < 2) st_ll(p.s->cand + grp * 2 + lane, best0, best1, 0, tag);
            if (w4 == 3) TS(23);
            const uint32_t row = 127 - (((lane < 16 ? best0 : best1) >> 1) & 127u);
            mbar_wait(BAR(B_X2), 0);
            const uint4 xv = lds128(sb + OFF_OUT + (row >> 3) * 2048u + ((lane >> 3) & 1) * 1024u + (row & 7) * 128u + (((lane ^ row) & 7) << 4));
            sts64(sb + OFF_ST2 + t * 8, m2, __float_as_uint(rinv));
            __syncwarp();
            arrive_one(BAR(B_ST2));
            const uint32_t rm = __shfl_sync(0xffffffffu, m2, row & 31);
            const Recip rr = split_recip(__shfl_sync(0xffffffffu, rinv, row & 31));
            const uint32_t h0 = ln_pair(xv.x, rm, rr, pa.x, ps.x), h1 = ln_pair(xv.y, rm, rr, pa.y, ps.y);
            const uint32_t h2 = ln_pair(xv.z, rm, rr, pa.z, ps.z), h3 = ln_pair(xv.w, rm, rr, pa.w, ps.w);
            uint4* d = p.s->rowh + (grp * 2 + (lane >> 4)) * 128 + hg * 16 + (lane & 15);
            st_ll(d, h0, h1, h2, h3);
            st_ll(d + 16384, xv.x, xv.y, xv.z, xv.w);
            float r = (fmaf(bf_lo(h0), bf_lo(wr.x), bf_hi(h0) * bf_hi(wr.x)) + fmaf(bf_lo(h1), bf_lo(wr.y), bf_hi(h1) * bf_hi(wr.y)))
                    + (fmaf(bf_lo(h2), bf_lo(wr.z), bf_hi(h2) * bf_hi(wr.z)) + fmaf(bf_lo(h3), bf_lo(wr.w), bf_hi(h3) * bf_hi(wr.w)));
            #pragma unroll
            for (int m = 8; m >= 1; m >>= 1) r += shfl_x(r, m);
            if (!(lane & 15)) st_ll(p.s->rsc + (grp * 8 + hg) * 2 + (lane >> 4), __float_as_uint(r), 0, 0, tag);
            if (w4 == 3) TS(24);
        }
        if (w4 == 0) {
            uint4 cv[2];
            poll_words<2>(cv, p.s->cand + lane * 2, 64, tag);
            __syncwarp();
            TS(11);
            const uint32_t ka = min(cv[0].x, cv[1].x), kb = max(cv[0].y, cv[1].y);
            uint32_t k0 = max(cv[0].x, cv[1].x), k1 = max(ka, kb), k2 = min(ka, kb), k3 = min(cv[0].y, cv[1].y), id[4];
            uint4 hv[4][2], sc;
            const uint4* ha[4];
            #pragma unroll
            for (int i = 0; i < 4; i++) {
                const uint32_t m = __reduce_max_sync(0xffffffffu, k0);
                if (k0 == m) { k0 = k1; k1 = k2; k2 = k3; }
                id[i] = (m & 0xfffu) ^ 0xffeu;
                ha[i] = p.s->rowh + ((id[i] >> 6) * 2 + (id[i] & 1)) * 128 + rank * 64 + lane;
                hv[i][0] = ld_ll(ha[i]); hv[i][1] = ld_ll(ha[i] + 32);
            }
            const uint32_t myid = lane < 16 ? (lane < 8 ? id[0] : id[1]) : (lane < 24 ? id[2] : id[3]), row = myid >> 1;
            const uint4* sa = p.s->rsc + ((myid >> 6) * 8 + (lane & 7)) * 2 + (myid & 1);
            sc = ld_ll(sa);
            sts32(sb + OFF_SEL + 32 + (lane >> 3) * 4, row);
            __syncwarp();
            arrive_one(BAR(B_CAND));
            #pragma unroll 1
            for (int it = 0; it < POLL_MAX; it++) {
                uint32_t m = 0;
                #pragma unroll
                for (int i = 0; i < 4; i++) m = max(m, max(hv[i][0].x, hv[i][1].x));
                if (__all_sync(0xffffffffu, m != EMPTY && sc.w == tag)) break;
                #pragma unroll
                for (int i = 0; i < 4; i++) { hv[i][0] = ld_ll(ha[i]); hv[i][1] = ld_ll(ha[i] + 32); }
                sc = ld_ll(sa);
            }
            TS(12);
            #pragma unroll
            for (int i = 0; i < 4; i++) { sts128(sb + OFF_ROWS + i * 1056u + lane * 16u, hv[i][0]); sts128(sb + OFF_ROWS + i * 1056u + 528u + lane * 16u, hv[i][1]); }
            __syncwarp();
            arrive_one(BAR(B_ROWS));
            TS(25);
            float r = __uint_as_float(sc.x);
            r += shfl_x(r, 1); r += shfl_x(r, 2); r += shfl_x(r, 4);
            r = rbf(r);
            const uint32_t key = (f2key(r) & 0xffff0000u) | (0xffffu - row);
            uint32_t kq[1] = {key};
            const uint32_t best0 = pop_max(kq), best1 = pop_max(kq), tok = key == best0 ? 0 : key == best1 ? 1 : 2;
            sts32(sb + OFF_SEL + 48 + (lane >> 3) * 4, tok);
            if (tok < 2) sts128(sb + OFF_SEL + tok * 16, make_uint4(row, (myid >> 6) * 2 + (myid & 1), __float_as_uint(r), 0));
            __syncwarp();
            arrive_one(BAR(B_SEL));
        } else if (w4 == 1) {
            mbar_wait(BAR(B_SEL), 0);
            const uint4 sel = lds128(sb + OFF_SEL + rank * 16);
            const int col = pr * 16 + c * 2 + (lane >> 4) + (lane & 8);
            uint32_t xs, hs; uint4 gw;
            #pragma unroll 1
            for (int it = 0; it < POLL_MAX; it++) {
                const char* a = (const char*)(p.s->rowh + sel.y * 128) + (col >> 1) * 4;
                hs = ld_rlx(a); xs = ld_rlx(a + 262144); gw = ld_ll(p.s->rest + 768 + (col >> 2));
                if (__all_sync(0xffffffffu, hs != EMPTY && xs != EMPTY && gw.w == tag)) break;
            }
            const uint32_t gq = (col & 2) ? gw.y : gw.x;
            const float fx = (col & 1) ? bf_hi(xs) : bf_lo(xs), fh = (col & 1) ? bf_hi(hs) : bf_lo(hs), fg = (col & 1) ? bf_hi(gq) : bf_lo(gq);
            const float sg = rbf(sigmoidf(__uint_as_float(sel.z)));
            const uint4* src = p.s->yp + g * 512 + rank * 256 + pr * 4 + c;
            uint4 w[7];
            #pragma unroll
            for (int i = 0; i < 7; i++) w[i] = make_uint4(0, EMPTY, 0, EMPTY);
            if (ffn) mbar_wait(BAR(YGATE), 0);
            if (YDLY) { const uint32_t c0 = clk32(); while (clk32() - c0 < (ffn ? YDLY : YDLY + 1500)) {} }
            #pragma unroll 1
            for (int it = 0; it < POLL_MAX; it++) {
                bool ok = true;
                #pragma unroll
                for (int i = 0; i < 7; i++) ld_ll_if(w[i], src + i * 4096, !(tagged2(w[i].y, tag2) && tagged2(w[i].w, tag2)));
                #pragma unroll
                for (int i = 0; i < 7; i++) ok = ok && tagged2(w[i].y, tag2) && tagged2(w[i].w, tag2);
                if (__all_sync(0xffffffffu, ok)) break;
            }
            TS(29);
            float y0 = 0.f, y1 = 0.f, y2 = 0.f, y3 = 0.f;
            #pragma unroll
            for (int i = 0; i < 7; i++) { y0 += __uint_as_float(w[i].x); y1 += __uint_as_float(w[i].y); y2 += __uint_as_float(w[i].z); y3 += __uint_as_float(w[i].w); }
            const bool b4 = lane & 16, b3 = lane & 8;
            const float a0 = (b4 ? y2 : y0) + shfl_x(b4 ? y0 : y2, 16), a1 = (b4 ? y3 : y1) + shfl_x(b4 ? y1 : y3, 16);
            float y = (b3 ? a1 : a0) + shfl_x(b3 ? a0 : a1, 8);
            y += shfl_x(y, 4);
            const float upd = rbf(rbf(y) * sg);
            if (!(lane & 4)) p.out[(size_t)sel.x * 1024 + col] = __float2bfloat16(fx + rbf(fg * rbf(fh + upd)));
            if (b == 0 && lane == 0) p.s->done[0] = tag;
            TS(28);
            if (!GS2) GS(6);
        } else if (w4 == 2) {
            mbar_wait(BAR(OUTGATE), 0);
            const uint32_t cg = (lds32(sb + OFF_SEL + 32 + c * 4) >> 3) - rb * 16;
            uint32_t late = __reduce_or_sync(0xffffffffu, cg < 16 ? 1u << cg : 0u);
            mbar_wait(BAR(B_OUTW), 0);
            fence_async_smem();
            #pragma unroll 1
            for (uint32_t i = 0; i < 16; i++)
                if (!((late >> i) & 1))
                    asm volatile(EL "cp.async.bulk.tensor.3d.global.shared::cta.bulk_group [%0, {0, %2, %3}], [%1];\n}"
                        :: "l"(&tmO), "r"(sb + OFF_OUT + i * 2048u), "r"(rb * 128 + i * 8), "r"(hg * 2) : "memory");
            bulk_commit();
            mbar_wait(BAR(B_SEL), 0);
            const uint32_t row0 = lds32(sb + OFF_SEL) - rb * 128, row1 = lds32(sb + OFF_SEL + 16) - rb * 128;
            #pragma unroll 1
            for (; late; late &= late - 1) {
                const uint32_t i = __ffs(late) - 1;
                #pragma unroll 1
                for (uint32_t q = 0; q < 4; q++) {
                    const uint32_t r = q * 2 + (lane >> 4), ch = lane & 15;
                    const uint4 v = lds128(sb + OFF_OUT + i * 2048u + (ch >> 3) * 1024u + r * 128u + (((ch ^ r) & 7) << 4));
                    if (i * 8 + r != row0 && i * 8 + r != row1) stg128(p.out + (size_t)(rb * 128 + i * 8 + r) * 1024 + hg * 128 + ch * 8, v);
                }
            }
            bulk_wait();
            TS(35);
        }
    } else {
        const int w4 = warp & 3, wgi = warp >> 2;
        uint32_t m2[2]; float rinv[2];
        uint32_t tag2;
        {
            const int g = lane >> 2, c = lane & 3, xrow = b * 16 + warp * 2;
            if (b < NW0)
                asm volatile("prefetch.global.L2 [%0];" :: "l"(p.wmod + (size_t)((b & 3) * 256 + tid) * 6144 + (((b >> 2) & 1) ? 0 : 1024) + (b >> 3) * 64));
            const uint2 cv = ldg64(p.c + tid * 4);
            const uint32_t tag = ld_rlx(p.s->done) + 1;
            if (lane < 2) stg_fill(p.s->st1 + xrow + lane, 0);
            if (warp == 0 && lane < 16 && b < 32 * NC) stg_fill(p.s->mp + b * 16 + lane, EMPTY);
            if (tid < 64) { int s = tid >> 2; sts128(sb + OFF_ONES + tid * 16, make_uint4(((tid & 3) == ((s >> 1) & 3)) ? 0x3F80u : 0u, 0, 0, 0)); }
            cluster_arrive();
            reg_inc<CG1>();
            {
                const float c0 = bf_lo(cv.x), c1 = bf_hi(cv.x), c2 = bf_lo(cv.y), c3 = bf_hi(cv.y);
                sts64(sb + OFF_SILU + tid * 8, pack2(c0 * sigmoidf(c0), c1 * sigmoidf(c1)), pack2(c2 * sigmoidf(c2), c3 * sigmoidf(c3)));
            }
            tag2 = tag % 3u;
            bar_sync(0, 384);
            bar_arrive(3, 320);
            if (warp == 0) TS(47);
            if (!GS2 && warp == 1) GS(0);
            #pragma unroll 1
            for (int part = 0; part < 2; part++)
            if (part == (b < NW0)) {
                mbar_wait(BAR(B_XS + (warp >> 1)), 0);
                if (warp == 7) TS(60);
                if (warp == 0) TS(54);
                float sd[2][4], q1[2][4], q2[2][4];
                #pragma unroll
                for (int e = 0; e < 4; e++) { sd[0][e] = sd[1][e] = q1[0][e] = q1[1][e] = q2[0][e] = q2[1][e] = 0.f; }
                #pragma unroll
                for (int i = 0; i < 4; i++) {
                    const uint4 u = lds128(sb + OFF_XS + warp * 4096u + (i * 32 + lane) * 16u), v = lds128(sb + OFF_XS + warp * 4096u + 2048u + (i * 32 + lane) * 16u);
                    mma16816(sd[0], u.x, v.x, u.y, v.y, ONE2, ONE2); mma16816(sd[1], u.z, v.z, u.w, v.w, ONE2, ONE2);
                    mma16816(q1[0], u.x, v.x, u.y, v.y, u.x, u.y); mma16816(q1[1], u.z, v.z, u.w, v.w, u.z, u.w);
                    mma16816(q2[0], u.x, v.x, u.y, v.y, v.x, v.y); mma16816(q2[1], u.z, v.z, u.w, v.w, v.z, v.w);
                }
                if (warp == 0) TS(30);
                const float d0 = __shfl_sync(0xffffffffu, (g & 1) ? q1[0][1] + q1[1][1] : q1[0][0] + q1[1][0], g * 4 + (g >> 1));
                const float d1 = __shfl_sync(0xffffffffu, (g & 1) ? q2[0][3] + q2[1][3] : q2[0][2] + q2[1][2], g * 4 + (g >> 1));
                float sk = (c & 1) ? sd[0][2] + sd[1][2] : sd[0][0] + sd[1][0], qk = (c & 1) ? d1 : d0;
                #pragma unroll
                for (int m = 4; m <= 16; m <<= 1) { sk += shfl_x(sk, m); qk += shfl_x(qk, m); }
                uint32_t mm; float ri;
                ln_final(sk, qk, mm, ri);
                if (lane < 2) st_ll(p.s->st1 + xrow + lane, mm, __float_as_uint(ri), 0, tag);
                if (warp == 0) TS(14);
                if (warp == 7) TS(61);
            } else if (b < 32 * NC) {
                float m[4][4];
                uint32_t sv[4];
                ldsm4(sv[0], sv[1], sv[2], sv[3], sb + OFF_SILU + ((b & 3) * 256 + warp * 32) * 2 + (lane >> 3) * 16);
                mbar_wait(BAR(B_WS + (warp >> 1)), 0);
                if (warp == 7) TS(55);
                #pragma unroll
                for (int tt = 0; tt < 4; tt++) {
                    m[tt][0] = m[tt][1] = m[tt][2] = m[tt][3] = 0.f;
                    #pragma unroll
                    for (int e = 0; e < 2; e++) {
                        uint32_t a0, a1, a2, a3;
                        ldsm4t(a0, a1, a2, a3, sb + OFF_WST + warp * 4096u + (e * 16 + (lane & 7) + ((lane >> 4) << 3)) * 128u + (((2 * tt + ((lane >> 3) & 1)) ^ (lane & 7)) << 4));
                        mma16816(m[tt], a0, a1, a2, a3, sv[2 * e], sv[2 * e + 1]);
                    }
                }
                if (warp == 0) TS(46);
                const uint32_t ra = sb + OFF_RED0 + warp * 256 + mod_pos(c, g);
                stsf(ra, (c & 2) ? ((c & 1) ? m[3][0] : m[2][0]) : ((c & 1) ? m[1][0] : m[0][0]));
                stsf(ra + 8, (c & 2) ? ((c & 1) ? m[3][2] : m[2][2]) : ((c & 1) ? m[1][2] : m[0][2]));
                if (warp != 7) bar_arrive(5, 256);
                else {
                    bar_sync(5, 256);
                    float v0 = 0.f, v1 = 0.f, v2 = 0.f, v3 = 0.f;
                    #pragma unroll
                    for (int w = 0; w < 4; w++) {
                        const uint4 u = lds128(sb + OFF_RED0 + w * 512 + lane * 16);
                        v0 += __uint_as_float(u.x); v1 += __uint_as_float(u.y); v2 += __uint_as_float(u.z); v3 += __uint_as_float(u.w);
                    }
                    v0 += shfl_x(v0, 16); v1 += shfl_x(v1, 16); v2 += shfl_x(v2, 16); v3 += shfl_x(v3, 16);
                    if (lane < 16) st_ll(p.s->mp + b * 16 + lane, __float_as_uint(v0), __float_as_uint(v1), __float_as_uint(v2), low_bits(v3, tag2));
                    TS(45);
                }
            }
            if (!LATEFREE) arrive_one(BAR(B_STFREE));
            cluster_wait();
            uint4 st[2];
            poll_words<2>(st, p.s->st1 + rb * 128 + warp * 16 + g, 8, tag);
            __syncwarp();
            m2[0] = st[0].x; rinv[0] = __uint_as_float(st[0].y); m2[1] = st[1].x; rinv[1] = __uint_as_float(st[1].y);
            if (LATEFREE) arrive_one(BAR(B_STFREE));
            if (warp == 0) TS(4);
        }
        const int lane = lane_id(), g = lane >> 2, c = lane & 3;
        const int srow = warp * 16 + (lane & 15);
        const uint32_t aoff = srow * 128u + ((((lane >> 4) ^ srow) & 7) << 4);
        uint32_t pt[16], qf[32];
        float pp[2][16];
        const uint32_t roff = srow * 128u + ((lane & 7) << 4);
        {
            float accKV[128], accQ[64];
            {
                uint32_t f[2][4], r[4];
                const Recip ri0 = split_recip(rinv[0]), ri1 = split_recip(rinv[1]);
                mbar_wait(BAR(B_F1), 0);
                if (warp == 0) TS(63);
                ldsm4(r[0], r[1], r[2], r[3], sb + OFF_RING + aoff);
                mbar_wait(BAR(B_MOD), 0);
                if (warp == 0) TS(15);
                if (!GS2 && warp == 1) GS(1);
                uint4 md = lds128(sb + OFF_MODS + c * 16);
                int s = 0, sp = 2, par = 0;
                #pragma unroll 1
                for (int j = 0; j < 16; j++) {
                    const int sn = s == 2 ? 0 : s + 1;
                    par ^= s == 2;
                    const uint64_t db = mk_desc(sb + OFF_RING + s * 65536u + 16384u, 8192, 1024, 1);
                    #pragma unroll
                    for (int ks = 0; ks < 4; ks++) {
                        uint32_t (&ff)[4] = f[ks & 1];
                        ff[0] = ln_pair(r[0], m2[0], ri0, md.x, md.z); ff[1] = ln_pair(r[1], m2[1], ri1, md.x, md.z);
                        ff[2] = ln_pair(r[2], m2[0], ri0, md.y, md.w); ff[3] = ln_pair(r[3], m2[1], ri1, md.y, md.w);
                        const int kn = (ks + 1) & 3;
                        ldsm4(r[0], r[1], r[2], r[3], sb + OFF_RING + (ks == 3 ? sn : s) * 65536u + (aoff ^ (kn << 5)));
                        md = lds128(sb + OFF_MODS + ((ks == 3 ? j + 1 : j) * 4 + kn) * 64 + c * 16);
                        wg_fence();
                        wgmma_n256_rs<1>(accKV, ff[0], ff[1], ff[2], ff[3], desc_add(db, 16384 + ks * 2048), ks ? 1 : j);
                        wgmma_n128_rs<1>(accQ, ff[0], ff[1], ff[2], ff[3], desc_add(db, ks * 2048), ks ? 1 : j);
                        wg_commit();
                        if (ks == 1) mbar_wait(BAR(B_MOD + ((j + 1) & 15)), 0);
                        if (ks == 2) { WT0(); mbar_wait(BAR(j < 15 ? B_F1 + sn : B_WPHI), j < 15 ? par : 0);
                        }
                        wg_wait<1>();
                        if (ks == 0) { if (MCW) arrive_both_if(BAR(B_E1 + sp), j); else arrive_if(BAR(B_E1 + sp), j); }
                    }
                    sp = s; s = sn;
                }
            }
            mbar_wait(BAR(B_E1 + 2), 0);
            wg_wait<0>();
            acc_fence(accKV); acc_fence(accQ);
            if (MCW) arrive_both_if(BAR(B_E1), 1); else arrive_one(BAR(B_E1));
            if (warp == 0) TS(16);
            if (!GS2 && warp == 1) GS(2);
            uint32_t kf[32];
            #pragma unroll
            for (int h = 0; h < 4; h++) {
                if (h == VFIRST) {
                    #pragma unroll
                    for (int i = 0; i < 16; i++) kf[i] = pack2(accKV[2 * i], accKV[2 * i + 1]);
                    phi_issue(pp, kf, sb, 0);
                }
                #pragma unroll
                for (int q = 0; q < 2; q++) {
                    const int o = 64 + 16 * h + 8 * q;
                    stsm4(sb + OFF_V + h * 8192u + srow * 64u + (((2 * q + (lane >> 4)) ^ ((srow >> 1) & 3)) << 4),
                          pack2(accKV[o], accKV[o + 1]), pack2(accKV[o + 2], accKV[o + 3]), pack2(accKV[o + 4], accKV[o + 5]), pack2(accKV[o + 6], accKV[o + 7]));
                }
            }
            #pragma unroll
            for (int i = 16; i < 32; i++) kf[i] = pack2(accKV[2 * i], accKV[2 * i + 1]);
            phi_transpose(pp, pt, sb + OFF_PHI0 + aoff, sb + OFF_PHI0 + (roff ^ ((lane >> 4) << 6)));
            phi_issue(pp, kf + 16, sb, 1);
            #pragma unroll
            for (int i = 0; i < 32; i++) qf[i] = pack2(accQ[2 * i], accQ[2 * i + 1]);
            if (PREWAIT) { wg_wait<0>(); acc_fence(pp[0]); acc_fence(pp[1]); }
        }
        reg_dec<CREG>();
        if (warp == 0) TS(56);
        {
            float cp, cn;
            fm_extrema(pt, cp, cn);
            if (STAG && wgi) { const uint32_t c0 = clk32(); while (clk32() - c0 < STAG) {} }
            #pragma unroll 1
            for (int u = 0; u < 4; u++) {
                const uint32_t cur = sb + ((u & 1) ? OFF_PHI1 : OFF_PHI0);
                float e[64], s[4];
                uint32_t pn[16];
                #pragma unroll
                for (int k = 0; k < 16; k++) {
                    if (k == KW) phi_transpose(pp, pn, cur + aoff, cur + (roff ^ ((lane >> 4) << 6)));
                    const float dep = k >= DEP ? e[33 + 2 * (k >= DEP ? k - DEP : 0)] : 0.f, f0 = bf_lo_after(pt[k], dep), f1 = bf_hi_after(pt[k], dep);
                    e[2 * k] = ex2(fmaf(f0, LOG2E, cp)); e[2 * k + 1] = ex2(fmaf(f1, LOG2E, cp));
                    e[32 + 2 * k] = ex2(fmaf(f0, -LOG2E, cn)); e[33 + 2 * k] = ex2(fmaf(f1, -LOG2E, cn));
                    if (k == 0) { s[0] = e[0]; s[1] = e[1]; s[2] = e[32]; s[3] = e[33]; }
                    else { s[0] += e[2 * k]; s[1] += e[2 * k + 1]; s[2] += e[32 + 2 * k]; s[3] += e[33 + 2 * k]; }
                }
                fm_extrema(pn, cp, cn);
                #pragma unroll
                for (int i = 0; i < 16; i++) pt[i] = pn[i];
                const float sp = s[0] + s[1], sn = s[2] + s[3], r = rcp(sp * sn), rp = r * sn, rn = r * sp;
                #pragma unroll
                for (int i = 0; i < 8; i++) {
                    const float q = i < 4 ? rp : rn;
                    sts128((cur + (lane >> 4) * 16384u + roff) ^ (i << 4), make_uint4(pack2(e[8 * i] * q, e[8 * i + 1] * q), pack2(e[8 * i + 2] * q, e[8 * i + 3] * q),
                                                                                   pack2(e[8 * i + 4] * q, e[8 * i + 5] * q), pack2(e[8 * i + 6] * q, e[8 * i + 7] * q)));
                }
                __syncwarp();
                arrive_one(BAR(B_PHI + u));
                if (u == 0) phi_issue(pp, qf, sb, 0);
                else {
                    mbar_wait(BAR(B_KVD + (u != 1)), 0);
                    if (u == 1) phi_issue(pp, qf + 16, sb, 1);
                }
            }
            wg_wait<0>();
        }
        if (warp == 0) TS(57);
        if (!GS2 && warp == 1) GS(3);
        uint32_t x2[16][2], wf[32][4];
        const uint32_t woff = ((lane >> 3) & 1) * 16384u + ((lane & 7) + ((lane >> 4) << 3)) * 128u + (((warp ^ lane) & 7) << 4);
        mbar_wait(BAR(B_S0), 0);
        #pragma unroll
        for (int q = 0; q < 8; q++) {
            ldsm4(x2[2 * q][0], x2[2 * q][1], x2[2 * q + 1][0], x2[2 * q + 1][1], sb + OFF_XT + (q >> 2) * 16384u + (aoff ^ ((q & 3) << 5)));
            ldsm4t(wf[q][0], wf[q][1], wf[q][2], wf[q][3], sb + OFF_GA + q * 2048u + woff);
        }
        __syncwarp();
        arrive_one(BAR(B_S0FREE));
        #pragma unroll 1
        for (int pp = 0; pp < 2; pp++) {
            float o0[20], o1[20];
            const uint64_t dk = mk_desc(sb + OFF_SP + pp * 8192u, OFF_Z - OFF_SP - pp * 8160u, 512, 2);
            const uint64_t dq = mk_desc(sb + (pp ? OFF_PHI1 : OFF_PHI0) + wgi * 8192u, 16, 1024, 1);
            mbar_wait(BAR(B_PHI + 2 + pp), 0);
            mbar_wait(BAR(B_KVF + pp), 0);
            fence_async_smem();
            wg_fence();
            #pragma unroll
            for (int ks = 0; ks < 4; ks++) {
                wgmma_n40_ss<0, 1>(o0, desc_add(dq, ks * 32), desc_add(dk, ks * 1024), ks);
                wgmma_n40_ss<0, 1>(o1, desc_add(dq, 16384 + ks * 32), desc_raw(dk, 256 + ks * 64 - (255 << 16)), ks);
            }
            wg_commit();
            wg_wait<0>();
            acc_fence(o0); acc_fence(o1);
            #pragma unroll
            for (int hh = 0; hh < 2; hh++) {
                const float (&o)[20] = hh ? o1 : o0;
                const Recip rd0 = split_recip(rcp(rbf(rbf(o[16]) + 1e-6f)));
                const Recip rd1 = split_recip(rcp(rbf(rbf(o[18]) + 1e-6f)));
                uint32_t op[8];
                #pragma unroll
                for (int j = 0; j < 4; j++) { op[2 * j] = hdiv2(pack2(o[4 * j], o[4 * j + 1]), rd0); op[2 * j + 1] = hdiv2(pack2(o[4 * j + 2], o[4 * j + 3]), rd1); }
                #pragma unroll
                for (int q = 0; q < 2; q++) stsm4(sb + OFF_OWN + pp * 16384u + (aoff ^ ((2 * hh + q) << 5)), op[4 * q], op[4 * q + 1], op[4 * q + 2], op[4 * q + 3]);
            }
            __syncwarp();
            arrive_one(BAR(B_OWN + pp));
            if (warp == 0) TS(20 + pp);
        }
        const uint32_t ooff = sb + OFF_OUT + (srow >> 3) * 1024u + aoff;
        {
            float acc[64];
            const uint32_t vchk = lane * 32u + g * 4u;
            if (!GS2 && warp == 1) GS(4);
            mbar_wait(BAR(B_OWN + 1), 0);
            fence_async_smem();
            const uint64_t da0 = mk_desc(sb + OFF_DA + wgi * 8192u, 16, 1024, 1), db0 = mk_desc(sb + OFF_DB, 8192, 1024, 1);
            #pragma unroll 1
            for (int n = 0; n < 16; n++) {
                const uint32_t s = (SLOT_A >> (4 * n)) & 7, sB = (SLOT_B >> (4 * n)) & 7;
                WT0();
                mbar_wait(BAR(B_FB + sB), (PAR_B >> n) & 1);
                WTJ(16 + n);
                mbar_wait(BAR(n < 2 ? B_OWN + n : B_FA + s), (PAR_A >> n) & 1);
                WTJ(n);
                {
                    const uint32_t ra = sb + OFF_DA + s * 16384u + warp * 2048u;
                    if (__any_sync(0xffffffffu, max(lds32(ra + vchk), lds32(ra + vchk + 1024)) == EMPTY)) {
                        #pragma unroll 1
                        for (int i = 0; i < 4; i++) {
                            uint4 v;
                            #pragma unroll 1
                            for (int it = 0; it < POLL_MAX; it++) {
                                v = ld_ll(p.s->os + (rb * 16 + d_block(hg, n)) * 1024 + warp * 128 + i * 32 + lane);
                                if (umax4(v) != EMPTY) break;
                            }
                            sts128(ra + i * 512 + lane * 16, v);
                        }
                        fence_async_smem();
                        __syncwarp();
                    }
                }
                TR(32 + 16 * wgi + n);
                const uint64_t da = desc_add(da0, s * 16384u), db = desc_add(db0, sB * 16384u);
                wg_fence();
                #pragma unroll
                for (int ks = 0; ks < 4; ks++) wgmma_n128_ss<0, 1>(acc, desc_add(da, ks * 32), desc_add(db, ks * 2048), ks ? 1 : n);
                wg_commit();
                wg_wait<1>();
                if (MCB) arrive_both_if(BAR(B_ED - 1 + n), n); else arrive_if(BAR(B_ED - 1 + n), n);
            }
            mbar_wait(BAR(B_PAR), 0);
            uint32_t gar[16], bfr[16];
            #pragma unroll
            for (int j = 0; j < 16; j += 4) {
                ldsm4(gar[j], gar[j + 1], gar[j + 2], gar[j + 3], sb + OFF_PAR + 768 + (j + (lane >> 3)) * 16);
                ldsm4(bfr[j], bfr[j + 1], bfr[j + 2], bfr[j + 3], sb + OFF_BQ + ((lane & 1) ? (j + (lane >> 3)) * 16 : 272));
            }
            wg_wait<0>();
            acc_fence(acc);
            bar_arrive(6 + wgi, 256);
            if (warp == 0) TS(9);
            if (!GS2 && warp == 1) GS(5);
            float sd[2][4], q1[2][4], q2[2][4];
            #pragma unroll
            for (int e = 0; e < 4; e++) { sd[0][e] = sd[1][e] = q1[0][e] = q1[1][e] = q2[0][e] = q2[1][e] = 0.f; }
            #pragma unroll
            for (int s = 0; s < 8; s++) {
                #pragma unroll
                for (int e = 0; e < 4; e++) { const int j = 2 * s + (e >> 1), h = e & 1; x2[j][h] = hadd2(x2[j][h], hmul2(gar[j], pack2(acc[4 * j + 2 * h], acc[4 * j + 2 * h + 1]))); }
                mma16816(sd[s & 1], x2[2 * s][0], x2[2 * s][1], x2[2 * s + 1][0], x2[2 * s + 1][1], bfr[2 * s], bfr[2 * s + 1]);
                #pragma unroll
                for (int e = 0; e < 2; e++) { mma1688(q1[e], x2[2 * s + e][0], x2[2 * s + e][1], x2[2 * s + e][0]); mma1688(q2[e], x2[2 * s + e][0], x2[2 * s + e][1], x2[2 * s + e][1]); }
            }
            if (c == (g >> 1)) {
                uint4* d = p.s->st2 + rb * 128 + warp * 16 + g;
                red_add4(d, sd[0][0] + sd[1][0], (g & 1) ? q1[0][1] + q1[1][1] : q1[0][0] + q1[1][0], sd[0][1] + sd[1][1], 1.0f);
                red_add4(d + 8, sd[0][2] + sd[1][2], (g & 1) ? q2[0][3] + q2[1][3] : q2[0][2] + q2[1][2], sd[0][3] + sd[1][3], 1.0f);
            }
            arrive_one(BAR(B_RED));
            if (warp == 0) TS(22);
            bar_sync(7 - wgi, 256);
            #pragma unroll
            for (int q = 0; q < 8; q++) stsm4((ooff + (q >> 2) * 1024u) ^ ((q & 3) << 5), x2[2 * q][0], x2[2 * q][1], x2[2 * q + 1][0], x2[2 * q + 1][1]);
            __syncwarp();
            arrive_one(BAR(B_X2));
            if (warp == 0) TS(62);
        }
        const uint32_t xa = sb + OFF_OUT + warp * 4096u + ((lane >> 3) & 1) * 1024u + (lane >> 4) * 128u + (((lane ^ (lane >> 4)) & 7) << 4);
        const uint4 pa = lds128(sb + OFF_PAR + (lane & 15) * 16), ps = lds128(sb + OFF_PAR + 256 + (lane & 15) * 16), pg = lds128(sb + OFF_PAR + 512 + (lane & 15) * 16);
        if (ffn) mbar_wait(BAR(B_GU), 0);
        if (warp == 0) TS(38);
        #pragma unroll
        for (int q = 8; q < NEARLY; q++) {
            ldsm4t(wf[q][0], wf[q][1], wf[q][2], wf[q][3], sb + (q < 16 ? OFF_GB : q < 24 ? OFF_UP0 : OFF_UP1) + (q & 7) * 2048u + woff);
            if (LPACE && (q & 1)) { const uint32_t c0 = clk32(); while (clk32() - c0 < LPACE) {} }
        }
        {
            if (warp == 0) TS(39);
            mbar_wait(BAR(B_ST2), 0);
            if (warp == 0) TS(53);
            #pragma unroll 1
            for (int q0 = 0; q0 < 8; q0 += OUU) {
                uint4 x[OUU]; uint2 st[OUU];
                const uint32_t a = (xa + (q0 >> 2) * 2048u + (q0 & 3) * 256u) ^ ((q0 & 3) << 5);
                #pragma unroll
                for (int q = 0; q < OUU; q++) { x[q] = lds128((a + q * 256u) ^ (q << 5)); st[q] = lds64(sb + OFF_ST2 + (warp * 16 + (q0 + q) * 2 + (lane >> 4)) * 8); }
                #pragma unroll
                for (int q = 0; q < OUU; q++) {
                    const Recip r = split_recip(__uint_as_float(st[q].y));
                    sts128((a + q * 256u) ^ (q << 5), make_uint4(
                        hadd2(x[q].x, hmul2(pg.x, ln_pair(x[q].x, st[q].x, r, pa.x, ps.x))), hadd2(x[q].y, hmul2(pg.y, ln_pair(x[q].y, st[q].x, r, pa.y, ps.y))),
                        hadd2(x[q].z, hmul2(pg.z, ln_pair(x[q].z, st[q].x, r, pa.z, ps.z))), hadd2(x[q].w, hmul2(pg.w, ln_pair(x[q].w, st[q].x, r, pa.w, ps.w)))));
                }
            }
            __syncwarp();
            arrive_one(BAR(B_OUTW));
            if (warp == 0) TS(32);
        }
        if (ffn) {
            float acc[4][4];
            uint32_t df[4][4][4];
            {
                #pragma unroll
                for (int i = 0; i < 4; i++) { acc[i][0] = acc[i][1] = acc[i][2] = acc[i][3] = 0.f; }
                const uint32_t da = sb + (wgi ? OFF_DN1 : OFF_DN0) + w4 * 8192u + ((lane & 7) + ((lane >> 4) << 3)) * 128u;
                #pragma unroll
                for (int q = NEARLY; q < 32; q++) ldsm4t(wf[q][0], wf[q][1], wf[q][2], wf[q][3], sb + (q < 16 ? OFF_GB : q < 24 ? OFF_UP0 : OFF_UP1) + (q & 7) * 2048u + woff);
                mbar_wait(BAR(B_WD), 0);
                #pragma unroll
                for (int q = 0; q < DNE; q++)
                    ldsm4t(df[q >> 2][q & 3][0], df[q >> 2][q & 3][1], df[q >> 2][q & 3][2], df[q >> 2][q & 3][3], da + (q & 3) * 2048u + (((2 * (q >> 2) + ((lane >> 3) & 1)) ^ (lane & 7)) << 4));
                mbar_wait(BAR(B_ROWS), 0);
                #pragma unroll
                for (int q = 0; q < 8; q++) {
                    uint32_t b0, b1, b2, b3;
                    ldsm4(b0, b1, b2, b3, sb + OFF_ROWS + (lane & 7) * 528u + (lane >> 3) * 16u + q * 64u);
                    #pragma unroll
                    for (int hf = 0; hf < 2; hf++) {
                        const int k = 16 * hf + 2 * q;
                        mma16816(acc[2 * hf], wf[k][0], wf[k][1], wf[k][2], wf[k][3], b0, b1);
                        mma16816(acc[2 * hf + 1], wf[k + 1][0], wf[k + 1][1], wf[k + 1][2], wf[k + 1][3], b2, b3);
                    }
                }
                const float gs = (acc[0][0] + acc[1][0]) + (acc[2][1] + acc[3][1]), us = (acc[0][2] + acc[1][2]) + (acc[2][3] + acc[3][3]);
                st_partner64(sb + OFF_PX + warp * 256 + lane * 8, BAR(B_PX), rank ^ 1, gs, us);
                if (warp == 0) TS(34);
                #pragma unroll
                for (int q = DNE; q < 16; q++)
                    ldsm4t(df[q >> 2][q & 3][0], df[q >> 2][q & 3][1], df[q >> 2][q & 3][2], df[q >> 2][q & 3][3], da + (q & 3) * 2048u + (((2 * (q >> 2) + ((lane >> 3) & 1)) ^ (lane & 7)) << 4));
                mbar_wait(BAR(B_SEL), 0);
                const uint32_t tok = lds32(sb + OFF_SEL + 48 + c * 4);
                mbar_wait(BAR(B_PX), 0);
                const uint2 q = lds64(sb + OFF_PX + warp * 256 + lane * 8);
                float gt = rbf(gs + __uint_as_float(q.x));
                gt = rbf(gt * sigmoidf(gt));
                if (tok < 2) sts16(sb + OFF_HID + tok * 144 + (warp * 8 + g) * 2, pack2(gt * rbf(us + __uint_as_float(q.y)), 0.f));
            }
            if (warp == 0) TS(26);
            bar_sync(1, 256);
            uint32_t bh[8];
            ldsm4(bh[0], bh[1], bh[2], bh[3], sb + OFF_HID + (lane & 1) * 144u + (lane >> 3) * 16u);
            ldsm4(bh[4], bh[5], bh[6], bh[7], sb + OFF_HID + (lane & 1) * 144u + (lane >> 3) * 16u + 64u);
            float y[4][4];
            #pragma unroll
            for (int tt = 0; tt < 4; tt++) { y[tt][0] = y[tt][1] = y[tt][2] = y[tt][3] = 0.f; }
            #pragma unroll
            for (int ks = 0; ks < 4; ks++)
                #pragma unroll
                for (int tt = 0; tt < 4; tt++) mma16816(y[tt], df[tt][ks][0], df[tt][ks][1], df[tt][ks][2], df[tt][ks][3], bh[2 * ks], bh[2 * ks + 1]);
            float e[4];
            #pragma unroll
            for (int i = 0; i < 4; i++) e[i] = (c & 2) ? ((c & 1) ? y[3][i] : y[2][i]) : ((c & 1) ? y[1][i] : y[0][i]);
            char* d = (char*)(p.s->yp + pr * 512 + rank * 128 + (warp * 4 + c) * 4) + g * 8;
            st_ll8(d, __float_as_uint(e[0]), low_bits(e[2], tag2));
            st_ll8(d + 4096, __float_as_uint(e[1]), low_bits(e[3], tag2));
            arrive_one(BAR(B_YP));
            if (warp == 0) TS(27);
        }
    }
}

typedef CUresult (*EncodeFn)(CUtensorMap*, CUtensorMapDataType, cuuint32_t, void*, const cuuint64_t*, const cuuint64_t*, const cuuint32_t*,
                             const cuuint32_t*, CUtensorMapInterleave, CUtensorMapSwizzle, CUtensorMapL2promotion, CUtensorMapFloatOOBfill);

CUtensorMap make_map(EncodeFn enc, const void* ptr, uint64_t cols, uint64_t rows, uint32_t bc, uint32_t br, CUtensorMapSwizzle swz, CUtensorMapL2promotion promo) {
    CUtensorMap m;
    cuuint64_t dims[2] = {cols, rows}, strides[1] = {cols * 2};
    cuuint32_t box[2] = {bc, br}, es[2] = {1, 1};
    enc(&m, CU_TENSOR_MAP_DATA_TYPE_BFLOAT16, 2, const_cast<void*>(ptr), dims, strides, box, es, CU_TENSOR_MAP_INTERLEAVE_NONE, swz, promo,
        CU_TENSOR_MAP_FLOAT_OOB_FILL_NONE);
    return m;
}
CUtensorMap make_block_map(EncodeFn enc, const void* ptr, uint32_t sections, uint64_t rows, uint32_t br, CUtensorMapL2promotion promo) {
    CUtensorMap m;
    cuuint64_t dims[4] = {64, rows, 16, sections}, strides[3] = {sections * 2048ull, 128, 2048};
    cuuint32_t box[4] = {64, br, 2, sections}, es[4] = {1, 1, 1, 1};
    enc(&m, CU_TENSOR_MAP_DATA_TYPE_BFLOAT16, sections > 1 ? 4 : 3, const_cast<void*>(ptr), dims, strides, box, es, CU_TENSOR_MAP_INTERLEAVE_NONE,
        CU_TENSOR_MAP_SWIZZLE_128B, promo, CU_TENSOR_MAP_FLOAT_OOB_FILL_NONE);
    return m;
}

}

extern "C" void kernel_launch(void* const* d_in, const int* in_sizes, int n_in, void* d_out, int out_size) {
    (void)in_sizes; (void)n_in; (void)out_size;
    void* fn = nullptr; cudaDriverEntryPointQueryResult qr;
    cudaGetDriverEntryPoint("cuTensorMapEncodeTiled", &fn, cudaEnableDefault, &qr);
    EncodeFn enc = (EncodeFn)fn;
    void* hs = nullptr;
    cudaGetSymbolAddress(&hs, g_scratch);
    const CUtensorMapL2promotion P256 = CU_TENSOR_MAP_L2_PROMOTION_L2_256B, P128 = CU_TENSOR_MAP_L2_PROMOTION_L2_128B;
    CUtensorMap tmW = make_block_map(enc, d_in[1], 3, 1024, 64, P256);
    CUtensorMap tmWo = make_map(enc, d_in[3], 1024, 1024, 64, 64, CU_TENSOR_MAP_SWIZZLE_128B, P256);
    CUtensorMap tmPhi = make_map(enc, d_in[2], 32, 1024, 32, 128, CU_TENSOR_MAP_SWIZZLE_64B, P128);
    CUtensorMap tmG = make_map(enc, d_in[6], 3584, 1024, 64, 128, CU_TENSOR_MAP_SWIZZLE_128B, P128);
    CUtensorMap tmU = make_map(enc, d_in[7], 3584, 1024, 64, 128, CU_TENSOR_MAP_SWIZZLE_128B, P128);
    CUtensorMap tmD = make_block_map(enc, d_in[8], 1, 3584, 64, P128);
    CUtensorMap tmX = make_map(enc, d_in[0], 1024, 2048, 64, 128, CU_TENSOR_MAP_SWIZZLE_128B, P128);
    CUtensorMap tmO = make_block_map(enc, d_out, 1, 2048, 8, P128);
    CUtensorMap tmM = make_map(enc, d_in[10], 6144, 1024, 64, 64, CU_TENSOR_MAP_SWIZZLE_128B, P128);
    CUtensorMap tmR = make_map(enc, d_in[10], 6144, 1024, 32, 64, CU_TENSOR_MAP_SWIZZLE_NONE, P128);
    CUtensorMap tmG8 = make_map(enc, d_in[6], 3584, 1024, 8, 64, CU_TENSOR_MAP_SWIZZLE_NONE, P128);
    CUtensorMap tmU8 = make_map(enc, d_in[7], 3584, 1024, 8, 64, CU_TENSOR_MAP_SWIZZLE_NONE, P128);
    CUtensorMap tmD8 = make_map(enc, d_in[8], 1024, 3584, 8, 64, CU_TENSOR_MAP_SWIZZLE_NONE, P128);
    CUtensorMap tmW2 = make_map(enc, d_in[1], 3072, 1024, 64, 64, CU_TENSOR_MAP_SWIZZLE_128B, P256);
    Ptrs p;
    p.x = (const bf16*)d_in[0]; p.c = (const bf16*)d_in[9]; p.wmod = (const bf16*)d_in[10]; p.wr = (const bf16*)d_in[5];
    p.wg = (const bf16*)d_in[6]; p.wu = (const bf16*)d_in[7]; p.wd = (const bf16*)d_in[8]; p.out = (bf16*)d_out; p.s = (Scratch*)hs;
    p.wqkv = (const bf16*)d_in[1]; p.wo = (const bf16*)d_in[3];
    cudaFuncSetAttribute(fused_kernel, cudaFuncAttributeMaxDynamicSharedMemorySize, SMEM_BYTES);
    fused_kernel<<<128, NTHREADS, SMEM_BYTES, cudaStreamPerThread>>>(p, tmW, tmWo, tmPhi, tmG, tmU, tmD, tmX, tmO, tmM, tmR, tmG8, tmU8, tmD8, tmW2);
}
```

```cpp
#include <cuda_runtime.h>
#include <cuda.h>
#include <cuda_bf16.h>
#include <stdint.h>

namespace {

typedef __nv_bfloat16 bf16;

constexpr int NTHREADS = 384;
constexpr int POLL_MAX = 400000;
constexpr uint32_t EMPTY = 0xffffffffu;

#define PND 6
#define PNG 5
constexpr int PRD = (64 + PND - 1) / PND, PRG = (384 + PNG - 1) / PNG;
constexpr uint32_t OFF_RING = 0;
constexpr uint32_t OFF_XS   = 65536;
constexpr uint32_t OFF_WST  = 98304;
constexpr uint32_t OFF_XT   = 0;
constexpr uint32_t OFF_GA   = 32768;
constexpr uint32_t OFF_PHI0 = 163840, OFF_PHI1 = 98304;
constexpr uint32_t OFF_V    = 131072;
constexpr uint32_t OFF_KVS  = 131072;
constexpr uint32_t OFF_DB   = 0;
constexpr uint32_t OFF_DA   = 98304;
constexpr uint64_t SLOT_A   = 0x5432105432105432ull, SLOT_B = 0x1054321054321054ull;
constexpr uint32_t PAR_A    = 0x3f00, PAR_B = 0x0fc0;
constexpr uint32_t OFF_OWN  = OFF_DA + 32768;
constexpr uint32_t OFF_OUT  = OFF_DA + 65536;
constexpr uint32_t OFF_UP0  = OFF_DA, OFF_UP1 = OFF_DB + 32768, OFF_DN0 = OFF_DA + 32768, OFF_DN1 = OFF_DB + 65536;
constexpr uint32_t OFF_WPHI = 196608;
constexpr uint32_t OFF_SP   = 204800;
constexpr uint32_t OFF_Z    = 221184;
constexpr uint32_t OFF_ONES = 225280;
constexpr uint32_t OFF_MODS = 226304;
constexpr uint32_t OFF_GB   = 196608;
constexpr uint32_t OFF_BQ   = 229376;
constexpr uint32_t OFF_ATOT = OFF_BQ + 256;
constexpr uint32_t OFF_BAR  = 230400;
constexpr uint32_t OFF_SEEN = OFF_BAR + 632;
constexpr uint32_t OFF_PAR  = OFF_BAR + 640;
constexpr uint32_t SMEM_BYTES = 232448;
constexpr uint32_t OFF_SILU = OFF_Z;
constexpr uint32_t OFF_RED0 = OFF_Z + 2048;
constexpr uint32_t OFF_DUMMY = OFF_RED0 + 512;
constexpr uint32_t OFF_ST2  = OFF_DB;
constexpr uint32_t OFF_SEL  = OFF_ST2 + 1024;
constexpr uint32_t OFF_ROWS = OFF_ST2 + 2048;
constexpr uint32_t OFF_PX   = OFF_ROWS + 4608;
constexpr uint32_t OFF_HID  = OFF_PX + 2048;

enum {
    B_F1 = 0, B_E1 = 3, B_STFREE = 6, B_WPHI = 7, B_FA = 8, B_FB = 14, B_RF = 20, B_KVD = 24, B_PAR = 26, B_S0 = 27, B_GU = 28, B_WD = 29,
    B_X2 = 30, B_ST2 = 31, B_CAND = 32,
    B_MP = 33, B_MOD = 34, B_PX = 50, B_S0FREE = 51, B_PHI = 52, B_OUTW = 56, B_PUB = 57, B_KVF = 59, B_OWN = 61, B_REL = 63, B_ROWS = 64, B_SEL = 65, B_YP = 66, B_RED = 67, B_TURN = 68,
    B_XS = 69,
    B_WS = 73, B_COUNT = 77,
    B_ED = B_MOD, B_OGO = B_XS + 2, B_PF = B_XS + 3
};

struct Scratch {
    uint4 os[256 * 1024];
    uint4 kvp[32 * 256 * 32];
    uint4 kvf[32 * 288];
    uint4 st1[2048];
    uint4 mp[128 * 16];
    uint4 rest[1024];
    uint4 flo[256 * 2];
    uint4 st2[2048];
    uint4 cand[64 * 2];
    uint4 rowh[128 * 128];
    uint4 rowx[128 * 128];
    uint4 rsc[64 * 8 * 2];
    uint4 yp[56 * 512];
    unsigned done[4];
};
__device__ __align__(1024) Scratch g_scratch;
#define TS(i) do {} while (0)
#undef GS
#define GS(i)
#define TR(i)
#define TRL(i)
#define WT0()
#define WTJ(j)

__device__ __forceinline__ uint32_t smem_u32(const void* p) { return (uint32_t)__cvta_generic_to_shared(p); }
__device__ __forceinline__ int lane_id() { int l; asm volatile("mov.u32 %0, %%laneid;" : "=r"(l)); return l; }
__device__ __forceinline__ uint32_t clk32() { uint32_t c; asm volatile("mov.u32 %0, %%clock;" : "=r"(c) :: "memory"); return c; }
__device__ __forceinline__ void arrive_one(uint32_t bar) {
    asm volatile("{\n.reg .pred p;\nelect.sync _|p, 0xffffffff;\n@p mbarrier.arrive.shared::cta.b64 _, [%0];\n}" :: "r"(bar) : "memory");
}
__device__ __forceinline__ void arrive_many(uint32_t bar, uint32_t n) {
    asm volatile("{\n.reg .pred p;\nelect.sync _|p, 0xffffffff;\n@p mbarrier.arrive.shared::cta.b64 _, [%0], %1;\n}" :: "r"(bar), "r"(n) : "memory");
}
__device__ __forceinline__ void arrive_if(uint32_t bar, uint32_t on) {
    asm volatile("{\n.reg .pred q, p;\nelect.sync _|q, 0xffffffff;\nsetp.ne.and.u32 p, %1, 0, q;\n@p mbarrier.arrive.shared::cta.b64 _, [%0];\n}" :: "r"(bar), "r"(on) : "memory");
}
__device__ __forceinline__ void arrive_both_if(uint32_t bar, uint32_t on) {
    asm volatile("{\n.reg .pred q, p;\n.reg .b32 r0, r1;\nelect.sync _|q, 0xffffffff;\nsetp.ne.and.u32 p, %1, 0, q;\n"
        "mapa.shared::cluster.u32 r0, %0, 0;\nmapa.shared::cluster.u32 r1, %0, 1;\n"
        "@p mbarrier.arrive.shared::cluster.b64 _, [r0];\n@p mbarrier.arrive.shared::cluster.b64 _, [r1];\n}" :: "r"(bar), "r"(on) : "memory");
}
__device__ __forceinline__ void st_partner64(uint32_t a, uint32_t bar, uint32_t cta, float x, float y) {
    asm volatile("{\n.reg .b32 ra, rb;\nmapa.shared::cluster.u32 ra, %0, %2;\nmapa.shared::cluster.u32 rb, %1, %2;\n"
        "st.async.weak.shared::cluster.mbarrier::complete_tx::bytes.v2.f32 [ra], {%3, %4}, [rb];\n}" :: "r"(a), "r"(bar), "r"(cta), "f"(x), "f"(y) : "memory");
}
__device__ __forceinline__ void mbar_wait(uint32_t bar, uint32_t parity) {
#define WAITV 1
    asm volatile("{\n.reg .pred P1;\n.reg .u32 cnt;\nmbarrier.try_wait.parity.shared::cta.b64 P1, [%0], %1;\n@P1 bra DONE;\nmov.u32 cnt, 0;\nLAB_WAIT:\n"
        "mbarrier.try_wait.parity.shared::cta.b64 P1, [%0], %1;\n@P1 bra DONE;\n"
        "add.u32 cnt, cnt, 1;\nsetp.lt.u32 P1, cnt, 1000000;\n@P1 bra LAB_WAIT;\ntrap;\nDONE:\n}" :: "r"(bar), "r"(parity) : "memory");
}
__device__ __forceinline__ uint64_t policy_evict_first() { uint64_t p; asm("createpolicy.fractional.L2::evict_first.b64 %0, 1.0;" : "=l"(p)); return p; }
#define EF_W 1
#define EF_WO 1
#define EF_F 1
#define EF_M 1
__device__ __forceinline__ void bulk_commit() { asm volatile("cp.async.bulk.commit_group;" ::: "memory"); }
__device__ __forceinline__ void bulk_wait() { asm volatile("cp.async.bulk.wait_group 0;" ::: "memory"); }
__device__ __forceinline__ void tmap_prefetch(const CUtensorMap* tm) { asm volatile("prefetch.tensormap [%0];" :: "l"(tm) : "memory"); }
#define EL "{\n.reg .pred e;\nelect.sync _|e, 0xffffffff;\n@e "
__device__ __forceinline__ void expect_tx_e(uint32_t bar, uint32_t bytes) { asm volatile(EL "mbarrier.arrive.expect_tx.shared::cta.b64 _, [%0], %1;\n}" :: "r"(bar), "r"(bytes) : "memory"); }
__device__ __forceinline__ void tma2_e(uint32_t dst, const CUtensorMap* tm, int c0, int c1, uint32_t bar) {
    asm volatile(EL "cp.async.bulk.tensor.2d.shared::cluster.global.mbarrier::complete_tx::bytes [%0], [%1, {%3, %4}], [%2];\n}"
        :: "r"(dst), "l"(tm), "r"(bar), "r"(c0), "r"(c1) : "memory");
}
__device__ __forceinline__ void tma2_ef_e(uint32_t dst, const CUtensorMap* tm, int c0, int c1, uint32_t bar) {
    asm volatile(EL "cp.async.bulk.tensor.2d.shared::cluster.global.mbarrier::complete_tx::bytes.L2::cache_hint [%0], [%1, {%3, %4}], [%2], %5;\n}"
        :: "r"(dst), "l"(tm), "r"(bar), "r"(c0), "r"(c1), "l"(policy_evict_first()) : "memory");
}
__device__ __forceinline__ void tma2_mc_e(uint32_t dst, const CUtensorMap* tm, int c0, int c1, uint32_t bar) {
    if (!EF_WO) asm volatile(EL "cp.async.bulk.tensor.2d.shared::cluster.global.mbarrier::complete_tx::bytes.multicast::cluster [%0], [%1, {%3, %4}], [%2], %5;\n}"
        :: "r"(dst), "l"(tm), "r"(bar), "r"(c0), "r"(c1), "h"((uint16_t)3) : "memory");
    else
    asm volatile(EL "cp.async.bulk.tensor.2d.shared::cluster.global.mbarrier::complete_tx::bytes.multicast::cluster.L2::cache_hint [%0], [%1, {%3, %4}], [%2], %5, %6;\n}"
        :: "r"(dst), "l"(tm), "r"(bar), "r"(c0), "r"(c1), "h"((uint16_t)3), "l"(policy_evict_first()) : "memory");
}
__device__ __forceinline__ void tma3_ef_e(uint32_t dst, const CUtensorMap* tm, int row, int blk, uint32_t bar) {
    if (!EF_F) asm volatile(EL "cp.async.bulk.tensor.3d.shared::cluster.global.mbarrier::complete_tx::bytes [%0], [%1, {0, %3, %4}], [%2];\n}"
        :: "r"(dst), "l"(tm), "r"(bar), "r"(row), "r"(blk) : "memory");
    else
    asm volatile(EL "cp.async.bulk.tensor.3d.shared::cluster.global.mbarrier::complete_tx::bytes.L2::cache_hint [%0], [%1, {0, %3, %4}], [%2], %5;\n}"
        :: "r"(dst), "l"(tm), "r"(bar), "r"(row), "r"(blk), "l"(policy_evict_first()) : "memory");
}
__device__ __forceinline__ void tma4_e(uint32_t dst, const CUtensorMap* tm, int row, int blk, uint32_t bar, bool ef) {
    if (!ef) asm volatile(EL "cp.async.bulk.tensor.4d.shared::cluster.global.mbarrier::complete_tx::bytes [%0], [%1, {0, %3, %4, 0}], [%2];\n}"
        :: "r"(dst), "l"(tm), "r"(bar), "r"(row), "r"(blk) : "memory");
    else
    asm volatile(EL "cp.async.bulk.tensor.4d.shared::cluster.global.mbarrier::complete_tx::bytes.L2::cache_hint [%0], [%1, {0, %3, %4, 0}], [%2], %5;\n}"
        :: "r"(dst), "l"(tm), "r"(bar), "r"(row), "r"(blk), "l"(policy_evict_first()) : "memory");
}
__device__ __forceinline__ void bulk_load_e(uint32_t dst, const void* src, uint32_t bytes, uint32_t bar) {
    asm volatile(EL "cp.async.bulk.shared::cluster.global.mbarrier::complete_tx::bytes [%0], [%1], %2, [%3];\n}" :: "r"(dst), "l"(src), "r"(bytes), "r"(bar) : "memory");
}
__device__ __forceinline__ void bulk_store_e(void* dst, uint32_t src, uint32_t bytes) {
    asm volatile(EL "cp.async.bulk.global.shared::cta.bulk_group [%0], [%1], %2;\n}" :: "l"(dst), "r"(src), "r"(bytes) : "memory");
}
__device__ __forceinline__ void st_flag_e(void* p, unsigned v) { asm volatile(EL "st.relaxed.gpu.global.u32 [%0], %1;\n}" :: "l"(p), "r"(v) : "memory"); }
__device__ __forceinline__ void mbar_init(uint32_t bar, uint32_t cnt) { asm volatile("mbarrier.init.shared::cta.b64 [%0], %1;" :: "r"(bar), "r"(cnt) : "memory"); }
__device__ __forceinline__ bool elect_one() {
    uint32_t p;
    asm volatile("{\n.reg .pred P;\nelect.sync _|P, 0xffffffff;\nselp.u32 %0, 1, 0, P;\n}" : "=r"(p));
    return p;
}
__device__ __forceinline__ void wg_fence() { asm volatile("wgmma.fence.sync.aligned;" ::: "memory"); }
__device__ __forceinline__ void wg_commit() { asm volatile("wgmma.commit_group.sync.aligned;" ::: "memory"); }
template<int N> __device__ __forceinline__ void wg_wait() { asm volatile("wgmma.wait_group.sync.aligned %0;" :: "n"(N) : "memory"); }
template<int N> __device__ __forceinline__ void acc_fence(float (&d)[N]) {
    #pragma unroll
    for (int i = 0; i < N; i++) asm volatile("" : "+f"(d[i]) :: "memory");
}
__device__ __forceinline__ uint64_t mk_desc(uint32_t addr, uint32_t lbo, uint32_t sbo, uint32_t swz) {
    uint32_t lo = ((addr & 0x3FFFF) >> 4) | (((lbo & 0x3FFFF) >> 4) << 16);
    uint32_t hi = (sbo >> 4) | (swz << 30);
    return ((uint64_t)hi << 32) | lo;
}
__device__ __forceinline__ uint64_t desc_add(uint64_t d, uint32_t bytes) { return (d & 0xffffffff00000000ull) | (uint32_t)((uint32_t)d + (bytes >> 4)); }
__device__ __forceinline__ uint64_t desc_raw(uint64_t d, uint32_t inc) { return (d & 0xffffffff00000000ull) | (uint32_t)((uint32_t)d + inc); }
__device__ __forceinline__ void fence_async_smem() { asm volatile("fence.proxy.async.shared::cta;" ::: "memory"); }
__device__ __forceinline__ void bar_sync(int id, int n) { asm volatile("bar.sync %0, %1;" :: "r"(id), "r"(n) : "memory"); }
__device__ __forceinline__ void bar_arrive(int id, int n) { asm volatile("bar.arrive %0, %1;" :: "r"(id), "r"(n) : "memory"); }
template<int R> __device__ __forceinline__ void reg_inc() { asm volatile("setmaxnreg.inc.sync.aligned.u32 %0;" :: "n"(R)); }
template<int R> __device__ __forceinline__ void reg_dec() { asm volatile("setmaxnreg.dec.sync.aligned.u32 %0;" :: "n"(R)); }
__device__ __forceinline__ void cluster_arrive() { asm volatile("barrier.cluster.arrive.relaxed.aligned;" ::: "memory"); }
__device__ __forceinline__ void cluster_wait() { asm volatile("barrier.cluster.wait.acquire.aligned;" ::: "memory"); }

__device__ __forceinline__ void stsm4(uint32_t addr, uint32_t r0, uint32_t r1, uint32_t r2, uint32_t r3) {
    asm volatile("stmatrix.sync.aligned.m8n8.x4.shared.b16 [%0], {%1,%2,%3,%4};" :: "r"(addr), "r"(r0), "r"(r1), "r"(r2), "r"(r3) : "memory");
}
__device__ __forceinline__ void ldsm4(uint32_t& r0, uint32_t& r1, uint32_t& r2, uint32_t& r3, uint32_t addr) {
    asm volatile("ldmatrix.sync.aligned.m8n8.x4.shared.b16 {%0,%1,%2,%3}, [%4];" : "=r"(r0), "=r"(r1), "=r"(r2), "=r"(r3) : "r"(addr) : "memory");
}
__device__ __forceinline__ void ldsm4t(uint32_t& r0, uint32_t& r1, uint32_t& r2, uint32_t& r3, uint32_t addr) {
    asm volatile("ldmatrix.sync.aligned.m8n8.x4.trans.shared.b16 {%0,%1,%2,%3}, [%4];" : "=r"(r0), "=r"(r1), "=r"(r2), "=r"(r3) : "r"(addr) : "memory");
}
__device__ __forceinline__ void mma16816(float (&d)[4], uint32_t a0, uint32_t a1, uint32_t a2, uint32_t a3, uint32_t b0, uint32_t b1) {
    asm("mma.sync.aligned.m16n8k16.row.col.f32.bf16.bf16.f32 {%0,%1,%2,%3}, {%4,%5,%6,%7}, {%8,%9}, {%0,%1,%2,%3};"
        : "+f"(d[0]), "+f"(d[1]), "+f"(d[2]), "+f"(d[3]) : "r"(a0), "r"(a1), "r"(a2), "r"(a3), "r"(b0), "r"(b1));
}
__device__ __forceinline__ void mma1688(float (&d)[4], uint32_t a0, uint32_t a1, uint32_t b0) {
    asm("mma.sync.aligned.m16n8k8.row.col.f32.bf16.bf16.f32 {%0,%1,%2,%3}, {%4,%5}, {%6}, {%0,%1,%2,%3};"
        : "+f"(d[0]), "+f"(d[1]), "+f"(d[2]), "+f"(d[3]) : "r"(a0), "r"(a1), "r"(b0));
}
__device__ __forceinline__ uint4 lds128(uint32_t a) { uint4 v; asm volatile("ld.shared.v4.b32 {%0,%1,%2,%3}, [%4];" : "=r"(v.x), "=r"(v.y), "=r"(v.z), "=r"(v.w) : "r"(a) : "memory"); return v; }
__device__ __forceinline__ uint2 lds64(uint32_t a) { uint2 v; asm volatile("ld.shared.v2.b32 {%0,%1}, [%2];" : "=r"(v.x), "=r"(v.y) : "r"(a) : "memory"); return v; }
__device__ __forceinline__ uint32_t lds32(uint32_t a) { uint32_t v; asm volatile("ld.shared.b32 %0, [%1];" : "=r"(v) : "r"(a) : "memory"); return v; }
__device__ __forceinline__ float ldsf(uint32_t a) { float v; asm volatile("ld.shared.f32 %0, [%1];" : "=f"(v) : "r"(a) : "memory"); return v; }
__device__ __forceinline__ uint32_t lds16(uint32_t a) { uint16_t v; asm volatile("ld.shared.b16 %0, [%1];" : "=h"(v) : "r"(a) : "memory"); return v; }
__device__ __forceinline__ void sts128(uint32_t a, uint4 v) { asm volatile("st.shared.v4.b32 [%0], {%1,%2,%3,%4};" :: "r"(a), "r"(v.x), "r"(v.y), "r"(v.z), "r"(v.w) : "memory"); }
__device__ __forceinline__ void sts64(uint32_t a, uint32_t x, uint32_t y) { asm volatile("st.shared.v2.b32 [%0], {%1,%2};" :: "r"(a), "r"(x), "r"(y) : "memory"); }
__device__ __forceinline__ void sts32(uint32_t a, uint32_t x) { asm volatile("st.shared.b32 [%0], %1;" :: "r"(a), "r"(x) : "memory"); }
__device__ __forceinline__ void stsf(uint32_t a, float x) { asm volatile("st.shared.f32 [%0], %1;" :: "r"(a), "f"(x) : "memory"); }
__device__ __forceinline__ void sts16(uint32_t a, uint32_t x) { asm volatile("st.shared.b16 [%0], %1;" :: "r"(a), "h"((uint16_t)x) : "memory"); }

__device__ __forceinline__ uint4 ldg128(const void* p) { uint4 v; asm volatile("ld.global.nc.v4.b32 {%0,%1,%2,%3}, [%4];" : "=r"(v.x), "=r"(v.y), "=r"(v.z), "=r"(v.w) : "l"(p)); return v; }
__device__ __forceinline__ uint2 ldg64(const void* p) { uint2 v; asm volatile("ld.global.nc.v2.b32 {%0,%1}, [%2];" : "=r"(v.x), "=r"(v.y) : "l"(p)); return v; }
__device__ __forceinline__ void stg128(void* p, uint4 v) { asm volatile("st.global.v4.b32 [%0], {%1,%2,%3,%4};" :: "l"(p), "r"(v.x), "r"(v.y), "r"(v.z), "r"(v.w) : "memory"); }
__device__ __forceinline__ void stg_fill(void* p, uint32_t v) { asm volatile("st.global.v4.b32 [%0], {%1,%1,%1,%1};" :: "l"(p), "r"(v) : "memory"); }
__device__ __forceinline__ void st_ll(void* p, uint32_t x, uint32_t y, uint32_t z, uint32_t w) {
    asm volatile("{\n.reg .b128 t;\n.reg .b64 a, b;\nmov.b64 a, {%1, %2};\nmov.b64 b, {%3, %4};\nmov.b128 t, {a, b};\nst.relaxed.gpu.global.b128 [%0], t;\n}"
        :: "l"(p), "r"(x), "r"(y), "r"(z), "r"(w) : "memory");
}
__device__ __forceinline__ uint4 ld_ll(const void* p) {
    uint4 v;
    asm volatile("{\n.reg .b128 t;\n.reg .b64 a, b;\nld.relaxed.gpu.global.b128 t, [%4];\nmov.b128 {a, b}, t;\nmov.b64 {%0, %1}, a;\nmov.b64 {%2, %3}, b;\n}"
        : "=r"(v.x), "=r"(v.y), "=r"(v.z), "=r"(v.w) : "l"(p) : "memory");
    return v;
}
__device__ __forceinline__ void ld_ll_if(uint4& v, const void* p, bool go) {
    asm volatile("{\n.reg .b128 t;\n.reg .b64 a, b;\n.reg .pred q;\nsetp.ne.u32 q, %5, 0;\nmov.b64 a, {%0, %1};\nmov.b64 b, {%2, %3};\nmov.b128 t, {a, b};\n"
        "@q ld.relaxed.gpu.global.b128 t, [%4];\nmov.b128 {a, b}, t;\nmov.b64 {%0, %1}, a;\nmov.b64 {%2, %3}, b;\n}"
        : "+r"(v.x), "+r"(v.y), "+r"(v.z), "+r"(v.w) : "l"(p), "r"((uint32_t)go) : "memory");
}
__device__ __forceinline__ void st_ll8(void* p, uint32_t x, uint32_t y) {
    asm volatile("{\n.reg .b64 a;\nmov.b64 a, {%1, %2};\nst.relaxed.gpu.global.b64 [%0], a;\n}" :: "l"(p), "r"(x), "r"(y) : "memory");
}
__device__ __forceinline__ void st_ll4(void* p, uint32_t x) { asm volatile("st.relaxed.gpu.global.b32 [%0], %1;" :: "l"(p), "r"(x) : "memory"); }
__device__ __forceinline__ unsigned ld_rlx(const void* p) { unsigned v; asm volatile("ld.relaxed.gpu.global.u32 %0, [%1];" : "=r"(v) : "l"(p) : "memory"); return v; }
__device__ __forceinline__ void red_add4(void* p, float x, float y, float z, float w) {
    asm volatile("red.relaxed.gpu.global.add.v4.f32 [%0], {%1, %2, %3, %4};" :: "l"(p), "f"(x), "f"(y), "f"(z), "f"(w) : "memory");
}
__device__ __forceinline__ void fence_rel_gpu() { asm volatile("fence.proxy.async.global;\nfence.release.gpu;" ::: "memory"); }
__device__ __forceinline__ void fence_acq_gpu() { asm volatile("fence.acquire.gpu;" ::: "memory"); }
template<int N> __device__ __forceinline__ void poll_words(uint4 (&v)[N], const uint4* p, int stride, uint32_t tag) {
    #pragma unroll 1
    for (int it = 0; it < POLL_MAX; it++) {
        bool ok = true;
        #pragma unroll
        for (int i = 0; i < N; i++) v[i] = ld_ll(p + i * stride);
        #pragma unroll
        for (int i = 0; i < N; i++) ok = ok && (v[i].w == tag);
        if (__all_sync(0xffffffffu, ok)) break;
    }
}
template<int B> __device__ __forceinline__ uint32_t low_byte(float v, uint32_t src) { return __byte_perm(__float_as_uint(v), src, 0x3214 + B); }
__device__ __forceinline__ uint32_t low_bits(float v, uint32_t tag2) { return (__float_as_uint(v) & ~3u) | tag2; }
__device__ __forceinline__ bool tagged2(uint32_t w, uint32_t tag2) { return (w & 3u) == tag2; }
__device__ __forceinline__ uint32_t umax4(uint4 v) { return max(max(v.x, v.y), max(v.z, v.w)); }
constexpr uint32_t ONE2 = 0x3F803F80u;
__device__ __forceinline__ uint32_t pack2(float lo, float hi) { uint32_t d; asm("cvt.rn.bf16x2.f32 %0, %1, %2;" : "=r"(d) : "f"(hi), "f"(lo)); return d; }
__device__ __forceinline__ float bf_lo(uint32_t v) { return __uint_as_float(v << 16); }
__device__ __forceinline__ float bf_lo_after(uint32_t v, float nonneg) { float d; asm("prmt.b32 %0, %1, %2, 0x10ff;" : "=f"(d) : "r"(v), "f"(nonneg)); return d; }
__device__ __forceinline__ float bf_hi_after(uint32_t v, float nonneg) { float d; asm("prmt.b32 %0, %1, %2, 0x32ff;" : "=f"(d) : "r"(v), "f"(nonneg)); return d; }
__device__ __forceinline__ float bf_hi(uint32_t v) { return __uint_as_float(v & 0xffff0000u); }
__device__ __forceinline__ float rbf(float x) { return bf_lo(pack2(x, 0.f)); }
__device__ __forceinline__ uint32_t hsub2(uint32_t a, uint32_t b) { uint32_t d; asm("sub.rn.bf16x2 %0, %1, %2;" : "=r"(d) : "r"(a), "r"(b)); return d; }
__device__ __forceinline__ uint32_t hadd2(uint32_t a, uint32_t b) { uint32_t d; asm("add.rn.bf16x2 %0, %1, %2;" : "=r"(d) : "r"(a), "r"(b)); return d; }
__device__ __forceinline__ uint32_t hmul2(uint32_t a, uint32_t b) { uint32_t d; asm("mul.rn.bf16x2 %0, %1, %2;" : "=r"(d) : "r"(a), "r"(b)); return d; }
__device__ __forceinline__ uint32_t hmax2(uint32_t a, uint32_t b) { uint32_t d; asm("max.bf16x2 %0, %1, %2;" : "=r"(d) : "r"(a), "r"(b)); return d; }
__device__ __forceinline__ uint32_t hmin2(uint32_t a, uint32_t b) { uint32_t d; asm("min.bf16x2 %0, %1, %2;" : "=r"(d) : "r"(a), "r"(b)); return d; }
__device__ __forceinline__ float ex2(float x) { float y; asm("ex2.approx.ftz.f32 %0, %1;" : "=f"(y) : "f"(x)); return y; }
__device__ __forceinline__ float rcp(float x) { float y; asm("rcp.approx.ftz.f32 %0, %1;" : "=f"(y) : "f"(x)); return y; }
__device__ __forceinline__ float shfl_x(float v, int m) { return __shfl_xor_sync(0xffffffffu, v, m); }
constexpr float LOG2E = 1.4426950408889634f;
__device__ __forceinline__ float sigmoidf(float x) { return rcp(1.0f + ex2(-LOG2E * x)); }
__device__ __forceinline__ uint32_t ln_pair(uint32_t x, uint32_t m2, float rinv, uint32_t a, uint32_t s) {
    uint32_t d = hsub2(x, m2);
    uint32_t n = pack2(bf_lo(d) * rinv, bf_hi(d) * rinv);
    return hadd2(hmul2(n, a), s);
}
struct Recip { uint32_t hi, lo; };
__device__ __forceinline__ Recip split_recip(float r) { Recip q; q.hi = pack2(r, r); const float l = r - bf_hi(q.hi); q.lo = pack2(l, l); return q; }
__device__ __forceinline__ uint32_t hdiv2(uint32_t n, Recip r) { uint32_t d; asm("fma.rn.bf16x2 %0, %1, %2, %3;" : "=r"(d) : "r"(n), "r"(r.hi), "r"(hmul2(n, r.lo))); return d; }
__device__ __forceinline__ uint32_t ln_pair(uint32_t x, uint32_t m2, Recip r, uint32_t a, uint32_t s) { return hadd2(hmul2(hdiv2(hsub2(x, m2), r), a), s); }
__device__ __forceinline__ void ln_final(float s1, float s2, uint32_t& m2, float& rinv) {
    const float mean = s1 * (1.0f / 1024.0f), var = fmaf(-mean, mean, s2 * (1.0f / 1024.0f));
    m2 = pack2(mean, mean);
    float sd;
    asm("sqrt.approx.ftz.f32 %0, %1;" : "=f"(sd) : "f"(rbf(rbf(fmaxf(var, 0.f)) + 1e-5f)));
    rinv = rcp(rbf(sd));
}
__device__ __forceinline__ uint32_t f2key(float f) { uint32_t u = __float_as_uint(f); return (u & 0x80000000u) ? ~u : (u | 0x80000000u); }

__device__ __forceinline__ void fm_extrema(const uint32_t (&p)[16], float& cp, float& cn) {
    uint32_t mx = p[0], mn = p[0];
    #pragma unroll
    for (int k = 1; k < 15; k += 2) { mx = hmax2(hmax2(mx, p[k]), p[k + 1]); mn = hmin2(hmin2(mn, p[k]), p[k + 1]); }
    mx = hmax2(mx, p[15]); mn = hmin2(mn, p[15]);
    cp = -fmaxf(bf_lo(mx), bf_hi(mx)) * LOG2E; cn = fminf(bf_lo(mn), bf_hi(mn)) * LOG2E;
}
template<int TB> __device__ __forceinline__ void wgmma_n32_rs(float (&d)[16], uint32_t a0, uint32_t a1, uint32_t a2, uint32_t a3, uint64_t db, int sc) {
  asm volatile("{\n.reg .pred p;\nsetp.ne.b32 p, %21, 0;\n"
    "wgmma.mma_async.sync.aligned.m64n32k16.f32.bf16.bf16 {%0, %1, %2, %3, %4, %5, %6, %7, %8, %9, %10, %11, %12, %13, %14, %15}, {%16,%17,%18,%19}, %20, p, 1, 1, %22;\n}\n"
    : "+f"(d[0]), "+f"(d[1]), "+f"(d[2]), "+f"(d[3]), "+f"(d[4]), "+f"(d[5]), "+f"(d[6]), "+f"(d[7]), "+f"(d[8]), "+f"(d[9]), "+f"(d[10]), "+f"(d[11]), "+f"(d[12]), "+f"(d[13]), "+f"(d[14]), "+f"(d[15])
    : "r"(a0), "r"(a1), "r"(a2), "r"(a3), "l"(db), "r"(sc), "n"(TB));
}
template<int TA, int TB> __device__ __forceinline__ void wgmma_n40_ss(float (&d)[20], uint64_t da, uint64_t db, int sc) {
  asm volatile("{\n.reg .pred p;\nsetp.ne.b32 p, %22, 0;\n"
    "wgmma.mma_async.sync.aligned.m64n40k16.f32.bf16.bf16 {%0, %1, %2, %3, %4, %5, %6, %7, %8, %9, %10, %11, %12, %13, %14, %15, %16, %17, %18, %19}, %20, %21, p, 1, 1, %23, %24;\n}\n"
    : "+f"(d[0]), "+f"(d[1]), "+f"(d[2]), "+f"(d[3]), "+f"(d[4]), "+f"(d[5]), "+f"(d[6]), "+f"(d[7]), "+f"(d[8]), "+f"(d[9]), "+f"(d[10]), "+f"(d[11]), "+f"(d[12]), "+f"(d[13]), "+f"(d[14]), "+f"(d[15]), "+f"(d[16]), "+f"(d[17]), "+f"(d[18]), "+f"(d[19])
    : "l"(da), "l"(db), "r"(sc), "n"(TA), "n"(TB));
}
template<int TA, int TB> __device__ __forceinline__ void wgmma_n128_ss(float (&d)[64], uint64_t da, uint64_t db, int sc) {
  asm volatile("{\n.reg .pred p;\nsetp.ne.b32 p, %66, 0;\n"
    "wgmma.mma_async.sync.aligned.m64n128k16.f32.bf16.bf16 {%0, %1, %2, %3, %4, %5, %6, %7, %8, %9, %10, %11, %12, %13, %14, %15, %16, %17, %18, %19, %20, %21, %22, %23, %24, %25, %26, %27, %28, %29, %30, %31, %32, %33, %34, %35, %36, %37, %38, %39, %40, %41, %42, %43, %44, %45, %46, %47, %48, %49, %50, %51, %52, %53, %54, %55, %56, %57, %58, %59, %60, %61, %62, %63}, %64, %65, p, 1, 1, %67, %68;\n}\n"
    : "+f"(d[0]), "+f"(d[1]), "+f"(d[2]), "+f"(d[3]), "+f"(d[4]), "+f"(d[5]), "+f"(d[6]), "+f"(d[7]), "+f"(d[8]), "+f"(d[9]), "+f"(d[10]), "+f"(d[11]), "+f"(d[12]), "+f"(d[13]), "+f"(d[14]), "+f"(d[15]), "+f"(d[16]), "+f"(d[17]), "+f"(d[18]), "+f"(d[19]), "+f"(d[20]), "+f"(d[21]), "+f"(d[22]), "+f"(d[23]), "+f"(d[24]), "+f"(d[25]), "+f"(d[26]), "+f"(d[27]), "+f"(d[28]), "+f"(d[29]), "+f"(d[30]), "+f"(d[31]), "+f"(d[32]), "+f"(d[33]), "+f"(d[34]), "+f"(d[35]), "+f"(d[36]), "+f"(d[37]), "+f"(d[38]), "+f"(d[39]), "+f"(d[40]), "+f"(d[41]), "+f"(d[42]), "+f"(d[43]), "+f"(d[44]), "+f"(d[45]), "+f"(d[46]), "+f"(d[47]), "+f"(d[48]), "+f"(d[49]), "+f"(d[50]), "+f"(d[51]), "+f"(d[52]), "+f"(d[53]), "+f"(d[54]), "+f"(d[55]), "+f"(d[56]), "+f"(d[57]), "+f"(d[58]), "+f"(d[59]), "+f"(d[60]), "+f"(d[61]), "+f"(d[62]), "+f"(d[63])
    : "l"(da), "l"(db), "r"(sc), "n"(TA), "n"(TB));
}
template<int TB> __device__ __forceinline__ void wgmma_n128_rs(float (&d)[64], uint32_t a0, uint32_t a1, uint32_t a2, uint32_t a3, uint64_t db, int sc) {
  asm volatile("{\n.reg .pred p;\nsetp.ne.b32 p, %69, 0;\n"
    "wgmma.mma_async.sync.aligned.m64n128k16.f32.bf16.bf16 {%0, %1, %2, %3, %4, %5, %6, %7, %8, %9, %10, %11, %12, %13, %14, %15, %16, %17, %18, %19, %20, %21, %22, %23, %24, %25, %26, %27, %28, %29, %30, %31, %32, %33, %34, %35, %36, %37, %38, %39, %40, %41, %42, %43, %44, %45, %46, %47, %48, %49, %50, %51, %52, %53, %54, %55, %56, %57, %58, %59, %60, %61, %62, %63}, {%64,%65,%66,%67}, %68, p, 1, 1, %70;\n}\n"
    : "+f"(d[0]), "+f"(d[1]), "+f"(d[2]), "+f"(d[3]), "+f"(d[4]), "+f"(d[5]), "+f"(d[6]), "+f"(d[7]), "+f"(d[8]), "+f"(d[9]), "+f"(d[10]), "+f"(d[11]), "+f"(d[12]), "+f"(d[13]), "+f"(d[14]), "+f"(d[15]), "+f"(d[16]), "+f"(d[17]), "+f"(d[18]), "+f"(d[19]), "+f"(d[20]), "+f"(d[21]), "+f"(d[22]), "+f"(d[23]), "+f"(d[24]), "+f"(d[25]), "+f"(d[26]), "+f"(d[27]), "+f"(d[28]), "+f"(d[29]), "+f"(d[30]), "+f"(d[31]), "+f"(d[32]), "+f"(d[33]), "+f"(d[34]), "+f"(d[35]), "+f"(d[36]), "+f"(d[37]), "+f"(d[38]), "+f"(d[39]), "+f"(d[40]), "+f"(d[41]), "+f"(d[42]), "+f"(d[43]), "+f"(d[44]), "+f"(d[45]), "+f"(d[46]), "+f"(d[47]), "+f"(d[48]), "+f"(d[49]), "+f"(d[50]), "+f"(d[51]), "+f"(d[52]), "+f"(d[53]), "+f"(d[54]), "+f"(d[55]), "+f"(d[56]), "+f"(d[57]), "+f"(d[58]), "+f"(d[59]), "+f"(d[60]), "+f"(d[61]), "+f"(d[62]), "+f"(d[63])
    : "r"(a0), "r"(a1), "r"(a2), "r"(a3), "l"(db), "r"(sc), "n"(TB));
}
template<int TB> __device__ __forceinline__ void wgmma_n256_rs(float (&d)[128], uint32_t a0, uint32_t a1, uint32_t a2, uint32_t a3, uint64_t db, int sc) {
  asm volatile("{\n.reg .pred p;\nsetp.ne.b32 p, %133, 0;\n"
    "wgmma.mma_async.sync.aligned.m64n256k16.f32.bf16.bf16 {%0, %1, %2, %3, %4, %5, %6, %7, %8, %9, %10, %11, %12, %13, %14, %15, %16, %17, %18, %19, %20, %21, %22, %23, %24, %25, %26, %27, %28, %29, %30, %31, %32, %33, %34, %35, %36, %37, %38, %39, %40, %41, %42, %43, %44, %45, %46, %47, %48, %49, %50, %51, %52, %53, %54, %55, %56, %57, %58, %59, %60, %61, %62, %63, %64, %65, %66, %67, %68, %69, %70, %71, %72, %73, %74, %75, %76, %77, %78, %79, %80, %81, %82, %83, %84, %85, %86, %87, %88, %89, %90, %91, %92, %93, %94, %95, %96, %97, %98, %99, %100, %101, %102, %103, %104, %105, %106, %107, %108, %109, %110, %111, %112, %113, %114, %115, %116, %117, %118, %119, %120, %121, %122, %123, %124, %125, %126, %127}, {%128,%129,%130,%131}, %132, p, 1, 1, %134;\n}\n"
    : "+f"(d[0]), "+f"(d[1]), "+f"(d[2]), "+f"(d[3]), "+f"(d[4]), "+f"(d[5]), "+f"(d[6]), "+f"(d[7]), "+f"(d[8]), "+f"(d[9]), "+f"(d[10]), "+f"(d[11]), "+f"(d[12]), "+f"(d[13]), "+f"(d[14]), "+f"(d[15]), "+f"(d[16]), "+f"(d[17]), "+f"(d[18]), "+f"(d[19]), "+f"(d[20]), "+f"(d[21]), "+f"(d[22]), "+f"(d[23]), "+f"(d[24]), "+f"(d[25]), "+f"(d[26]), "+f"(d[27]), "+f"(d[28]), "+f"(d[29]), "+f"(d[30]), "+f"(d[31]), "+f"(d[32]), "+f"(d[33]), "+f"(d[34]), "+f"(d[35]), "+f"(d[36]), "+f"(d[37]), "+f"(d[38]), "+f"(d[39]), "+f"(d[40]), "+f"(d[41]), "+f"(d[42]), "+f"(d[43]), "+f"(d[44]), "+f"(d[45]), "+f"(d[46]), "+f"(d[47]), "+f"(d[48]), "+f"(d[49]), "+f"(d[50]), "+f"(d[51]), "+f"(d[52]), "+f"(d[53]), "+f"(d[54]), "+f"(d[55]), "+f"(d[56]), "+f"(d[57]), "+f"(d[58]), "+f"(d[59]), "+f"(d[60]), "+f"(d[61]), "+f"(d[62]), "+f"(d[63]), "+f"(d[64]), "+f"(d[65]), "+f"(d[66]), "+f"(d[67]), "+f"(d[68]), "+f"(d[69]), "+f"(d[70]), "+f"(d[71]), "+f"(d[72]), "+f"(d[73]), "+f"(d[74]), "+f"(d[75]), "+f"(d[76]), "+f"(d[77]), "+f"(d[78]), "+f"(d[79]), "+f"(d[80]), "+f"(d[81]), "+f"(d[82]), "+f"(d[83]), "+f"(d[84]), "+f"(d[85]), "+f"(d[86]), "+f"(d[87]), "+f"(d[88]), "+f"(d[89]), "+f"(d[90]), "+f"(d[91]), "+f"(d[92]), "+f"(d[93]), "+f"(d[94]), "+f"(d[95]), "+f"(d[96]), "+f"(d[97]), "+f"(d[98]), "+f"(d[99]), "+f"(d[100]), "+f"(d[101]), "+f"(d[102]), "+f"(d[103]), "+f"(d[104]), "+f"(d[105]), "+f"(d[106]), "+f"(d[107]), "+f"(d[108]), "+f"(d[109]), "+f"(d[110]), "+f"(d[111]), "+f"(d[112]), "+f"(d[113]), "+f"(d[114]), "+f"(d[115]), "+f"(d[116]), "+f"(d[117]), "+f"(d[118]), "+f"(d[119]), "+f"(d[120]), "+f"(d[121]), "+f"(d[122]), "+f"(d[123]), "+f"(d[124]), "+f"(d[125]), "+f"(d[126]), "+f"(d[127])
    : "r"(a0), "r"(a1), "r"(a2), "r"(a3), "l"(db), "r"(sc), "n"(TB));
}

#define CCOL 1
#define T_S0 3300
#define T_S1 5800
#define G1W 1
#define LNP 1
#define CG1 232
#define JU 2
#define WPF 0
#define FPF 0
#define KW 8
#define DEP 2
#define STAG 0
#define KVSH 0
#define KVDLY 900
#define PREWAIT 1
#define OUN 4
#define DNE 8
#define YGATE B_YP
#define YDLY 0
#define OUTGATE B_CAND
#define NEARLY 32
#define LN2P 1
#define LPACE 0
#define XGATE B_RED
#define MCW 0
#define JS 0
#define KT 2
#define KPAUSE 0
#define JEF 16
#define BDLY 0
#define PJ2 12
#define PM2 2
#define NPF 20
#define PSP 500
#define PS0 300
#define RJ 0
#define KVD2 0
#define STG23 0
#define CLRM 3
#define WPN 5
#define SGATE 2
#define T_P0 1500
#define T_P1 3000
#define LATEFREE 1
#define NC 2
#define T_W1 2800
#define T_WD 0
#define NW0 32
#define PFN 3
#define PFJ 3
#define PFM 4
#define WOJ 10
#define WON 1
#define NLD (CCOL ? 0 : 1)
#define VFIRST 2
#define T_X0 450
#define T_XD 600
#define MCB 1
#define ORIENT 2
#define PFORDER 0x51634
#define PFORDER2 0x51
#define PFW0 2
#define CLRJ 3
#define CLRK 8
#define JPF 0
#define CLRGATE (B_FB + 4)
#define KVC0 0
#define CLRS 50
#define OGATE 5
#define PFD 0
#define GBN 6
#define BG1 99
#define BG2 99
#define BG3 99
#define BG4 99
#define BG5 99
#define SYNCQ 640
#define SYNCG 4
#define BSP 0
#define T_INI 500
#define T_WLATE 4000
#define T_REST 6000
#define T_COL 7000
#define T_COL2 14000
#define PF_START 9000
#define PF_FIRST 2
#define PFP 400
#define CREG 208
#define TMA_WO tma2_ef_e
#define TMA_M tma2_ef_e
#define TMA_F tma2_ef_e
#define JUN 4
constexpr int JUU = JUN, OUU = OUN;
constexpr bool GS2 = false;
struct Ptrs { const bf16 *x, *c, *wmod, *wr, *wg, *wu, *wd, *wqkv, *wo; bf16* out; Scratch* s; };

#define BAR(i) (sb + OFF_BAR + 8u * (i))

__device__ __forceinline__ int d_block(int hg, int n) {
    const int m = n - (n >= 9 ? 9 : 2);
    return n < 2 ? 2 * hg + n : 2 * (m + (m >= hg)) + (n >= 9);
}
__host__ __device__ constexpr uint32_t bar_count(int i) {
    return (MCB && i >= B_ED && i < B_ED + 16) ? 16 : ((i >= B_E1 && i < B_E1 + 3) || (i >= B_S0FREE && i < B_PHI + 4) || i == B_OWN || i == B_OWN + 1 || (i >= B_ED && i < B_ED + 16)
            || i == B_STFREE || i == B_X2 || i == B_OUTW || i == B_YP || i == B_RED) ? 8
         : ((i >= B_KVD && i < B_KVD + 2) || i == B_ST2 || i == B_TURN) ? 4 : (i == B_KVF || i == B_KVF + 1 ) ? 2 : 1;
}
template<int I0, int I1> __device__ __forceinline__ void init_barriers(uint32_t sb) {
    #pragma unroll
    for (int i = I0; i < I1; i++) mbar_init(BAR(i), bar_count(i));
}
template<int N> __device__ __forceinline__ uint32_t pop_max(uint32_t (&k)[N]) {
    uint32_t m = k[0];
    #pragma unroll
    for (int i = 1; i < N; i++) m = max(m, k[i]);
    m = __reduce_max_sync(0xffffffffu, m);
    #pragma unroll
    for (int i = 0; i < N; i++) k[i] = (k[i] == m) ? 0u : k[i];
    return m;
}
__device__ __forceinline__ uint32_t mod_pos(int step, int g) { return step * 64 + (g >> 1) * 16 + (g & 1) * 4; }
__device__ __forceinline__ void fma8(float (&a)[8], uint4 w, float s) {
    a[0] = fmaf(bf_lo(w.x), s, a[0]); a[1] = fmaf(bf_hi(w.x), s, a[1]); a[2] = fmaf(bf_lo(w.y), s, a[2]); a[3] = fmaf(bf_hi(w.y), s, a[3]);
    a[4] = fmaf(bf_lo(w.z), s, a[4]); a[5] = fmaf(bf_hi(w.z), s, a[5]); a[6] = fmaf(bf_lo(w.w), s, a[6]); a[7] = fmaf(bf_hi(w.w), s, a[7]);
}
__device__ __forceinline__ float reduce8(const float (&v)[8], int lane) {
    const bool b3 = lane & 16, b2 = lane & 8, b1 = lane & 4;
    float a[4], b[2];
    #pragma unroll
    for (int i = 0; i < 4; i++) { float keep = b3 ? v[4 + i] : v[i], send = b3 ? v[i] : v[4 + i]; a[i] = keep + shfl_x(send, 16); }
    #pragma unroll
    for (int i = 0; i < 2; i++) { float keep = b2 ? a[2 + i] : a[i], send = b2 ? a[i] : a[2 + i]; b[i] = keep + shfl_x(send, 8); }
    float keep = b1 ? b[1] : b[0], send = b1 ? b[0] : b[1];
    return keep + shfl_x(send, 4);
}
__device__ __forceinline__ bool mod_collect(uint4 w0, uint4 w1, uint4 w2, uint4 w3, uint32_t sb, int jb, int lane, uint32_t tag2) {
    const uint32_t add = lane < 16 ? ONE2 : 0u;
    const uint32_t lo = pack2((__uint_as_float(w0.x) + __uint_as_float(w1.x)) + (__uint_as_float(w2.x) + __uint_as_float(w3.x)),
                              (__uint_as_float(w0.y) + __uint_as_float(w1.y)) + (__uint_as_float(w2.y) + __uint_as_float(w3.y)));
    const uint32_t hi = pack2((__uint_as_float(w0.z) + __uint_as_float(w1.z)) + (__uint_as_float(w2.z) + __uint_as_float(w3.z)),
                              (__uint_as_float(w0.w) + __uint_as_float(w1.w)) + (__uint_as_float(w2.w) + __uint_as_float(w3.w)));
    sts64(sb + OFF_MODS + jb * 256 + (lane & 15) * 16 + (lane >> 4) * 8, hadd2(lo, add), hadd2(hi, add));
    return tagged2(w0.w, tag2) && tagged2(w1.w, tag2) && tagged2(w2.w, tag2) && tagged2(w3.w, tag2);
}
__device__ __forceinline__ void phi_issue(float (&pp)[2][16], const uint32_t* a, uint32_t sb, int pair) {
    const uint64_t dw = mk_desc(sb + OFF_WPHI + pair * 4096, 16, 512, 2);
    wg_fence();
    #pragma unroll
    for (int ks = 0; ks < 2; ks++)
        #pragma unroll
        for (int h = 0; h < 2; h++) wgmma_n32_rs<1>(pp[h], a[8 * h + 4 * ks], a[8 * h + 4 * ks + 1], a[8 * h + 4 * ks + 2], a[8 * h + 4 * ks + 3], desc_add(dw, h * 2048 + ks * 1024), ks);
    wg_commit();
}
__device__ __forceinline__ void phi_transpose(float (&pp)[2][16], uint32_t (&pt)[16], uint32_t wr, uint32_t rd) {
    wg_wait<0>();
    acc_fence(pp[0]); acc_fence(pp[1]);
    #pragma unroll
    for (int q = 0; q < 4; q++) {
        const float (&a)[16] = pp[q >> 1]; const int o = 8 * (q & 1);
        stsm4(wr ^ (q << 5), pack2(a[o], a[o + 1]), pack2(a[o + 2], a[o + 3]), pack2(a[o + 4], a[o + 5]), pack2(a[o + 6], a[o + 7]));
    }
    __syncwarp();
    #pragma unroll
    for (int i = 0; i < 4; i++) { const uint4 v = lds128(rd ^ (i << 4)); pt[4 * i] = v.x; pt[4 * i + 1] = v.y; pt[4 * i + 2] = v.z; pt[4 * i + 3] = v.w; }
    __syncwarp();
}

__global__ void __cluster_dims__(2, 1, 1) __launch_bounds__(NTHREADS, 1)
fused_kernel(const Ptrs p, const __grid_constant__ CUtensorMap tmW, const __grid_constant__ CUtensorMap tmWo, const __grid_constant__ CUtensorMap tmPhi,
             const __grid_constant__ CUtensorMap tmG, const __grid_constant__ CUtensorMap tmU, const __grid_constant__ CUtensorMap tmD,
             const __grid_constant__ CUtensorMap tmX, const __grid_constant__ CUtensorMap tmO, const __grid_constant__ CUtensorMap tmM,
             const __grid_constant__ CUtensorMap tmR, const __grid_constant__ CUtensorMap tmG8, const __grid_constant__ CUtensorMap tmU8,
             const __grid_constant__ CUtensorMap tmD8)
{
    extern __shared__ __align__(1024) uint8_t smem_raw[];
    const uint32_t sb = smem_u32(smem_raw);
    const int tid = threadIdx.x, lane = tid & 31, warp = __shfl_sync(0xffffffffu, tid >> 5, 0);
    const int b = blockIdx.x;
    const int pr = b >> 1, rank = b & 1;
    const int cls = pr < 4 ? 15 : pr < 36 ? 2 * ((pr - 4) & 7) : 2 * ((pr - 36) % 7) + 1, mem = pr < 4 ? pr : pr < 36 ? (pr - 4) >> 3 : (pr - 36) / 7;
    const int hg = (((cls + 1) >> 1) & 1) * 4 + mem, rb = (cls >> 1) * 2 + rank;
    const bool ffn = b < 112;
    const uint32_t cstart = clk32();

    if (warp >= 8) {
        const int t = tid & 127, w4 = warp & 3, g = lane >> 2, c = lane & 3;
        if (w4 == 0) TS(40);
        reg_dec<504 - 2 * CG1>();
        if (w4 == 2) TS(41);
        if (w4 == 0) { tmap_prefetch(&tmX); tmap_prefetch(&tmW); }
        if (w4 == 3) tmap_prefetch(&tmM);
        if (w4 < 2) while (clk32() - cstart < T_INI) {}
        if (elect_one()) {
            if (w4 & 2) { if (w4 & 1) init_barriers<B_WS, B_COUNT>(sb); else init_barriers<B_XS, B_WS>(sb); }
            else { if (w4 & 1) init_barriers<B_MP, B_XS>(sb); else init_barriers<0, B_MP>(sb); }
        }
        __syncwarp();
        if (w4 < 2) asm volatile("fence.mbarrier_init.release.cluster;" ::: "memory");
        if (w4 == 1) {
            expect_tx_e(BAR(B_PX), 2048); sts32(sb + OFF_SEEN, 0);
        }
        if (w4 == 0) TS(42);
        bar_arrive(0, 384);
        if (w4 == 2) {
            #pragma unroll 1
            for (int i = 0; i < 4; i++) {
                while (clk32() - cstart < T_X0 + i * T_XD) {}
                bulk_load_e(sb + OFF_XS + i * 8192u, p.x + (size_t)(b * 16 + i * 4) * 1024, 8192, BAR(B_XS + i));
                expect_tx_e(BAR(B_XS + i), 8192);
                if (i == 0) TS(43);
            }
        }
        if (w4 == 3 && b < 32 * NC) {
            while (b >= NW0 && clk32() - cstart < T_W1 + (b >> 5) * T_WD) {}
            #pragma unroll 1
            for (int i = 0; i < 4; i++) {
                tma2_ef_e(sb + OFF_WST + i * 8192u, &tmM, (((b >> 2) & 1) ? 0 : 1024) + (b >> 3) * 64, (b & 3) * 256 + i * 64, BAR(B_WS + i));
                expect_tx_e(BAR(B_WS + i), 8192);
            }
            TS(44);
        }
        cluster_arrive();
        const uint32_t tag = ld_rlx(p.s->done) + 1, tag2 = tag % 3u;
        if (w4 == 0) {
            uint4* clr = p.s->kvp + (hg * 1024 + rb) * 32 + lane;
            #pragma unroll 1
            for (int j = 0; j < 3; j++) {
                while (clk32() - cstart < (j ? T_P1 : T_P0)) {}
                if (lane < 24) asm volatile("prefetch.global.L2 [%0];" :: "l"((const char*)p.wqkv + ((j * 128 + b) * 24 + lane) * 128));
            }
            int s = 0, par = 1;
            #pragma unroll 1
            for (int j = 0; j < 19; j++) {
                if (j >= 2) mbar_wait(BAR(j == 2 ? B_STFREE : B_E1 + s), j == 2 ? 0 : par);
                else while (clk32() - cstart < (j ? T_S1 : T_S0)) {}
                const uint32_t st = sb + OFF_RING + s * 65536u;
                if (j < 16) {
                    tma4_e(st + 16384u, &tmW, j * 64, hg * 2, BAR(B_F1 + s), EF_W);
                    tma2_e(st, &tmX, j * 64, rb * 128, BAR(B_F1 + s));
                    expect_tx_e(BAR(B_F1 + s), 65536);
                    if (j >= WOJ && j < WOJ + 4) asm volatile("prefetch.global.L2 [%0];" :: "l"((const char*)p.wo + (j - WOJ) * 524288 + (b * 32 + lane) * 128));
                } else if (j == 17) {
                    #pragma unroll 1
                    for (int n = 0; n < 4; n++) {
                        if (!(n & 1)) expect_tx_e(BAR(B_FB + 4 + (n >> 1)), 16384);
                        TMA_WO(st + n * 8192u, &tmWo, hg * 128 + (n & 1) * 64, (2 * hg + (n >> 1)) * 64, BAR(B_FB + 4 + (n >> 1)));
                    }
                } else if (j == 18) {
                    expect_tx_e(BAR(B_S0), ffn ? 65536 : 32768);
                    #pragma unroll 1
                    for (int i = 0; i < (ffn ? 4 : 2); i++)
                        tma2_ef_e(st + i * 16384u, i < 2 ? &tmX : i == 2 ? &tmG : &tmU, i < 2 ? hg * 128 + i * 64 : pr * 64, i < 2 ? rb * 128 : rank * 512, BAR(B_S0));
                }
                if (j == 1) TS(50);
                par ^= s == 1;
                s = s == 0 ? 2 : s - 1;
                if (j >= 2 && j < 18) {
                    #pragma unroll
                    for (int i = 0; i < 4; i++) stg_fill(clr + i * 512, EMPTY);
                    clr += 2048;
                }
                const int piece = j - PFJ;
                if (ffn && piece >= 0 && piece < PND + 2 * PNG) {
                    if (piece < PND) asm volatile(EL "cp.async.bulk.tensor.3d.shared::cluster.global.mbarrier::complete_tx::bytes [%0], [%1, {0, %3, %4}], [%2];\n}"
                        :: "r"(sb + OFF_DUMMY), "l"(&tmD8), "r"(BAR(B_PF)), "r"(rank * 8), "r"(pr * 64 + piece * PRD) : "memory");
                    else tma2_e(sb + OFF_DUMMY, (piece & 1) ? &tmU8 : &tmG8, pr * 64, rank * 512 + 512 - PRG - ((piece - PND) >> 1) * PRG, BAR(B_PF));
                }
            }
            expect_tx_e(BAR(B_PF), ffn ? PND * PRD * 128 + 2 * PNG * PRG * 16 : 0);
        } else if (w4 == 1) {
            #pragma unroll 1
            for (int it = 0, jb = NW0 / 8; it < POLL_MAX && jb < 16; it++) {
                while (clk32() - cstart < (jb < 4 * NC ? T_COL : T_COL2)) {}
                const int n = min(4, (jb < 4 * NC ? 4 * NC : 16) - jb);
                bulk_load_e(sb + OFF_WPHI, p.s->mp + jb * 128, n * 2048, BAR(B_MP));
                expect_tx_e(BAR(B_MP), n * 2048);
                mbar_wait(BAR(B_MP), it & 1);
                #pragma unroll 1
                for (int q = 0; q < n; q++) {
                    const uint32_t a = sb + OFF_WPHI + q * 2048 + (lane >> 4) * 1024 + (lane & 15) * 16;
                    if (!__all_sync(0xffffffffu, mod_collect(lds128(a), lds128(a + 256), lds128(a + 512), lds128(a + 768), sb, jb, lane, tag2))) break;
                    arrive_many(BAR(B_MOD + jb), bar_count(B_MOD));
                    if (jb == 4) TS(5);
                    if (jb == 15) TS(8);
                    jb++;
                }
            }
            fence_async_smem();
            __syncwarp();
            expect_tx_e(BAR(B_WPHI), 8192);
            tma2_e(sb + OFF_WPHI, &tmPhi, 0, hg * 128, BAR(B_WPHI));
            #pragma unroll 1
            for (int i = 0; i < 4; i++) {
                uint4* rw = p.s->rowh + (rb * 8 + i * 2 + (lane >> 4)) * 128 + hg * 16 + (lane & 15);
                stg_fill(rw, EMPTY); stg_fill(rw + 16384, EMPTY);
                if (lane < 18) stg_fill(p.s->kvf + (hg * 4 + i) * 288 + (lane < 16 ? (rb >> 2) * 64 + (rb & 3) * 8 + (lane >> 3) * 32 + (lane & 7) : 240 + rb * 2 + lane), EMPTY);
            }
            if (hg == 0 && lane < 8) stg_fill(p.s->cand + rb * 8 + lane, 0);
            if (lane < 28) stg_fill(lane < 16 ? p.s->st2 + rb * 128 + hg * 16 + lane : lane < 20 ? p.s->flo + (rb * 16 + hg * 2) * 2 + lane - 16
                                    : p.s->rsc + ((rb * 4 + ((lane - 20) >> 1)) * 8 + hg) * 2 + (lane & 1), 0);
            fence_rel_gpu();
            #pragma unroll 1
            for (int i = 0; i < (ffn ? 9 : 8); i++) {
                uint4* d = (i < 8 ? p.s->os + (rb * 16 + 2 * hg) * 1024 + i * 256 : p.s->yp + pr * 512 + rank * 128) + lane;
                #pragma unroll
                for (int q = 0; q < 4; q++) { stg_fill(d + q * 32, EMPTY); stg_fill(d + (i < 8 ? 128 : 256) + q * 32, EMPTY); }
            }
            TS(36);
        } else {
            const int hw = w4 & 1;
            const uint32_t fb = BAR(B_RF + 2 * hw);
            if (w4 == 2) {
                if (lane < 8) stg_fill(p.s->rest + b * 8 + lane, 0);
                else if (lane < 24 && b >= 32 * NC) stg_fill(p.s->mp + b * 16 + lane - 8, EMPTY);
            }
            bar_sync(3, 320);
            const uint32_t buf = sb + OFF_SP + hw * 8192u;
            #pragma unroll 1
            for (int job = b < 32 * NC; job < 2; job++) {
                const int nr = job ? 8 : 4;
                const int c0 = job ? 2048 + b * 32 : (((b >> 2) & 1) ? 0 : 1024) + (b >> 3) * 64 + hw * 32;
                const int row0 = job ? hw * 512 : (b & 3) * 256;
                while (clk32() - cstart < (job ? T_REST : T_WLATE)) __nanosleep(100);
                float macc[8] = {0.f, 0.f, 0.f, 0.f, 0.f, 0.f, 0.f, 0.f};
                #pragma unroll 1
                for (int q = -2; q < nr; q++) {
                    if (q >= 0) {
                        mbar_wait(fb + (q & 1) * 8, (q >> 1) & 1);
                        const uint32_t sv0 = sb + OFF_SILU + (row0 + q * 64 + g) * 2, wa = buf + (q & 1) * 4096u + lane * 16u;
                        #pragma unroll JUU
                        for (int i = 0; i < 8; i += 2) {
                            const uint32_t s0 = lds16(sv0 + i * 16), s1 = lds16(sv0 + i * 16 + 16);
                            const uint4 w0 = lds128(wa + i * 512u), w1 = lds128(wa + i * 512u + 512u);
                            fma8(macc, w0, bf_lo(s0)); fma8(macc, w1, bf_lo(s1));
                        }
                    }
                    __syncwarp();
                    if (q + 2 < nr) {
                        expect_tx_e(fb + (q & 1) * 8, 4096);
                        TMA_M(buf + (q & 1) * 4096u, &tmR, c0, row0 + (q + 2) * 64, fb + (q & 1) * 8);
                    }
                }
                stsf(sb + OFF_RED0 + (job ? hw * 256 + (c * 8 + g) * 4 : mod_pos(hw * 2 + (c >> 1), g) + (c & 1) * 8), reduce8(macc, lane));
                bar_sync(4, 64);
                if (w4 == 2) {
                    const uint4 u0 = lds128(sb + OFF_RED0 + (lane & 15) * 16), u1 = lds128(sb + OFF_RED0 + 256 + (lane & 15) * 16);
                    const float v0 = __uint_as_float(u0.x) + __uint_as_float(u1.x), v1 = __uint_as_float(u0.y) + __uint_as_float(u1.y);
                    const float v2 = __uint_as_float(u0.z) + __uint_as_float(u1.z), v3 = __uint_as_float(u0.w) + __uint_as_float(u1.w);
                    const uint32_t add = (b >> 5) == 2 ? ONE2 : 0u;
                    if (job == 0) { if (lane < 16) st_ll(p.s->mp + b * 16 + lane, u0.x, u0.y, u0.z, low_bits(__uint_as_float(u0.w), tag2)); TS(13); }
                    else { if (lane < 8) st_ll(p.s->rest + b * 8 + lane, hadd2(pack2(v0, v1), add), hadd2(pack2(v2, v3), add), 0, tag); TS(33); }
                }
                bar_sync(4, 64);
            }
            tmap_prefetch(hw ? &tmWo : &tmG); tmap_prefetch(hw ? &tmU : &tmD); tmap_prefetch(hw ? &tmPhi : &tmO);
        }
        __syncwarp();
        cluster_wait();
        bar_sync(2, 128);
        reg_inc<504 - 2 * CREG>();
        if (w4 == 0) TS(6);
        #pragma unroll 1
        for (int pp = 0; pp < 2; pp++) {
            mbar_wait(BAR(B_PHI + pp), 0);
            if (w4 == 0) TS(pp ? 59 : 52);
            fence_async_smem();
            float o[2][20];
            const uint32_t vb = OFF_V + pp * 16384u;
            const uint64_t dp = mk_desc(sb + (pp ? OFF_PHI1 : OFF_PHI0), 16, 1024, 1), dv = mk_desc(sb + vb, OFF_ONES - vb, 512, 2);
            wg_fence();
            #pragma unroll
            for (int hh = 0; hh < 2; hh++) {
                #pragma unroll
                for (int ks = 0; ks < 8; ks++)
                    wgmma_n40_ss<1, 1>(o[hh], desc_add(dp, hh * 16384 + ks * 2048), desc_raw(dv, (hh * 8 + ks) * (64 - (64 << 16))), ks);
                wg_commit();
            }
            #pragma unroll
            for (int hh = 0; hh < 2; hh++) {
                if (hh) wg_wait<0>(); else wg_wait<1>();
                acc_fence(o[hh]);
                if (hh) arrive_one(BAR(B_KVD + pp));
                if (hh == KVSH && pp && w4 < 2) {
                    mbar_wait(BAR(B_KVD), 0);
                    bulk_load_e(sb + OFF_KVS + w4 * 8192u, p.s->kvp + ((hg * 4 + w4) * 16 + rb) * 512, 8192, BAR(B_RF + w4));
                    expect_tx_e(BAR(B_RF + w4), 8192);
                }
                uint4* dst = p.s->kvp + (((hg * 4 + 2 * pp + hh) * 16 + (t >> 3)) * 16 + rb) * 32 + (t & 7);
                const float (&a)[20] = o[hh];
                #pragma unroll
                for (int k = 0; k < 2; k++) {
                    const uint32_t z = __float_as_uint(a[16 + 2 * k]);
                    st_ll(dst + k * 8, low_byte<1>(a[4 * k], z), low_byte<2>(a[4 * k + 1], z), low_byte<3>(a[4 * k + 2], z), low_bits(a[4 * k + 3], tag2));
                    st_ll(dst + 16 + k * 8, __float_as_uint(a[8 + 4 * k]), __float_as_uint(a[9 + 4 * k]), __float_as_uint(a[10 + 4 * k]), low_bits(a[11 + 4 * k], tag2));
                }
            }
        }
        if (w4 == 0) TS(17);
        {
            uint4* const fin = p.s->kvf + (hg * 4 + w4) * 288;
            {
                const uint4* src = p.s->kvp + ((hg * 4 + w4) * 16 + rb) * 512 + lane;
                uint4 w[16];
                if (w4 >= 2) {
                    const uint32_t c0 = clk32();
                    mbar_wait(BAR(B_KVD + 1), 0);
                    while (clk32() - c0 < KVDLY - (3 - w4) * KVD2) {}
                    if (STG23) {
                        bulk_load_e(sb + OFF_KVS + w4 * 8192u, src - lane, 8192, BAR(B_RF + w4));
                        expect_tx_e(BAR(B_RF + w4), 8192);
                    }
                }
                if (STG23 || w4 < 2) {
                    mbar_wait(BAR(B_RF + w4), 0);
                    if (w4 == 3) TS(58);
                    #pragma unroll
                    for (int i = 0; i < 16; i++) w[i] = lds128(sb + OFF_KVS + w4 * 8192u + i * 512u + lane * 16u);
                } else {
                    #pragma unroll
                    for (int i = 0; i < 16; i++) w[i].w = EMPTY;
                }
                #pragma unroll 1
                for (int it = 0; it < POLL_MAX; it++) {
                    uint32_t bad = 0;
                    #pragma unroll
                    for (int i = 0; i < 16; i++) bad |= w[i].w ^ tag2;
                    if (__all_sync(0xffffffffu, !(bad & 3))) break;
                    #pragma unroll
                    for (int i = 0; i < 16; i++) ld_ll_if(w[i], src + i * 32, !tagged2(w[i].w, tag2));
                }
                if (w4 == 0) TS(18);
                if (w4 == 3) TS(10);
                float s[5], s2[5];
                #pragma unroll
                for (int i = 0; i < 16; i++) {
                    const float z = __uint_as_float(__byte_perm(__byte_perm(w[i].x, w[i].y, 0x0400), w[i].z, 0x4210));
                    float (&a)[5] = (i & 1) ? s2 : s;
                    if (i < 2) { a[0] = __uint_as_float(w[i].x); a[1] = __uint_as_float(w[i].y); a[2] = __uint_as_float(w[i].z); a[3] = __uint_as_float(w[i].w); a[4] = z; }
                    else { a[0] += __uint_as_float(w[i].x); a[1] += __uint_as_float(w[i].y); a[2] += __uint_as_float(w[i].z); a[3] += __uint_as_float(w[i].w); a[4] += z; }
                }
                #pragma unroll
                for (int i = 0; i < 5; i++) s[i] += s2[i];
                char* d = (char*)fin + ((rb >> 2) * 16 + (rb & 3) * 2 + (g & 1)) * 64 + (((lane >> 3) ^ (rb & 3)) << 4) + c * 4;
                st_ll4(d, pack2(s[0], s[1]));
                st_ll4(d + 512, pack2(s[2], s[3]));
                if (lane < 16 && c < 2) st_ll4((char*)fin + 4096 + rb * 32 + (g * 2 + c) * 4, pack2(s[4], s[4]));
            }
            if (w4 == 3) TS(48);
            mbar_wait(BAR(B_PF), 1);
            fence_acq_gpu();
            uint4 v[9];
            #pragma unroll 1
            for (int it = 0; it < POLL_MAX; it++) {
                uint32_t m = 0;
                #pragma unroll
                for (int k = 0; k < 9; k++) v[k] = ld_ll(fin + k * 32 + lane);
                #pragma unroll
                for (int k = 0; k < 9; k++) m = max(m, umax4(v[k]));
                if (__all_sync(0xffffffffu, m != EMPTY)) break;
            }
            #pragma unroll
            for (int k = 0; k < 8; k++) sts128(sb + OFF_SP + w4 * 4096u + k * 512u + lane * 16u, v[k]);
            const uint32_t za = sb + OFF_Z + ((lane >> 3) * 16 + ((lane >> 1) & 3) * 2 + (lane & 1) * 8) * 64u + ((w4 ^ ((lane >> 1) & 3)) << 4);
            sts128(za, make_uint4(v[8].x, v[8].x, v[8].x, v[8].x)); sts128(za + 64, make_uint4(v[8].z, v[8].z, v[8].z, v[8].z));
            __syncwarp();
            arrive_one(BAR(B_KVF + (w4 >> 1)));
            if (w4 == 0) TS(19);
            if (w4 == 3) TS(1);
        }
        if (w4 == 0) {
            const unsigned* f = (const unsigned*)(p.s->flo + (rb * 16 + d_block(hg, lane & 15)) * 2);
            const uint4* const a0 = p.s->os + rb * 16384;
            uint32_t seen = 0;
            uint32_t kb = hg ? 0 : 2, s = 4, freeb = BAR(B_OWN), par = 0;
            fence_rel_gpu();
            arrive_one(BAR(B_REL));
            mbar_wait(BAR(B_OWN), 0);
            #pragma unroll 1
            for (int n = 2; n < 16; n++) {
                if (!((seen >> n) & 1)) {
                    if (n >= 8) asm volatile("ld.acquire.cta.shared.u32 %0, [%1];" : "=r"(seen) : "r"(sb + OFF_SEEN) : "memory");
                    #pragma unroll 1
                    for (int it = 0; it < POLL_MAX && !((seen >> n) & 1); it++) { seen = __ballot_sync(0xffffffffu, ld_rlx(f) == tag); fence_acq_gpu(); }
                }
                mbar_wait(freeb, par);
                TR(64 + n);
                bulk_load_e(sb + OFF_DA + s * 16384u, a0 + kb * 1024, 16384, BAR(B_FA + s));
                expect_tx_e(BAR(B_FA + s), 16384);
                if (n == 2) TS(2);
                TR(16 + n);
                if (n == OGATE) arrive_one(BAR(B_OGO));
                if (n == 5 || n == 6) mbar_wait(BAR(B_PUB + n - 5), 0);
                kb = n == 8 ? 1 : kb + 2;
                if ((kb >> 1) == hg) kb += 2;
                s = (SLOT_A >> (4 * n + 4)) & 7;
                if (n >= 5) { freeb = BAR(B_ED + n - 5); par = 1; } else if (n == 3) freeb = BAR(B_OWN + 1);
            }
        } else if (w4 == 1) {
            if (ffn) { expect_tx_e(BAR(B_GU), 98304); expect_tx_e(BAR(B_WD), 65536); }
            mbar_wait(BAR(B_S0FREE), 0);
            #pragma unroll 1
            for (int n = 2; n < (ffn ? 20 : 16); n++) {
                if (n == BG1) mbar_wait(BAR(B_KVF + 1), 0);
                if (n == BG2) mbar_wait(BAR(B_PUB), 0);
                if (n == BG5) mbar_wait(BAR(B_OGO), 1);
                if (n >= 6) mbar_wait(BAR(B_ED + n - 6), 1);
                if (n < 16) {
                    const uint32_t s = (SLOT_B >> (4 * n)) & 7, bar = BAR(B_FB + s), dst = sb + OFF_DB + s * 16384u;
                    expect_tx_e(bar, 16384);
                    if (MCB && n >= 6) tma2_mc_e(dst + rank * 8192u, &tmWo, hg * 128 + rank * 64, d_block(hg, n) * 64, bar);
                    else { TMA_WO(dst, &tmWo, hg * 128, d_block(hg, n) * 64, bar); TMA_WO(dst + 8192u, &tmWo, hg * 128 + 64, d_block(hg, n) * 64, bar); }
                    if (ffn && n >= GBN && n < GBN + 2) TMA_F(sb + OFF_GB + (n - GBN) * 16384u, n > GBN ? &tmU : &tmG, pr * 64, rank * 512 + 128, BAR(B_GU));
                } else if (n < 18) {
                    if (n == 16) TS(49);
                    TMA_F(sb + OFF_UP0 + (n & 1) * 16384u, (n & 1) ? &tmU : &tmG, pr * 64, rank * 512 + 256, BAR(B_GU));
                    TMA_F(sb + OFF_UP1 + (n & 1) * 16384u, (n & 1) ? &tmU : &tmG, pr * 64, rank * 512 + 384, BAR(B_GU));
                } else {
                    tma3_ef_e(sb + OFF_DN0 + (n & 1) * 16384u, &tmD, pr * 64, rank * 8 + (n & 1) * 2, BAR(B_WD));
                    tma3_ef_e(sb + OFF_DN1 + (n & 1) * 16384u, &tmD, pr * 64, rank * 8 + 4 + (n & 1) * 2, BAR(B_WD));
                }
            }
        } else if (w4 == 3) {
            const unsigned* f = (const unsigned*)(p.s->flo + (rb * 16 + d_block(hg, lane & 15)) * 2);
            uint32_t seen = 0xffff0003u;
            mbar_wait(BAR(B_PUB + 1), 0);
            #pragma unroll 1
            for (int it = 0; it < POLL_MAX && seen != 0xffffffffu; it++) {
                const uint32_t m = seen | __ballot_sync(0xffffffffu, !((seen >> lane) & 1) && ld_rlx(f) == tag);
                if (m != seen) {
                    seen = m;
                    fence_acq_gpu();
                    __syncwarp();
                    asm volatile(EL "st.release.cta.shared.u32 [%0], %1;\n}" :: "r"(sb + OFF_SEEN), "r"(seen) : "memory");
                }
            }
        } else {
            asm volatile("fence.proxy.async.global;" ::: "memory");
            #pragma unroll 1
            for (int q = 0; q < 2; q++) {
                if (q) mbar_wait(BAR(B_OGO), 1);
                mbar_wait(BAR(B_OWN + q), 0);
                fence_async_smem();
                bulk_store_e(p.s->os + (rb * 16 + 2 * hg + q) * 1024, sb + OFF_OWN + q * 16384u, 16384);
                bulk_commit();
                bulk_wait();
                mbar_wait(BAR(B_REL), 0);
                st_flag_e(p.s->flo + (rb * 16 + 2 * hg + q) * 2, tag);
                arrive_one(BAR(B_PUB + q));
                if (q == 0) TS(3);
                TR(q);
            }
            {
                uint4 w[4];
                poll_words<4>(w, p.s->rest + hg * 32 + lane, 256, tag);
                sts64(sb + OFF_PAR + lane * 8, w[2].x, w[2].y); sts64(sb + OFF_PAR + 256 + lane * 8, w[1].x, w[1].y);
                sts64(sb + OFF_PAR + 512 + lane * 8, w[3].x, w[3].y); sts64(sb + OFF_PAR + 768 + lane * 8, w[0].x, w[0].y);
                const uint2 wr = ldg64(p.wr + hg * 128 + lane * 4);
                sts64(sb + OFF_BQ + lane * 8, hmul2(w[2].x, wr.x), hmul2(w[2].y, wr.y));
            }
            float s = 0.f;
            #pragma unroll 1
            for (int i = 0; i < 2; i++) {
                uint4 w[4]; uint2 wr[4];
                #pragma unroll
                for (int q = 0; q < 4; q++) wr[q] = ldg64(p.wr + (lane + 32 * q + 128 * i) * 4);
                poll_words<4>(w, p.s->rest + 512 + i * 128 + lane, 32, tag);
                #pragma unroll
                for (int q = 0; q < 4; q++) { const uint32_t r0 = hmul2(w[q].x, wr[q].x), r1 = hmul2(w[q].y, wr[q].y); s += (bf_lo(r0) + bf_hi(r0)) + (bf_lo(r1) + bf_hi(r1)); }
            }
            __syncwarp();
            #pragma unroll
            for (int m = 16; m >= 1; m >>= 1) s += shfl_x(s, m);
            if (lane == 0) { stsf(sb + OFF_ATOT, s); sts128(sb + OFF_BQ + 272, make_uint4(ONE2, ONE2, ONE2, ONE2)); }
            __syncwarp();
            arrive_one(BAR(B_PAR));
        }
        __syncwarp();
        {
            mbar_wait(BAR(B_PAR), 0);
            const uint4 pa = lds128(sb + OFF_PAR + (lane & 15) * 16), ps = lds128(sb + OFF_PAR + 256 + (lane & 15) * 16);
            const uint4 wr = ldg128(p.wr + hg * 128 + (lane & 15) * 8);
            const float atot = ldsf(sb + OFF_ATOT);
            mbar_wait(BAR(XGATE), 0);
            if (w4 == 0) TS(37);
            uint4 w;
            #pragma unroll 1
            for (int it = 0; it < POLL_MAX; it++) {
                w = ld_ll(p.s->st2 + rb * 128 + t);
                if (__all_sync(0xffffffffu, __uint_as_float(w.w) == 8.0f)) break;
            }
            if (w4 == 0) TS(31);
            uint32_t m2; float rinv;
            ln_final(__uint_as_float(w.x), __uint_as_float(w.y), m2, rinv);
            uint32_t k[1] = {(f2key(fmaf(-bf_lo(m2), atot, __uint_as_float(w.z)) * rinv) & ~0xfffu) | ((2047 - rb * 128 - t) << 1)};
            const uint32_t best0 = pop_max(k), best1 = pop_max(k) | 1u, grp = rb * 4 + w4;
            if (hg == 0 && lane < 2) st_ll(p.s->cand + grp * 2 + lane, best0, best1, 0, tag);
            if (w4 == 3) TS(23);
            const uint32_t row = 127 - (((lane < 16 ? best0 : best1) >> 1) & 127u);
            mbar_wait(BAR(B_X2), 0);
            const uint4 xv = lds128(sb + OFF_OUT + (row >> 3) * 2048u + ((lane >> 3) & 1) * 1024u + (row & 7) * 128u + (((lane ^ row) & 7) << 4));
            sts64(sb + OFF_ST2 + t * 8, m2, __float_as_uint(rinv));
            __syncwarp();
            arrive_one(BAR(B_ST2));
            const uint32_t rm = __shfl_sync(0xffffffffu, m2, row & 31);
            const Recip rr = split_recip(__shfl_sync(0xffffffffu, rinv, row & 31));
            const uint32_t h0 = ln_pair(xv.x, rm, rr, pa.x, ps.x), h1 = ln_pair(xv.y, rm, rr, pa.y, ps.y);
            const uint32_t h2 = ln_pair(xv.z, rm, rr, pa.z, ps.z), h3 = ln_pair(xv.w, rm, rr, pa.w, ps.w);
            uint4* d = p.s->rowh + (grp * 2 + (lane >> 4)) * 128 + hg * 16 + (lane & 15);
            st_ll(d, h0, h1, h2, h3);
            st_ll(d + 16384, xv.x, xv.y, xv.z, xv.w);
            float r = (fmaf(bf_lo(h0), bf_lo(wr.x), bf_hi(h0) * bf_hi(wr.x)) + fmaf(bf_lo(h1), bf_lo(wr.y), bf_hi(h1) * bf_hi(wr.y)))
                    + (fmaf(bf_lo(h2), bf_lo(wr.z), bf_hi(h2) * bf_hi(wr.z)) + fmaf(bf_lo(h3), bf_lo(wr.w), bf_hi(h3) * bf_hi(wr.w)));
            #pragma unroll
            for (int m = 8; m >= 1; m >>= 1) r += shfl_x(r, m);
            if (!(lane & 15)) st_ll(p.s->rsc + (grp * 8 + hg) * 2 + (lane >> 4), __float_as_uint(r), 0, 0, tag);
            if (w4 == 3) TS(24);
        }
        if (w4 == 0) {
            uint4 cv[2];
            poll_words<2>(cv, p.s->cand + lane * 2, 64, tag);
            __syncwarp();
            TS(11);
            const uint32_t ka = min(cv[0].x, cv[1].x), kb = max(cv[0].y, cv[1].y);
            uint32_t k0 = max(cv[0].x, cv[1].x), k1 = max(ka, kb), k2 = min(ka, kb), k3 = min(cv[0].y, cv[1].y), id[4];
            uint4 hv[4][2], sc;
            const uint4* ha[4];
            #pragma unroll
            for (int i = 0; i < 4; i++) {
                const uint32_t m = __reduce_max_sync(0xffffffffu, k0);
                if (k0 == m) { k0 = k1; k1 = k2; k2 = k3; }
                id[i] = (m & 0xfffu) ^ 0xffeu;
                ha[i] = p.s->rowh + ((id[i] >> 6) * 2 + (id[i] & 1)) * 128 + rank * 64 + lane;
                hv[i][0] = ld_ll(ha[i]); hv[i][1] = ld_ll(ha[i] + 32);
            }
            const uint32_t myid = lane < 16 ? (lane < 8 ? id[0] : id[1]) : (lane < 24 ? id[2] : id[3]), row = myid >> 1;
            const uint4* sa = p.s->rsc + ((myid >> 6) * 8 + (lane & 7)) * 2 + (myid & 1);
            sc = ld_ll(sa);
            sts32(sb + OFF_SEL + 32 + (lane >> 3) * 4, row);
            __syncwarp();
            arrive_one(BAR(B_CAND));
            #pragma unroll 1
            for (int it = 0; it < POLL_MAX; it++) {
                uint32_t m = 0;
                #pragma unroll
                for (int i = 0; i < 4; i++) m = max(m, max(hv[i][0].x, hv[i][1].x));
                if (__all_sync(0xffffffffu, m != EMPTY && sc.w == tag)) break;
                #pragma unroll
                for (int i = 0; i < 4; i++) { hv[i][0] = ld_ll(ha[i]); hv[i][1] = ld_ll(ha[i] + 32); }
                sc = ld_ll(sa);
            }
            TS(12);
            #pragma unroll
            for (int i = 0; i < 4; i++) { sts128(sb + OFF_ROWS + i * 1056u + lane * 16u, hv[i][0]); sts128(sb + OFF_ROWS + i * 1056u + 528u + lane * 16u, hv[i][1]); }
            __syncwarp();
            arrive_one(BAR(B_ROWS));
            TS(25);
            float r = __uint_as_float(sc.x);
            r += shfl_x(r, 1); r += shfl_x(r, 2); r += shfl_x(r, 4);
            r = rbf(r);
            const uint32_t key = (f2key(r) & 0xffff0000u) | (0xffffu - row);
            uint32_t kq[1] = {key};
            const uint32_t best0 = pop_max(kq), best1 = pop_max(kq), tok = key == best0 ? 0 : key == best1 ? 1 : 2;
            sts32(sb + OFF_SEL + 48 + (lane >> 3) * 4, tok);
            if (tok < 2) sts128(sb + OFF_SEL + tok * 16, make_uint4(row, (myid >> 6) * 2 + (myid & 1), __float_as_uint(r), 0));
            __syncwarp();
            arrive_one(BAR(B_SEL));
        } else if (w4 == 1) {
            mbar_wait(BAR(B_SEL), 0);
            const uint4 sel = lds128(sb + OFF_SEL + rank * 16);
            const int col = pr * 16 + c * 2 + (lane >> 4) + (lane & 8);
            uint32_t xs, hs; uint4 gw;
            #pragma unroll 1
            for (int it = 0; it < POLL_MAX; it++) {
                const char* a = (const char*)(p.s->rowh + sel.y * 128) + (col >> 1) * 4;
                hs = ld_rlx(a); xs = ld_rlx(a + 262144); gw = ld_ll(p.s->rest + 768 + (col >> 2));
                if (__all_sync(0xffffffffu, hs != EMPTY && xs != EMPTY && gw.w == tag)) break;
            }
            const uint32_t gq = (col & 2) ? gw.y : gw.x;
            const float fx = (col & 1) ? bf_hi(xs) : bf_lo(xs), fh = (col & 1) ? bf_hi(hs) : bf_lo(hs), fg = (col & 1) ? bf_hi(gq) : bf_lo(gq);
            const float sg = rbf(sigmoidf(__uint_as_float(sel.z)));
            const uint4* src = p.s->yp + g * 512 + rank * 256 + pr * 4 + c;
            uint4 w[7];
            #pragma unroll
            for (int i = 0; i < 7; i++) w[i] = make_uint4(0, EMPTY, 0, EMPTY);
            if (ffn) mbar_wait(BAR(YGATE), 0);
            if (YDLY) { const uint32_t c0 = clk32(); while (clk32() - c0 < (ffn ? YDLY : YDLY + 1500)) {} }
            #pragma unroll 1
            for (int it = 0; it < POLL_MAX; it++) {
                bool ok = true;
                #pragma unroll
                for (int i = 0; i < 7; i++) ld_ll_if(w[i], src + i * 4096, !(tagged2(w[i].y, tag2) && tagged2(w[i].w, tag2)));
                #pragma unroll
                for (int i = 0; i < 7; i++) ok = ok && tagged2(w[i].y, tag2) && tagged2(w[i].w, tag2);
                if (__all_sync(0xffffffffu, ok)) break;
            }
            TS(29);
            float y0 = 0.f, y1 = 0.f, y2 = 0.f, y3 = 0.f;
            #pragma unroll
            for (int i = 0; i < 7; i++) { y0 += __uint_as_float(w[i].x); y1 += __uint_as_float(w[i].y); y2 += __uint_as_float(w[i].z); y3 += __uint_as_float(w[i].w); }
            const bool b4 = lane & 16, b3 = lane & 8;
            const float a0 = (b4 ? y2 : y0) + shfl_x(b4 ? y0 : y2, 16), a1 = (b4 ? y3 : y1) + shfl_x(b4 ? y1 : y3, 16);
            float y = (b3 ? a1 : a0) + shfl_x(b3 ? a0 : a1, 8);
            y += shfl_x(y, 4);
            const float upd = rbf(rbf(y) * sg);
            if (!(lane & 4)) p.out[(size_t)sel.x * 1024 + col] = __float2bfloat16(fx + rbf(fg * rbf(fh + upd)));
            if (b == 0 && lane == 0) p.s->done[0] = tag;
            TS(28);
            if (!GS2) GS(6);
        } else if (w4 == 2) {
            mbar_wait(BAR(OUTGATE), 0);
            const uint32_t cg = (lds32(sb + OFF_SEL + 32 + c * 4) >> 3) - rb * 16;
            uint32_t late = __reduce_or_sync(0xffffffffu, cg < 16 ? 1u << cg : 0u);
            mbar_wait(BAR(B_OUTW), 0);
            fence_async_smem();
            #pragma unroll 1
            for (uint32_t i = 0; i < 16; i++)
                if (!((late >> i) & 1))
                    asm volatile(EL "cp.async.bulk.tensor.3d.global.shared::cta.bulk_group [%0, {0, %2, %3}], [%1];\n}"
                        :: "l"(&tmO), "r"(sb + OFF_OUT + i * 2048u), "r"(rb * 128 + i * 8), "r"(hg * 2) : "memory");
            bulk_commit();
            mbar_wait(BAR(B_SEL), 0);
            const uint32_t row0 = lds32(sb + OFF_SEL) - rb * 128, row1 = lds32(sb + OFF_SEL + 16) - rb * 128;
            #pragma unroll 1
            for (; late; late &= late - 1) {
                const uint32_t i = __ffs(late) - 1;
                #pragma unroll 1
                for (uint32_t q = 0; q < 4; q++) {
                    const uint32_t r = q * 2 + (lane >> 4), ch = lane & 15;
                    const uint4 v = lds128(sb + OFF_OUT + i * 2048u + (ch >> 3) * 1024u + r * 128u + (((ch ^ r) & 7) << 4));
                    if (i * 8 + r != row0 && i * 8 + r != row1) stg128(p.out + (size_t)(rb * 128 + i * 8 + r) * 1024 + hg * 128 + ch * 8, v);
                }
            }
            bulk_wait();
            TS(35);
        }
    } else {
        const int w4 = warp & 3, wgi = warp >> 2;
        uint32_t m2[2]; float rinv[2];
        uint32_t tag2;
        {
            const int g = lane >> 2, c = lane & 3, xrow = b * 16 + warp * 2;
            if (b < NW0)
                asm volatile("prefetch.global.L2 [%0];" :: "l"(p.wmod + (size_t)((b & 3) * 256 + tid) * 6144 + (((b >> 2) & 1) ? 0 : 1024) + (b >> 3) * 64));
            const uint2 cv = ldg64(p.c + tid * 4);
            const uint32_t tag = ld_rlx(p.s->done) + 1;
            if (lane < 2) stg_fill(p.s->st1 + xrow + lane, 0);
            if (warp == 0 && lane < 16 && b < 32 * NC) stg_fill(p.s->mp + b * 16 + lane, EMPTY);
            if (tid < 64) { int s = tid >> 2; sts128(sb + OFF_ONES + tid * 16, make_uint4(((tid & 3) == ((s >> 1) & 3)) ? 0x3F80u : 0u, 0, 0, 0)); }
            cluster_arrive();
            reg_inc<CG1>();
            {
                const float c0 = bf_lo(cv.x), c1 = bf_hi(cv.x), c2 = bf_lo(cv.y), c3 = bf_hi(cv.y);
                sts64(sb + OFF_SILU + tid * 8, pack2(c0 * sigmoidf(c0), c1 * sigmoidf(c1)), pack2(c2 * sigmoidf(c2), c3 * sigmoidf(c3)));
            }
            tag2 = tag % 3u;
            bar_sync(0, 384);
            bar_arrive(3, 320);
            if (warp == 0) TS(47);
            if (!GS2 && warp == 1) GS(0);
            #pragma unroll 1
            for (int part = 0; part < 2; part++)
            if (part == (b < NW0)) {
                mbar_wait(BAR(B_XS + (warp >> 1)), 0);
                if (warp == 7) TS(60);
                if (warp == 0) TS(54);
                float sd[2][4], q1[2][4], q2[2][4];
                #pragma unroll
                for (int e = 0; e < 4; e++) { sd[0][e] = sd[1][e] = q1[0][e] = q1[1][e] = q2[0][e] = q2[1][e] = 0.f; }
                #pragma unroll
                for (int i = 0; i < 4; i++) {
                    const uint4 u = lds128(sb + OFF_XS + warp * 4096u + (i * 32 + lane) * 16u), v = lds128(sb + OFF_XS + warp * 4096u + 2048u + (i * 32 + lane) * 16u);
                    mma16816(sd[0], u.x, v.x, u.y, v.y, ONE2, ONE2); mma16816(sd[1], u.z, v.z, u.w, v.w, ONE2, ONE2);
                    mma16816(q1[0], u.x, v.x, u.y, v.y, u.x, u.y); mma16816(q1[1], u.z, v.z, u.w, v.w, u.z, u.w);
                    mma16816(q2[0], u.x, v.x, u.y, v.y, v.x, v.y); mma16816(q2[1], u.z, v.z, u.w, v.w, v.z, v.w);
                }
                if (warp == 0) TS(30);
                const float d0 = __shfl_sync(0xffffffffu, (g & 1) ? q1[0][1] + q1[1][1] : q1[0][0] + q1[1][0], g * 4 + (g >> 1));
                const float d1 = __shfl_sync(0xffffffffu, (g & 1) ? q2[0][3] + q2[1][3] : q2[0][2] + q2[1][2], g * 4 + (g >> 1));
                float sk = (c & 1) ? sd[0][2] + sd[1][2] : sd[0][0] + sd[1][0], qk = (c & 1) ? d1 : d0;
                #pragma unroll
                for (int m = 4; m <= 16; m <<= 1) { sk += shfl_x(sk, m); qk += shfl_x(qk, m); }
                uint32_t mm; float ri;
                ln_final(sk, qk, mm, ri);
                if (lane < 2) st_ll(p.s->st1 + xrow + lane, mm, __float_as_uint(ri), 0, tag);
                if (warp == 0) TS(14);
                if (warp == 7) TS(61);
            } else if (b < 32 * NC) {
                float m[4][4];
                uint32_t sv[4];
                ldsm4(sv[0], sv[1], sv[2], sv[3], sb + OFF_SILU + ((b & 3) * 256 + warp * 32) * 2 + (lane >> 3) * 16);
                mbar_wait(BAR(B_WS + (warp >> 1)), 0);
                if (warp == 7) TS(55);
                #pragma unroll
                for (int tt = 0; tt < 4; tt++) {
                    m[tt][0] = m[tt][1] = m[tt][2] = m[tt][3] = 0.f;
                    #pragma unroll
                    for (int e = 0; e < 2; e++) {
                        uint32_t a0, a1, a2, a3;
                        ldsm4t(a0, a1, a2, a3, sb + OFF_WST + warp * 4096u + (e * 16 + (lane & 7) + ((lane >> 4) << 3)) * 128u + (((2 * tt + ((lane >> 3) & 1)) ^ (lane & 7)) << 4));
                        mma16816(m[tt], a0, a1, a2, a3, sv[2 * e], sv[2 * e + 1]);
                    }
                }
                if (warp == 0) TS(46);
                const uint32_t ra = sb + OFF_RED0 + warp * 256 + mod_pos(c, g);
                stsf(ra, (c & 2) ? ((c & 1) ? m[3][0] : m[2][0]) : ((c & 1) ? m[1][0] : m[0][0]));
                stsf(ra + 8, (c & 2) ? ((c & 1) ? m[3][2] : m[2][2]) : ((c & 1) ? m[1][2] : m[0][2]));
                if (warp != 7) bar_arrive(5, 256);
                else {
                    bar_sync(5, 256);
                    float v0 = 0.f, v1 = 0.f, v2 = 0.f, v3 = 0.f;
                    #pragma unroll
                    for (int w = 0; w < 4; w++) {
                        const uint4 u = lds128(sb + OFF_RED0 + w * 512 + lane * 16);
                        v0 += __uint_as_float(u.x); v1 += __uint_as_float(u.y); v2 += __uint_as_float(u.z); v3 += __uint_as_float(u.w);
                    }
                    v0 += shfl_x(v0, 16); v1 += shfl_x(v1, 16); v2 += shfl_x(v2, 16); v3 += shfl_x(v3, 16);
                    if (lane < 16) st_ll(p.s->mp + b * 16 + lane, __float_as_uint(v0), __float_as_uint(v1), __float_as_uint(v2), low_bits(v3, tag2));
                    TS(45);
                }
            }
            if (!LATEFREE) arrive_one(BAR(B_STFREE));
            cluster_wait();
            uint4 st[2];
            bool need = warp < NW0 / 8;
            #pragma unroll 1
            for (int it = 0; it < POLL_MAX; it++) {
                st[0] = ld_ll(p.s->st1 + rb * 128 + warp * 16 + g); st[1] = ld_ll(p.s->st1 + rb * 128 + warp * 16 + g + 8);
                if (need) {
                    const uint4* src = p.s->mp + (warp * 8 + (lane >> 4) * 4) * 16 + (lane & 15);
                    const uint4 w0 = ld_ll(src), w1 = ld_ll(src + 16), w2 = ld_ll(src + 32), w3 = ld_ll(src + 48);
                    if (__all_sync(0xffffffffu, mod_collect(w0, w1, w2, w3, sb, warp, lane, tag2))) {
                        need = false;
                        arrive_many(BAR(B_MOD + warp), bar_count(B_MOD));
                        if (warp == 0) TS(51);
                    }
                }
                if (__all_sync(0xffffffffu, st[0].w == tag && st[1].w == tag) && !need) break;
            }
            m2[0] = st[0].x; rinv[0] = __uint_as_float(st[0].y); m2[1] = st[1].x; rinv[1] = __uint_as_float(st[1].y);
            if (LATEFREE) arrive_one(BAR(B_STFREE));
            if (warp == 0) TS(4);
        }
        const int lane = lane_id(), g = lane >> 2, c = lane & 3;
        const int srow = warp * 16 + (lane & 15);
        const uint32_t aoff = srow * 128u + ((((lane >> 4) ^ srow) & 7) << 4);
        uint32_t pt[16], qf[32];
        float pp[2][16];
        const uint32_t roff = srow * 128u + ((lane & 7) << 4);
        {
            float accKV[128], accQ[64];
            {
                uint32_t f[2][4], r[4];
                const Recip ri0 = split_recip(rinv[0]), ri1 = split_recip(rinv[1]);
                mbar_wait(BAR(B_F1), 0);
                if (warp == 0) TS(63);
                ldsm4(r[0], r[1], r[2], r[3], sb + OFF_RING + aoff);
                mbar_wait(BAR(B_MOD), 0);
                if (warp == 0) TS(15);
                if (!GS2 && warp == 1) GS(1);
                uint4 md = lds128(sb + OFF_MODS + c * 16);
                int s = 0, sp = 1, par = 0;
                #pragma unroll 1
                for (int j = 0; j < 16; j++) {
                    const int sn = s == 0 ? 2 : s - 1;
                    par ^= s == 1;
                    const uint32_t modb = (JS && wgi && j == JS) ? BAR(B_TURN) : BAR(B_MOD + ((j + 1) & 15));
                    const uint64_t db = mk_desc(sb + OFF_RING + s * 65536u + 16384u, 8192, 1024, 1);
                    #pragma unroll
                    for (int ks = 0; ks < 4; ks++) {
                        uint32_t (&ff)[4] = f[ks & 1];
                        ff[0] = ln_pair(r[0], m2[0], ri0, md.x, md.z); ff[1] = ln_pair(r[1], m2[1], ri1, md.x, md.z);
                        ff[2] = ln_pair(r[2], m2[0], ri0, md.y, md.w); ff[3] = ln_pair(r[3], m2[1], ri1, md.y, md.w);
                        const int kn = (ks + 1) & 3;
                        ldsm4(r[0], r[1], r[2], r[3], sb + OFF_RING + (ks == 3 ? sn : s) * 65536u + (aoff ^ (kn << 5)));
                        md = lds128(sb + OFF_MODS + ((ks == 3 ? j + 1 : j) * 4 + kn) * 64 + c * 16);
                        wg_fence();
                        wgmma_n256_rs<1>(accKV, ff[0], ff[1], ff[2], ff[3], desc_add(db, 16384 + ks * 2048), ks ? 1 : j);
                        wgmma_n128_rs<1>(accQ, ff[0], ff[1], ff[2], ff[3], desc_add(db, ks * 2048), ks ? 1 : j);
                        wg_commit();
                        if (JS && ks == KT) arrive_if(BAR(B_TURN), j == 15 && !wgi);
                        if (ks == 1) mbar_wait(modb, 0);
                        if (ks == 2) { WT0(); mbar_wait(BAR(j < 15 ? B_F1 + sn : B_WPHI), j < 15 ? par : 0);
                        }
                        wg_wait<1>();
                        if (ks == 0) arrive_if(BAR(B_E1 + sp), j);
                    }
                    sp = s; s = sn;
                }
            }
            mbar_wait(BAR(B_E1 + 2), 0);
            wg_wait<0>();
            acc_fence(accKV); acc_fence(accQ);
            arrive_one(BAR(B_E1));
            if (warp == 4) TS(16);
            if (!GS2 && warp == 1) GS(2);
            uint32_t kf[32];
            #pragma unroll
            for (int h = 0; h < 4; h++) {
                if (h == VFIRST) {
                    #pragma unroll
                    for (int i = 0; i < 16; i++) kf[i] = pack2(accKV[2 * i], accKV[2 * i + 1]);
                    phi_issue(pp, kf, sb, 0);
                }
                #pragma unroll
                for (int q = 0; q < 2; q++) {
                    const int o = 64 + 16 * h + 8 * q;
                    stsm4(sb + OFF_V + h * 8192u + srow * 64u + (((2 * q + (lane >> 4)) ^ ((srow >> 1) & 3)) << 4),
                          pack2(accKV[o], accKV[o + 1]), pack2(accKV[o + 2], accKV[o + 3]), pack2(accKV[o + 4], accKV[o + 5]), pack2(accKV[o + 6], accKV[o + 7]));
                }
            }
            #pragma unroll
            for (int i = 16; i < 32; i++) kf[i] = pack2(accKV[2 * i], accKV[2 * i + 1]);
            phi_transpose(pp, pt, sb + OFF_PHI0 + aoff, sb + OFF_PHI0 + (roff ^ ((lane >> 4) << 6)));
            phi_issue(pp, kf + 16, sb, 1);
            #pragma unroll
            for (int i = 0; i < 32; i++) qf[i] = pack2(accQ[2 * i], accQ[2 * i + 1]);
            if (PREWAIT) { wg_wait<0>(); acc_fence(pp[0]); acc_fence(pp[1]); }
        }
        reg_dec<CREG>();
        if (warp == 0) TS(56);
        {
            float cp, cn;
            fm_extrema(pt, cp, cn);
            if (STAG && wgi) { const uint32_t c0 = clk32(); while (clk32() - c0 < STAG) {} }
            #pragma unroll 1
            for (int u = 0; u < 4; u++) {
                const uint32_t cur = sb + ((u & 1) ? OFF_PHI1 : OFF_PHI0);
                float e[64], s[4];
                uint32_t pn[16];
                #pragma unroll
                for (int k = 0; k < 16; k++) {
                    if (k == KW) phi_transpose(pp, pn, cur + aoff, cur + (roff ^ ((lane >> 4) << 6)));
                    const float dep = k >= DEP ? e[33 + 2 * (k >= DEP ? k - DEP : 0)] : 0.f, f0 = bf_lo_after(pt[k], dep), f1 = bf_hi_after(pt[k], dep);
                    e[2 * k] = ex2(fmaf(f0, LOG2E, cp)); e[2 * k + 1] = ex2(fmaf(f1, LOG2E, cp));
                    e[32 + 2 * k] = ex2(fmaf(f0, -LOG2E, cn)); e[33 + 2 * k] = ex2(fmaf(f1, -LOG2E, cn));
                    if (k == 0) { s[0] = e[0]; s[1] = e[1]; s[2] = e[32]; s[3] = e[33]; }
                    else { s[0] += e[2 * k]; s[1] += e[2 * k + 1]; s[2] += e[32 + 2 * k]; s[3] += e[33 + 2 * k]; }
                }
                fm_extrema(pn, cp, cn);
                #pragma unroll
                for (int i = 0; i < 16; i++) pt[i] = pn[i];
                const float sp = s[0] + s[1], sn = s[2] + s[3], r = rcp(sp * sn), rp = r * sn, rn = r * sp;
                #pragma unroll
                for (int i = 0; i < 8; i++) {
                    const float q = i < 4 ? rp : rn;
                    sts128((cur + (lane >> 4) * 16384u + roff) ^ (i << 4), make_uint4(pack2(e[8 * i] * q, e[8 * i + 1] * q), pack2(e[8 * i + 2] * q, e[8 * i + 3] * q),
                                                                                   pack2(e[8 * i + 4] * q, e[8 * i + 5] * q), pack2(e[8 * i + 6] * q, e[8 * i + 7] * q)));
                }
                __syncwarp();
                arrive_one(BAR(B_PHI + u));
                if (u == 0) { mbar_wait(BAR(B_E1 + 1), 0); phi_issue(pp, qf, sb, 0); }
                else {
                    if (KPAUSE) mbar_wait(BAR(B_PHI + 1), 0);
                    mbar_wait(BAR(B_KVD + (u != 1)), 0);
                    if (u == 1) phi_issue(pp, qf + 16, sb, 1);
                }
            }
            wg_wait<0>();
        }
        if (warp == 4) TS(57);
        if (!GS2 && warp == 1) GS(3);
        uint32_t x2[16][2], wf[32][4];
        const uint32_t woff = ((lane >> 3) & 1) * 16384u + ((lane & 7) + ((lane >> 4) << 3)) * 128u + (((warp ^ lane) & 7) << 4);
        mbar_wait(BAR(B_S0), 0);
        #pragma unroll
        for (int q = 0; q < 8; q++) {
            ldsm4(x2[2 * q][0], x2[2 * q][1], x2[2 * q + 1][0], x2[2 * q + 1][1], sb + OFF_XT + (q >> 2) * 16384u + (aoff ^ ((q & 3) << 5)));
            ldsm4t(wf[q][0], wf[q][1], wf[q][2], wf[q][3], sb + OFF_GA + q * 2048u + woff);
        }
        __syncwarp();
        arrive_one(BAR(B_S0FREE));
        #pragma unroll 1
        for (int pp = 0; pp < 2; pp++) {
            float o0[20], o1[20];
            const uint64_t dk = mk_desc(sb + OFF_SP + pp * 8192u, OFF_Z - OFF_SP - pp * 8160u, 512, 2);
            const uint64_t dq = mk_desc(sb + (pp ? OFF_PHI1 : OFF_PHI0) + wgi * 8192u, 16, 1024, 1);
            mbar_wait(BAR(B_PHI + 2 + pp), 0);
            mbar_wait(BAR(B_KVF + pp), 0);
            fence_async_smem();
            wg_fence();
            #pragma unroll
            for (int ks = 0; ks < 4; ks++) {
                wgmma_n40_ss<0, 1>(o0, desc_add(dq, ks * 32), desc_add(dk, ks * 1024), ks);
                wgmma_n40_ss<0, 1>(o1, desc_add(dq, 16384 + ks * 32), desc_raw(dk, 256 + ks * 64 - (255 << 16)), ks);
            }
            wg_commit();
            wg_wait<0>();
            acc_fence(o0); acc_fence(o1);
            #pragma unroll
            for (int hh = 0; hh < 2; hh++) {
                const float (&o)[20] = hh ? o1 : o0;
                const Recip rd0 = split_recip(rcp(rbf(rbf(o[16]) + 1e-6f)));
                const Recip rd1 = split_recip(rcp(rbf(rbf(o[18]) + 1e-6f)));
                uint32_t op[8];
                #pragma unroll
                for (int j = 0; j < 4; j++) { op[2 * j] = hdiv2(pack2(o[4 * j], o[4 * j + 1]), rd0); op[2 * j + 1] = hdiv2(pack2(o[4 * j + 2], o[4 * j + 3]), rd1); }
                #pragma unroll
                for (int q = 0; q < 2; q++) stsm4(sb + OFF_OWN + pp * 16384u + (aoff ^ ((2 * hh + q) << 5)), op[4 * q], op[4 * q + 1], op[4 * q + 2], op[4 * q + 3]);
            }
            __syncwarp();
            arrive_one(BAR(B_OWN + pp));
            if (warp == 0) TS(20 + pp);
        }
        const uint32_t ooff = sb + OFF_OUT + (srow >> 3) * 1024u + aoff;
        {
            float acc[64];
            const uint32_t vchk = lane * 32u + g * 4u;
            if (!GS2 && warp == 1) GS(4);
            mbar_wait(BAR(B_OWN + 1), 0);
            fence_async_smem();
            const uint64_t da0 = mk_desc(sb + OFF_DA + wgi * 8192u, 16, 1024, 1), db0 = mk_desc(sb + OFF_DB, 8192, 1024, 1);
            #pragma unroll 1
            for (int n = 0; n < 16; n++) {
                const uint32_t s = (SLOT_A >> (4 * n)) & 7, sB = (SLOT_B >> (4 * n)) & 7;
                WT0();
                mbar_wait(BAR(B_FB + sB), (PAR_B >> n) & 1);
                WTJ(16 + n);
                mbar_wait(BAR(n < 2 ? B_OWN + n : B_FA + s), (PAR_A >> n) & 1);
                WTJ(n);
                {
                    const uint32_t ra = sb + OFF_DA + s * 16384u + warp * 2048u;
                    if (__any_sync(0xffffffffu, max(lds32(ra + vchk), lds32(ra + vchk + 1024)) == EMPTY)) {
                        #pragma unroll 1
                        for (int i = 0; i < 4; i++) {
                            uint4 v;
                            #pragma unroll 1
                            for (int it = 0; it < POLL_MAX; it++) {
                                v = ld_ll(p.s->os + (rb * 16 + d_block(hg, n)) * 1024 + warp * 128 + i * 32 + lane);
                                if (umax4(v) != EMPTY) break;
                            }
                            sts128(ra + i * 512 + lane * 16, v);
                        }
                        fence_async_smem();
                        __syncwarp();
                    }
                }
                TR(32 + 16 * wgi + n);
                const uint64_t da = desc_add(da0, s * 16384u), db = desc_add(db0, sB * 16384u);
                wg_fence();
                #pragma unroll
                for (int ks = 0; ks < 4; ks++) wgmma_n128_ss<0, 1>(acc, desc_add(da, ks * 32), desc_add(db, ks * 2048), ks ? 1 : n);
                wg_commit();
                wg_wait<1>();
                if (MCB) arrive_both_if(BAR(B_ED - 1 + n), n); else arrive_if(BAR(B_ED - 1 + n), n);
            }
            mbar_wait(BAR(B_PAR), 0);
            uint32_t gar[16], bfr[16];
            #pragma unroll
            for (int j = 0; j < 16; j += 4) {
                ldsm4(gar[j], gar[j + 1], gar[j + 2], gar[j + 3], sb + OFF_PAR + 768 + (j + (lane >> 3)) * 16);
                ldsm4(bfr[j], bfr[j + 1], bfr[j + 2], bfr[j + 3], sb + OFF_BQ + ((lane & 1) ? (j + (lane >> 3)) * 16 : 272));
            }
            wg_wait<0>();
            acc_fence(acc);
            bar_arrive(6 + wgi, 256);
            if (warp == 0) TS(9);
            if (!GS2 && warp == 1) GS(5);
            float sd[2][4], q1[2][4], q2[2][4];
            #pragma unroll
            for (int e = 0; e < 4; e++) { sd[0][e] = sd[1][e] = q1[0][e] = q1[1][e] = q2[0][e] = q2[1][e] = 0.f; }
            #pragma unroll
            for (int s = 0; s < 8; s++) {
                #pragma unroll
                for (int e = 0; e < 4; e++) { const int j = 2 * s + (e >> 1), h = e & 1; x2[j][h] = hadd2(x2[j][h], hmul2(gar[j], pack2(acc[4 * j + 2 * h], acc[4 * j + 2 * h + 1]))); }
                mma16816(sd[s & 1], x2[2 * s][0], x2[2 * s][1], x2[2 * s + 1][0], x2[2 * s + 1][1], bfr[2 * s], bfr[2 * s + 1]);
                #pragma unroll
                for (int e = 0; e < 2; e++) { mma1688(q1[e], x2[2 * s + e][0], x2[2 * s + e][1], x2[2 * s + e][0]); mma1688(q2[e], x2[2 * s + e][0], x2[2 * s + e][1], x2[2 * s + e][1]); }
            }
            if (c == (g >> 1)) {
                uint4* d = p.s->st2 + rb * 128 + warp * 16 + g;
                red_add4(d, sd[0][0] + sd[1][0], (g & 1) ? q1[0][1] + q1[1][1] : q1[0][0] + q1[1][0], sd[0][1] + sd[1][1], 1.0f);
                red_add4(d + 8, sd[0][2] + sd[1][2], (g & 1) ? q2[0][3] + q2[1][3] : q2[0][2] + q2[1][2], sd[0][3] + sd[1][3], 1.0f);
            }
            arrive_one(BAR(B_RED));
            if (warp == 0) TS(22);
            bar_sync(7 - wgi, 256);
            #pragma unroll
            for (int q = 0; q < 8; q++) stsm4((ooff + (q >> 2) * 1024u) ^ ((q & 3) << 5), x2[2 * q][0], x2[2 * q][1], x2[2 * q + 1][0], x2[2 * q + 1][1]);
            __syncwarp();
            arrive_one(BAR(B_X2));
            if (warp == 0) TS(62);
        }
        const uint32_t xa = sb + OFF_OUT + warp * 4096u + ((lane >> 3) & 1) * 1024u + (lane >> 4) * 128u + (((lane ^ (lane >> 4)) & 7) << 4);
        const uint4 pa = lds128(sb + OFF_PAR + (lane & 15) * 16), ps = lds128(sb + OFF_PAR + 256 + (lane & 15) * 16), pg = lds128(sb + OFF_PAR + 512 + (lane & 15) * 16);
        if (ffn) mbar_wait(BAR(B_GU), 0);
        if (warp == 0) TS(38);
        #pragma unroll
        for (int q = 8; q < NEARLY; q++) {
            ldsm4t(wf[q][0], wf[q][1], wf[q][2], wf[q][3], sb + (q < 16 ? OFF_GB : q < 24 ? OFF_UP0 : OFF_UP1) + (q & 7) * 2048u + woff);
            if (LPACE && (q & 1)) { const uint32_t c0 = clk32(); while (clk32() - c0 < LPACE) {} }
        }
        {
            if (warp == 0) TS(39);
            mbar_wait(BAR(B_ST2), 0);
            if (warp == 0) TS(53);
            #pragma unroll 1
            for (int q0 = 0; q0 < 8; q0 += OUU) {
                uint4 x[OUU]; uint2 st[OUU];
                const uint32_t a = (xa + (q0 >> 2) * 2048u + (q0 & 3) * 256u) ^ ((q0 & 3) << 5);
                #pragma unroll
                for (int q = 0; q < OUU; q++) { x[q] = lds128((a + q * 256u) ^ (q << 5)); st[q] = lds64(sb + OFF_ST2 + (warp * 16 + (q0 + q) * 2 + (lane >> 4)) * 8); }
                #pragma unroll
                for (int q = 0; q < OUU; q++) {
                    const Recip r = split_recip(__uint_as_float(st[q].y));
                    sts128((a + q * 256u) ^ (q << 5), make_uint4(
                        hadd2(x[q].x, hmul2(pg.x, ln_pair(x[q].x, st[q].x, r, pa.x, ps.x))), hadd2(x[q].y, hmul2(pg.y, ln_pair(x[q].y, st[q].x, r, pa.y, ps.y))),
                        hadd2(x[q].z, hmul2(pg.z, ln_pair(x[q].z, st[q].x, r, pa.z, ps.z))), hadd2(x[q].w, hmul2(pg.w, ln_pair(x[q].w, st[q].x, r, pa.w, ps.w)))));
                }
            }
            __syncwarp();
            arrive_one(BAR(B_OUTW));
            if (warp == 0) TS(32);
        }
        if (ffn) {
            float acc[4][4];
            uint32_t df[4][4][4];
            {
                #pragma unroll
                for (int i = 0; i < 4; i++) { acc[i][0] = acc[i][1] = acc[i][2] = acc[i][3] = 0.f; }
                const uint32_t da = sb + (wgi ? OFF_DN1 : OFF_DN0) + w4 * 8192u + ((lane & 7) + ((lane >> 4) << 3)) * 128u;
                #pragma unroll
                for (int q = NEARLY; q < 32; q++) ldsm4t(wf[q][0], wf[q][1], wf[q][2], wf[q][3], sb + (q < 16 ? OFF_GB : q < 24 ? OFF_UP0 : OFF_UP1) + (q & 7) * 2048u + woff);
                mbar_wait(BAR(B_WD), 0);
                #pragma unroll
                for (int q = 0; q < DNE; q++)
                    ldsm4t(df[q >> 2][q & 3][0], df[q >> 2][q & 3][1], df[q >> 2][q & 3][2], df[q >> 2][q & 3][3], da + (q & 3) * 2048u + (((2 * (q >> 2) + ((lane >> 3) & 1)) ^ (lane & 7)) << 4));
                mbar_wait(BAR(B_ROWS), 0);
                #pragma unroll
                for (int q = 0; q < 8; q++) {
                    uint32_t b0, b1, b2, b3;
                    ldsm4(b0, b1, b2, b3, sb + OFF_ROWS + (lane & 7) * 528u + (lane >> 3) * 16u + q * 64u);
                    #pragma unroll
                    for (int hf = 0; hf < 2; hf++) {
                        const int k = 16 * hf + 2 * q;
                        mma16816(acc[2 * hf], wf[k][0], wf[k][1], wf[k][2], wf[k][3], b0, b1);
                        mma16816(acc[2 * hf + 1], wf[k + 1][0], wf[k + 1][1], wf[k + 1][2], wf[k + 1][3], b2, b3);
                    }
                }
                const float gs = (acc[0][0] + acc[1][0]) + (acc[2][1] + acc[3][1]), us = (acc[0][2] + acc[1][2]) + (acc[2][3] + acc[3][3]);
                st_partner64(sb + OFF_PX + warp * 256 + lane * 8, BAR(B_PX), rank ^ 1, gs, us);
                if (warp == 0) TS(34);
                #pragma unroll
                for (int q = DNE; q < 16; q++)
                    ldsm4t(df[q >> 2][q & 3][0], df[q >> 2][q & 3][1], df[q >> 2][q & 3][2], df[q >> 2][q & 3][3], da + (q & 3) * 2048u + (((2 * (q >> 2) + ((lane >> 3) & 1)) ^ (lane & 7)) << 4));
                mbar_wait(BAR(B_SEL), 0);
                const uint32_t tok = lds32(sb + OFF_SEL + 48 + c * 4);
                mbar_wait(BAR(B_PX), 0);
                const uint2 q = lds64(sb + OFF_PX + warp * 256 + lane * 8);
                float gt = rbf(gs + __uint_as_float(q.x));
                gt = rbf(gt * sigmoidf(gt));
                if (tok < 2) sts16(sb + OFF_HID + tok * 144 + (warp * 8 + g) * 2, pack2(gt * rbf(us + __uint_as_float(q.y)), 0.f));
            }
            if (warp == 0) TS(26);
            bar_sync(1, 256);
            uint32_t bh[8];
            ldsm4(bh[0], bh[1], bh[2], bh[3], sb + OFF_HID + (lane & 1) * 144u + (lane >> 3) * 16u);
            ldsm4(bh[4], bh[5], bh[6], bh[7], sb + OFF_HID + (lane & 1) * 144u + (lane >> 3) * 16u + 64u);
            float y[4][4];
            #pragma unroll
            for (int tt = 0; tt < 4; tt++) { y[tt][0] = y[tt][1] = y[tt][2] = y[tt][3] = 0.f; }
            #pragma unroll
            for (int ks = 0; ks < 4; ks++)
                #pragma unroll
                for (int tt = 0; tt < 4; tt++) mma16816(y[tt], df[tt][ks][0], df[tt][ks][1], df[tt][ks][2], df[tt][ks][3], bh[2 * ks], bh[2 * ks + 1]);
            float e[4];
            #pragma unroll
            for (int i = 0; i < 4; i++) e[i] = (c & 2) ? ((c & 1) ? y[3][i] : y[2][i]) : ((c & 1) ? y[1][i] : y[0][i]);
            char* d = (char*)(p.s->yp + pr * 512 + rank * 128 + (warp * 4 + c) * 4) + g * 8;
            st_ll8(d, __float_as_uint(e[0]), low_bits(e[2], tag2));
            st_ll8(d + 4096, __float_as_uint(e[1]), low_bits(e[3], tag2));
            arrive_one(BAR(B_YP));
            if (warp == 0) TS(27);
        }
    }
}

typedef CUresult (*EncodeFn)(CUtensorMap*, CUtensorMapDataType, cuuint32_t, void*, const cuuint64_t*, const cuuint64_t*, const cuuint32_t*,
                             const cuuint32_t*, CUtensorMapInterleave, CUtensorMapSwizzle, CUtensorMapL2promotion, CUtensorMapFloatOOBfill);

CUtensorMap make_map(EncodeFn enc, const void* ptr, uint64_t cols, uint64_t rows, uint32_t bc, uint32_t br, CUtensorMapSwizzle swz, CUtensorMapL2promotion promo) {
    CUtensorMap m;
    cuuint64_t dims[2] = {cols, rows}, strides[1] = {cols * 2};
    cuuint32_t box[2] = {bc, br}, es[2] = {1, 1};
    enc(&m, CU_TENSOR_MAP_DATA_TYPE_BFLOAT16, 2, const_cast<void*>(ptr), dims, strides, box, es, CU_TENSOR_MAP_INTERLEAVE_NONE, swz, promo,
        CU_TENSOR_MAP_FLOAT_OOB_FILL_NONE);
    return m;
}
CUtensorMap make_block_map(EncodeFn enc, const void* ptr, uint32_t sections, uint64_t rows, uint32_t br, CUtensorMapL2promotion promo) {
    CUtensorMap m;
    cuuint64_t dims[4] = {64, rows, 16, sections}, strides[3] = {sections * 2048ull, 128, 2048};
    cuuint32_t box[4] = {64, br, 2, sections}, es[4] = {1, 1, 1, 1};
    enc(&m, CU_TENSOR_MAP_DATA_TYPE_BFLOAT16, sections > 1 ? 4 : 3, const_cast<void*>(ptr), dims, strides, box, es, CU_TENSOR_MAP_INTERLEAVE_NONE,
        CU_TENSOR_MAP_SWIZZLE_128B, promo, CU_TENSOR_MAP_FLOAT_OOB_FILL_NONE);
    return m;
}

}

extern "C" void kernel_launch(void* const* d_in, const int* in_sizes, int n_in, void* d_out, int out_size) {
    (void)in_sizes; (void)n_in; (void)out_size;
    void* fn = nullptr; cudaDriverEntryPointQueryResult qr;
    cudaGetDriverEntryPoint("cuTensorMapEncodeTiled", &fn, cudaEnableDefault, &qr);
    EncodeFn enc = (EncodeFn)fn;
    void* hs = nullptr;
    cudaGetSymbolAddress(&hs, g_scratch);
    const CUtensorMapL2promotion P256 = CU_TENSOR_MAP_L2_PROMOTION_L2_256B, P128 = CU_TENSOR_MAP_L2_PROMOTION_L2_128B;
    CUtensorMap tmW = make_block_map(enc, d_in[1], 3, 1024, 64, P256);
    CUtensorMap tmWo = make_map(enc, d_in[3], 1024, 1024, 64, 64, CU_TENSOR_MAP_SWIZZLE_128B, P256);
    CUtensorMap tmPhi = make_map(enc, d_in[2], 32, 1024, 32, 128, CU_TENSOR_MAP_SWIZZLE_64B, P128);
    CUtensorMap tmG = make_map(enc, d_in[6], 3584, 1024, 64, 128, CU_TENSOR_MAP_SWIZZLE_128B, P128);
    CUtensorMap tmU = make_map(enc, d_in[7], 3584, 1024, 64, 128, CU_TENSOR_MAP_SWIZZLE_128B, P128);
    CUtensorMap tmD = make_block_map(enc, d_in[8], 1, 3584, 64, P128);
    CUtensorMap tmX = make_map(enc, d_in[0], 1024, 2048, 64, 128, CU_TENSOR_MAP_SWIZZLE_128B, P128);
    CUtensorMap tmO = make_block_map(enc, d_out, 1, 2048, 8, P128);
    CUtensorMap tmM = make_map(enc, d_in[10], 6144, 1024, 64, 64, CU_TENSOR_MAP_SWIZZLE_128B, P128);
    CUtensorMap tmR = make_map(enc, d_in[10], 6144, 1024, 32, 64, CU_TENSOR_MAP_SWIZZLE_NONE, P128);
    CUtensorMap tmG8 = make_map(enc, d_in[6], 3584, 1024, 8, PRG, CU_TENSOR_MAP_SWIZZLE_NONE, P128);
    CUtensorMap tmU8 = make_map(enc, d_in[7], 3584, 1024, 8, PRG, CU_TENSOR_MAP_SWIZZLE_NONE, P128);
    CUtensorMap tmD8;
    {
        cuuint64_t dims[3] = {64, 16, 3584}, strides[2] = {128, 2048};
        cuuint32_t box[3] = {8, 8, PRD}, es[3] = {1, 1, 1};
        enc(&tmD8, CU_TENSOR_MAP_DATA_TYPE_BFLOAT16, 3, d_in[8], dims, strides, box, es, CU_TENSOR_MAP_INTERLEAVE_NONE, CU_TENSOR_MAP_SWIZZLE_NONE, P128,
            CU_TENSOR_MAP_FLOAT_OOB_FILL_NONE);
    }
    Ptrs p;
    p.x = (const bf16*)d_in[0]; p.c = (const bf16*)d_in[9]; p.wmod = (const bf16*)d_in[10]; p.wr = (const bf16*)d_in[5];
    p.wg = (const bf16*)d_in[6]; p.wu = (const bf16*)d_in[7]; p.wd = (const bf16*)d_in[8]; p.out = (bf16*)d_out; p.s = (Scratch*)hs;
    p.wqkv = (const bf16*)d_in[1]; p.wo = (const bf16*)d_in[3];
    cudaFuncSetAttribute(fused_kernel, cudaFuncAttributeMaxDynamicSharedMemorySize, SMEM_BYTES);
    fused_kernel<<<128, NTHREADS, SMEM_BYTES, cudaStreamPerThread>>>(p, tmW, tmWo, tmPhi, tmG, tmU, tmD, tmX, tmO, tmM, tmR, tmG8, tmU8, tmD8);
}
```

```cpp
#include <cuda_runtime.h>
#include <cuda.h>
#include <cuda_bf16.h>
#include <stdint.h>

namespace {

typedef __nv_bfloat16 bf16;

constexpr int NTHREADS = 384;
constexpr int POLL_MAX = 400000;
constexpr uint32_t EMPTY = 0xffffffffu;

#define PND 6
#define PNG 5
constexpr int PRD = (64 + PND - 1) / PND, PRG = (384 + PNG - 1) / PNG;
constexpr uint32_t OFF_RING = 0;
constexpr uint32_t OFF_XS   = 65536;
constexpr uint32_t OFF_WST  = 98304;
constexpr uint32_t OFF_XT   = 0;
constexpr uint32_t OFF_GA   = 32768;
constexpr uint32_t OFF_PHI0 = 163840, OFF_PHI1 = 98304;
constexpr uint32_t OFF_V    = 131072;
constexpr uint32_t OFF_KVS  = 131072;
constexpr uint32_t OFF_DB   = 0;
constexpr uint32_t OFF_DA   = 98304;
constexpr uint64_t SLOT_A   = 0x5432105432105432ull, SLOT_B = 0x1054321054321054ull;
constexpr uint32_t PAR_A    = 0x3f00, PAR_B = 0x0fc0;
constexpr uint32_t OFF_OWN  = OFF_DA + 32768;
constexpr uint32_t OFF_OUT  = OFF_DA + 65536;
constexpr uint32_t OFF_UP0  = OFF_DA, OFF_UP1 = OFF_DB + 32768, OFF_DN0 = OFF_DA + 32768, OFF_DN1 = OFF_DB + 65536;
constexpr uint32_t OFF_WPHI = 196608;
constexpr uint32_t OFF_SP   = 204800;
constexpr uint32_t OFF_Z    = 221184;
constexpr uint32_t OFF_ONES = 225280;
constexpr uint32_t OFF_MODS = 226304;
constexpr uint32_t OFF_GB   = 196608;
constexpr uint32_t OFF_BQ   = 229376;
constexpr uint32_t OFF_ATOT = OFF_BQ + 256;
constexpr uint32_t OFF_BAR  = 230400;
constexpr uint32_t OFF_SEEN = OFF_BAR + 632;
constexpr uint32_t OFF_PAR  = OFF_BAR + 640;
constexpr uint32_t SMEM_BYTES = 232448;
constexpr uint32_t OFF_SILU = OFF_Z;
constexpr uint32_t OFF_RED0 = OFF_Z + 2048;
constexpr uint32_t OFF_DUMMY = OFF_RED0 + 512;
constexpr uint32_t OFF_ST2  = OFF_DB;
constexpr uint32_t OFF_SEL  = OFF_ST2 + 1024;
constexpr uint32_t OFF_ROWS = OFF_ST2 + 2048;
constexpr uint32_t OFF_PX   = OFF_ROWS + 4608;
constexpr uint32_t OFF_HID  = OFF_PX + 2048;

enum {
    B_F1 = 0, B_E1 = 3, B_STFREE = 6, B_WPHI = 7, B_FA = 8, B_FB = 14, B_RF = 20, B_KVD = 24, B_PAR = 26, B_S0 = 27, B_GU = 28, B_WD = 29,
    B_X2 = 30, B_ST2 = 31, B_CAND = 32,
    B_MP = 33, B_MOD = 34, B_PX = 50, B_S0FREE = 51, B_PHI = 52, B_OUTW = 56, B_PUB = 57, B_KVF = 59, B_OWN = 61, B_REL = 63, B_ROWS = 64, B_SEL = 65, B_YP = 66, B_RED = 67, B_TURN = 68,
    B_XS = 69,
    B_WS = 73, B_COUNT = 77,
    B_ED = B_MOD, B_OGO = B_XS + 2, B_PF = B_XS + 3
};

struct Scratch {
    uint4 os[256 * 1024];
    uint4 kvp[32 * 256 * 32];
    uint4 kvf[32 * 288];
    uint4 st1[2048];
    uint4 mp[128 * 16];
    uint4 rest[1024];
    uint4 flo[256 * 2];
    uint4 st2[2048];
    uint4 cand[64 * 2];
    uint4 rowh[128 * 128];
    uint4 rowx[128 * 128];
    uint4 rsc[64 * 8 * 2];
    uint4 yp[56 * 512];
    unsigned done[4];
};
__device__ __align__(1024) Scratch g_scratch;
#define TS(i) do {} while (0)
#undef GS
#define GS(i)
#define TR(i)
#define TRL(i)
#define WT0()
#define WTJ(j)

__device__ __forceinline__ uint32_t smem_u32(const void* p) { return (uint32_t)__cvta_generic_to_shared(p); }
__device__ __forceinline__ int lane_id() { int l; asm volatile("mov.u32 %0, %%laneid;" : "=r"(l)); return l; }
__device__ __forceinline__ uint32_t clk32() { uint32_t c; asm volatile("mov.u32 %0, %%clock;" : "=r"(c) :: "memory"); return c; }
__device__ __forceinline__ void arrive_one(uint32_t bar) {
    asm volatile("{\n.reg .pred p;\nelect.sync _|p, 0xffffffff;\n@p mbarrier.arrive.shared::cta.b64 _, [%0];\n}" :: "r"(bar) : "memory");
}
__device__ __forceinline__ void arrive_many(uint32_t bar, uint32_t n) {
    asm volatile("{\n.reg .pred p;\nelect.sync _|p, 0xffffffff;\n@p mbarrier.arrive.shared::cta.b64 _, [%0], %1;\n}" :: "r"(bar), "r"(n) : "memory");
}
__device__ __forceinline__ void arrive_if(uint32_t bar, uint32_t on) {
    asm volatile("{\n.reg .pred q, p;\nelect.sync _|q, 0xffffffff;\nsetp.ne.and.u32 p, %1, 0, q;\n@p mbarrier.arrive.shared::cta.b64 _, [%0];\n}" :: "r"(bar), "r"(on) : "memory");
}
__device__ __forceinline__ void arrive_both_if(uint32_t bar, uint32_t on) {
    asm volatile("{\n.reg .pred q, p;\n.reg .b32 r0, r1;\nelect.sync _|q, 0xffffffff;\nsetp.ne.and.u32 p, %1, 0, q;\n"
        "mapa.shared::cluster.u32 r0, %0, 0;\nmapa.shared::cluster.u32 r1, %0, 1;\n"
        "@p mbarrier.arrive.shared::cluster.b64 _, [r0];\n@p mbarrier.arrive.shared::cluster.b64 _, [r1];\n}" :: "r"(bar), "r"(on) : "memory");
}
__device__ __forceinline__ void st_partner64(uint32_t a, uint32_t bar, uint32_t cta, float x, float y) {
    asm volatile("{\n.reg .b32 ra, rb;\nmapa.shared::cluster.u32 ra, %0, %2;\nmapa.shared::cluster.u32 rb, %1, %2;\n"
        "st.async.weak.shared::cluster.mbarrier::complete_tx::bytes.v2.f32 [ra], {%3, %4}, [rb];\n}" :: "r"(a), "r"(bar), "r"(cta), "f"(x), "f"(y) : "memory");
}
__device__ __forceinline__ void mbar_wait(uint32_t bar, uint32_t parity) {
#define WAITV 1
    asm volatile("{\n.reg .pred P1;\n.reg .u32 cnt;\nmbarrier.try_wait.parity.shared::cta.b64 P1, [%0], %1;\n@P1 bra DONE;\nmov.u32 cnt, 0;\nLAB_WAIT:\n"
        "mbarrier.try_wait.parity.shared::cta.b64 P1, [%0], %1;\n@P1 bra DONE;\n"
        "add.u32 cnt, cnt, 1;\nsetp.lt.u32 P1, cnt, 1000000;\n@P1 bra LAB_WAIT;\ntrap;\nDONE:\n}" :: "r"(bar), "r"(parity) : "memory");
}
__device__ __forceinline__ uint64_t policy_evict_first() { uint64_t p; asm("createpolicy.fractional.L2::evict_first.b64 %0, 1.0;" : "=l"(p)); return p; }
#define EF_W 1
#define EF_WO 1
#define EF_F 1
#define EF_M 1
__device__ __forceinline__ void bulk_commit() { asm volatile("cp.async.bulk.commit_group;" ::: "memory"); }
__device__ __forceinline__ void bulk_wait() { asm volatile("cp.async.bulk.wait_group 0;" ::: "memory"); }
__device__ __forceinline__ void tmap_prefetch(const CUtensorMap* tm) { asm volatile("prefetch.tensormap [%0];" :: "l"(tm) : "memory"); }
#define EL "{\n.reg .pred e;\nelect.sync _|e, 0xffffffff;\n@e "
__device__ __forceinline__ void expect_tx_e(uint32_t bar, uint32_t bytes) { asm volatile(EL "mbarrier.arrive.expect_tx.shared::cta.b64 _, [%0], %1;\n}" :: "r"(bar), "r"(bytes) : "memory"); }
__device__ __forceinline__ void tma2_e(uint32_t dst, const CUtensorMap* tm, int c0, int c1, uint32_t bar) {
    asm volatile(EL "cp.async.bulk.tensor.2d.shared::cluster.global.mbarrier::complete_tx::bytes [%0], [%1, {%3, %4}], [%2];\n}"
        :: "r"(dst), "l"(tm), "r"(bar), "r"(c0), "r"(c1) : "memory");
}
__device__ __forceinline__ void tma2_ef_e(uint32_t dst, const CUtensorMap* tm, int c0, int c1, uint32_t bar) {
    asm volatile(EL "cp.async.bulk.tensor.2d.shared::cluster.global.mbarrier::complete_tx::bytes.L2::cache_hint [%0], [%1, {%3, %4}], [%2], %5;\n}"
        :: "r"(dst), "l"(tm), "r"(bar), "r"(c0), "r"(c1), "l"(policy_evict_first()) : "memory");
}
__device__ __forceinline__ void tma2_mc_e(uint32_t dst, const CUtensorMap* tm, int c0, int c1, uint32_t bar) {
    if (!EF_WO) asm volatile(EL "cp.async.bulk.tensor.2d.shared::cluster.global.mbarrier::complete_tx::bytes.multicast::cluster [%0], [%1, {%3, %4}], [%2], %5;\n}"
        :: "r"(dst), "l"(tm), "r"(bar), "r"(c0), "r"(c1), "h"((uint16_t)3) : "memory");
    else
    asm volatile(EL "cp.async.bulk.tensor.2d.shared::cluster.global.mbarrier::complete_tx::bytes.multicast::cluster.L2::cache_hint [%0], [%1, {%3, %4}], [%2], %5, %6;\n}"
        :: "r"(dst), "l"(tm), "r"(bar), "r"(c0), "r"(c1), "h"((uint16_t)3), "l"(policy_evict_first()) : "memory");
}
__device__ __forceinline__ void tma3_ef_e(uint32_t dst, const CUtensorMap* tm, int row, int blk, uint32_t bar) {
    if (!EF_F) asm volatile(EL "cp.async.bulk.tensor.3d.shared::cluster.global.mbarrier::complete_tx::bytes [%0], [%1, {0, %3, %4}], [%2];\n}"
        :: "r"(dst), "l"(tm), "r"(bar), "r"(row), "r"(blk) : "memory");
    else
    asm volatile(EL "cp.async.bulk.tensor.3d.shared::cluster.global.mbarrier::complete_tx::bytes.L2::cache_hint [%0], [%1, {0, %3, %4}], [%2], %5;\n}"
        :: "r"(dst), "l"(tm), "r"(bar), "r"(row), "r"(blk), "l"(policy_evict_first()) : "memory");
}
__device__ __forceinline__ void tma4_e(uint32_t dst, const CUtensorMap* tm, int row, int blk, uint32_t bar, bool ef) {
    if (!ef) asm volatile(EL "cp.async.bulk.tensor.4d.shared::cluster.global.mbarrier::complete_tx::bytes [%0], [%1, {0, %3, %4, 0}], [%2];\n}"
        :: "r"(dst), "l"(tm), "r"(bar), "r"(row), "r"(blk) : "memory");
    else
    asm volatile(EL "cp.async.bulk.tensor.4d.shared::cluster.global.mbarrier::complete_tx::bytes.L2::cache_hint [%0], [%1, {0, %3, %4, 0}], [%2], %5;\n}"
        :: "r"(dst), "l"(tm), "r"(bar), "r"(row), "r"(blk), "l"(policy_evict_first()) : "memory");
}
__device__ __forceinline__ void bulk_load_e(uint32_t dst, const void* src, uint32_t bytes, uint32_t bar) {
    asm volatile(EL "cp.async.bulk.shared::cluster.global.mbarrier::complete_tx::bytes [%0], [%1], %2, [%3];\n}" :: "r"(dst), "l"(src), "r"(bytes), "r"(bar) : "memory");
}
__device__ __forceinline__ void bulk_store_e(void* dst, uint32_t src, uint32_t bytes) {
    asm volatile(EL "cp.async.bulk.global.shared::cta.bulk_group [%0], [%1], %2;\n}" :: "l"(dst), "r"(src), "r"(bytes) : "memory");
}
__device__ __forceinline__ void st_flag_e(void* p, unsigned v) { asm volatile(EL "st.relaxed.gpu.global.u32 [%0], %1;\n}" :: "l"(p), "r"(v) : "memory"); }
__device__ __forceinline__ void mbar_init(uint32_t bar, uint32_t cnt) { asm volatile("mbarrier.init.shared::cta.b64 [%0], %1;" :: "r"(bar), "r"(cnt) : "memory"); }
__device__ __forceinline__ bool elect_one() {
    uint32_t p;
    asm volatile("{\n.reg .pred P;\nelect.sync _|P, 0xffffffff;\nselp.u32 %0, 1, 0, P;\n}" : "=r"(p));
    return p;
}
__device__ __forceinline__ void wg_fence() { asm volatile("wgmma.fence.sync.aligned;" ::: "memory"); }
__device__ __forceinline__ void wg_commit() { asm volatile("wgmma.commit_group.sync.aligned;" ::: "memory"); }
template<int N> __device__ __forceinline__ void wg_wait() { asm volatile("wgmma.wait_group.sync.aligned %0;" :: "n"(N) : "memory"); }
template<int N> __device__ __forceinline__ void acc_fence(float (&d)[N]) {
    #pragma unroll
    for (int i = 0; i < N; i++) asm volatile("" : "+f"(d[i]) :: "memory");
}
__device__ __forceinline__ uint64_t mk_desc(uint32_t addr, uint32_t lbo, uint32_t sbo, uint32_t swz) {
    uint32_t lo = ((addr & 0x3FFFF) >> 4) | (((lbo & 0x3FFFF) >> 4) << 16);
    uint32_t hi = (sbo >> 4) | (swz << 30);
    return ((uint64_t)hi << 32) | lo;
}
__device__ __forceinline__ uint64_t desc_add(uint64_t d, uint32_t bytes) { return (d & 0xffffffff00000000ull) | (uint32_t)((uint32_t)d + (bytes >> 4)); }
__device__ __forceinline__ uint64_t desc_raw(uint64_t d, uint32_t inc) { return (d & 0xffffffff00000000ull) | (uint32_t)((uint32_t)d + inc); }
__device__ __forceinline__ void fence_async_smem() { asm volatile("fence.proxy.async.shared::cta;" ::: "memory"); }
__device__ __forceinline__ void bar_sync(int id, int n) { asm volatile("bar.sync %0, %1;" :: "r"(id), "r"(n) : "memory"); }
__device__ __forceinline__ void bar_arrive(int id, int n) { asm volatile("bar.arrive %0, %1;" :: "r"(id), "r"(n) : "memory"); }
template<int R> __device__ __forceinline__ void reg_inc() { asm volatile("setmaxnreg.inc.sync.aligned.u32 %0;" :: "n"(R)); }
template<int R> __device__ __forceinline__ void reg_dec() { asm volatile("setmaxnreg.dec.sync.aligned.u32 %0;" :: "n"(R)); }
__device__ __forceinline__ void cluster_arrive() { asm volatile("barrier.cluster.arrive.relaxed.aligned;" ::: "memory"); }
__device__ __forceinline__ void cluster_wait() { asm volatile("barrier.cluster.wait.acquire.aligned;" ::: "memory"); }

__device__ __forceinline__ void stsm4(uint32_t addr, uint32_t r0, uint32_t r1, uint32_t r2, uint32_t r3) {
    asm volatile("stmatrix.sync.aligned.m8n8.x4.shared.b16 [%0], {%1,%2,%3,%4};" :: "r"(addr), "r"(r0), "r"(r1), "r"(r2), "r"(r3) : "memory");
}
__device__ __forceinline__ void ldsm4(uint32_t& r0, uint32_t& r1, uint32_t& r2, uint32_t& r3, uint32_t addr) {
    asm volatile("ldmatrix.sync.aligned.m8n8.x4.shared.b16 {%0,%1,%2,%3}, [%4];" : "=r"(r0), "=r"(r1), "=r"(r2), "=r"(r3) : "r"(addr) : "memory");
}
__device__ __forceinline__ void ldsm4t(uint32_t& r0, uint32_t& r1, uint32_t& r2, uint32_t& r3, uint32_t addr) {
    asm volatile("ldmatrix.sync.aligned.m8n8.x4.trans.shared.b16 {%0,%1,%2,%3}, [%4];" : "=r"(r0), "=r"(r1), "=r"(r2), "=r"(r3) : "r"(addr) : "memory");
}
__device__ __forceinline__ void mma16816(float (&d)[4], uint32_t a0, uint32_t a1, uint32_t a2, uint32_t a3, uint32_t b0, uint32_t b1) {
    asm("mma.sync.aligned.m16n8k16.row.col.f32.bf16.bf16.f32 {%0,%1,%2,%3}, {%4,%5,%6,%7}, {%8,%9}, {%0,%1,%2,%3};"
        : "+f"(d[0]), "+f"(d[1]), "+f"(d[2]), "+f"(d[3]) : "r"(a0), "r"(a1), "r"(a2), "r"(a3), "r"(b0), "r"(b1));
}
__device__ __forceinline__ void mma1688(float (&d)[4], uint32_t a0, uint32_t a1, uint32_t b0) {
    asm("mma.sync.aligned.m16n8k8.row.col.f32.bf16.bf16.f32 {%0,%1,%2,%3}, {%4,%5}, {%6}, {%0,%1,%2,%3};"
        : "+f"(d[0]), "+f"(d[1]), "+f"(d[2]), "+f"(d[3]) : "r"(a0), "r"(a1), "r"(b0));
}
__device__ __forceinline__ uint4 lds128(uint32_t a) { uint4 v; asm volatile("ld.shared.v4.b32 {%0,%1,%2,%3}, [%4];" : "=r"(v.x), "=r"(v.y), "=r"(v.z), "=r"(v.w) : "r"(a) : "memory"); return v; }
__device__ __forceinline__ uint2 lds64(uint32_t a) { uint2 v; asm volatile("ld.shared.v2.b32 {%0,%1}, [%2];" : "=r"(v.x), "=r"(v.y) : "r"(a) : "memory"); return v; }
__device__ __forceinline__ uint32_t lds32(uint32_t a) { uint32_t v; asm volatile("ld.shared.b32 %0, [%1];" : "=r"(v) : "r"(a) : "memory"); return v; }
__device__ __forceinline__ float ldsf(uint32_t a) { float v; asm volatile("ld.shared.f32 %0, [%1];" : "=f"(v) : "r"(a) : "memory"); return v; }
__device__ __forceinline__ uint32_t lds16(uint32_t a) { uint16_t v; asm volatile("ld.shared.b16 %0, [%1];" : "=h"(v) : "r"(a) : "memory"); return v; }
__device__ __forceinline__ void sts128(uint32_t a, uint4 v) { asm volatile("st.shared.v4.b32 [%0], {%1,%2,%3,%4};" :: "r"(a), "r"(v.x), "r"(v.y), "r"(v.z), "r"(v.w) : "memory"); }
__device__ __forceinline__ void sts64(uint32_t a, uint32_t x, uint32_t y) { asm volatile("st.shared.v2.b32 [%0], {%1,%2};" :: "r"(a), "r"(x), "r"(y) : "memory"); }
__device__ __forceinline__ void sts32(uint32_t a, uint32_t x) { asm volatile("st.shared.b32 [%0], %1;" :: "r"(a), "r"(x) : "memory"); }
__device__ __forceinline__ void stsf(uint32_t a, float x) { asm volatile("st.shared.f32 [%0], %1;" :: "r"(a), "f"(x) : "memory"); }
__device__ __forceinline__ void sts16(uint32_t a, uint32_t x) { asm volatile("st.shared.b16 [%0], %1;" :: "r"(a), "h"((uint16_t)x) : "memory"); }

__device__ __forceinline__ uint4 ldg128(const void* p) { uint4 v; asm volatile("ld.global.nc.v4.b32 {%0,%1,%2,%3}, [%4];" : "=r"(v.x), "=r"(v.y), "=r"(v.z), "=r"(v.w) : "l"(p)); return v; }
__device__ __forceinline__ uint2 ldg64(const void* p) { uint2 v; asm volatile("ld.global.nc.v2.b32 {%0,%1}, [%2];" : "=r"(v.x), "=r"(v.y) : "l"(p)); return v; }
__device__ __forceinline__ void stg128(void* p, uint4 v) { asm volatile("st.global.v4.b32 [%0], {%1,%2,%3,%4};" :: "l"(p), "r"(v.x), "r"(v.y), "r"(v.z), "r"(v.w) : "memory"); }
__device__ __forceinline__ void stg_fill(void* p, uint32_t v) { asm volatile("st.global.v4.b32 [%0], {%1,%1,%1,%1};" :: "l"(p), "r"(v) : "memory"); }
__device__ __forceinline__ void st_ll(void* p, uint32_t x, uint32_t y, uint32_t z, uint32_t w) {
    asm volatile("{\n.reg .b128 t;\n.reg .b64 a, b;\nmov.b64 a, {%1, %2};\nmov.b64 b, {%3, %4};\nmov.b128 t, {a, b};\nst.relaxed.gpu.global.b128 [%0], t;\n}"
        :: "l"(p), "r"(x), "r"(y), "r"(z), "r"(w) : "memory");
}
__device__ __forceinline__ uint4 ld_ll(const void* p) {
    uint4 v;
    asm volatile("{\n.reg .b128 t;\n.reg .b64 a, b;\nld.relaxed.gpu.global.b128 t, [%4];\nmov.b128 {a, b}, t;\nmov.b64 {%0, %1}, a;\nmov.b64 {%2, %3}, b;\n}"
        : "=r"(v.x), "=r"(v.y), "=r"(v.z), "=r"(v.w) : "l"(p) : "memory");
    return v;
}
__device__ __forceinline__ void ld_ll_if(uint4& v, const void* p, bool go) {
    asm volatile("{\n.reg .b128 t;\n.reg .b64 a, b;\n.reg .pred q;\nsetp.ne.u32 q, %5, 0;\nmov.b64 a, {%0, %1};\nmov.b64 b, {%2, %3};\nmov.b128 t, {a, b};\n"
        "@q ld.relaxed.gpu.global.b128 t, [%4];\nmov.b128 {a, b}, t;\nmov.b64 {%0, %1}, a;\nmov.b64 {%2, %3}, b;\n}"
        : "+r"(v.x), "+r"(v.y), "+r"(v.z), "+r"(v.w) : "l"(p), "r"((uint32_t)go) : "memory");
}
__device__ __forceinline__ void st_ll8(void* p, uint32_t x, uint32_t y) {
    asm volatile("{\n.reg .b64 a;\nmov.b64 a, {%1, %2};\nst.relaxed.gpu.global.b64 [%0], a;\n}" :: "l"(p), "r"(x), "r"(y) : "memory");
}
__device__ __forceinline__ void st_ll4(void* p, uint32_t x) { asm volatile("st.relaxed.gpu.global.b32 [%0], %1;" :: "l"(p), "r"(x) : "memory"); }
__device__ __forceinline__ unsigned ld_rlx(const void* p) { unsigned v; asm volatile("ld.relaxed.gpu.global.u32 %0, [%1];" : "=r"(v) : "l"(p) : "memory"); return v; }
__device__ __forceinline__ void red_add4(void* p, float x, float y, float z, float w) {
    asm volatile("red.relaxed.gpu.global.add.v4.f32 [%0], {%1, %2, %3, %4};" :: "l"(p), "f"(x), "f"(y), "f"(z), "f"(w) : "memory");
}
__device__ __forceinline__ void fence_rel_gpu() { asm volatile("fence.proxy.async.global;\nfence.release.gpu;" ::: "memory"); }
__device__ __forceinline__ void fence_acq_gpu() { asm volatile("fence.acquire.gpu;" ::: "memory"); }
template<int N> __device__ __forceinline__ void poll_words(uint4 (&v)[N], const uint4* p, int stride, uint32_t tag) {
    #pragma unroll 1
    for (int it = 0; it < POLL_MAX; it++) {
        bool ok = true;
        #pragma unroll
        for (int i = 0; i < N; i++) v[i] = ld_ll(p + i * stride);
        #pragma unroll
        for (int i = 0; i < N; i++) ok = ok && (v[i].w == tag);
        if (__all_sync(0xffffffffu, ok)) break;
    }
}
__device__ __forceinline__ void pause(uint32_t n) { const uint32_t c0 = clk32(); while (clk32() - c0 < n) {} }
template<int B> __device__ __forceinline__ uint32_t low_byte(float v, uint32_t src) { return __byte_perm(__float_as_uint(v), src, 0x3214 + B); }
__device__ __forceinline__ uint32_t low_bits(float v, uint32_t tag2) { return (__float_as_uint(v) & ~3u) | tag2; }
__device__ __forceinline__ bool tagged2(uint32_t w, uint32_t tag2) { return (w & 3u) == tag2; }
__device__ __forceinline__ uint32_t umax4(uint4 v) { return max(max(v.x, v.y), max(v.z, v.w)); }
constexpr uint32_t ONE2 = 0x3F803F80u;
__device__ __forceinline__ uint32_t pack2(float lo, float hi) { uint32_t d; asm("cvt.rn.bf16x2.f32 %0, %1, %2;" : "=r"(d) : "f"(hi), "f"(lo)); return d; }
__device__ __forceinline__ float bf_lo(uint32_t v) { return __uint_as_float(v << 16); }
__device__ __forceinline__ float bf_lo_after(uint32_t v, float nonneg) { float d; asm("prmt.b32 %0, %1, %2, 0x10ff;" : "=f"(d) : "r"(v), "f"(nonneg)); return d; }
__device__ __forceinline__ float bf_hi_after(uint32_t v, float nonneg) { float d; asm("prmt.b32 %0, %1, %2, 0x32ff;" : "=f"(d) : "r"(v), "f"(nonneg)); return d; }
__device__ __forceinline__ float bf_hi(uint32_t v) { return __uint_as_float(v & 0xffff0000u); }
__device__ __forceinline__ float rbf(float x) { return bf_lo(pack2(x, 0.f)); }
__device__ __forceinline__ uint32_t hsub2(uint32_t a, uint32_t b) { uint32_t d; asm("sub.rn.bf16x2 %0, %1, %2;" : "=r"(d) : "r"(a), "r"(b)); return d; }
__device__ __forceinline__ uint32_t hadd2(uint32_t a, uint32_t b) { uint32_t d; asm("add.rn.bf16x2 %0, %1, %2;" : "=r"(d) : "r"(a), "r"(b)); return d; }
__device__ __forceinline__ uint32_t hmul2(uint32_t a, uint32_t b) { uint32_t d; asm("mul.rn.bf16x2 %0, %1, %2;" : "=r"(d) : "r"(a), "r"(b)); return d; }
__device__ __forceinline__ uint32_t hmax2(uint32_t a, uint32_t b) { uint32_t d; asm("max.bf16x2 %0, %1, %2;" : "=r"(d) : "r"(a), "r"(b)); return d; }
__device__ __forceinline__ uint32_t hmin2(uint32_t a, uint32_t b) { uint32_t d; asm("min.bf16x2 %0, %1, %2;" : "=r"(d) : "r"(a), "r"(b)); return d; }
__device__ __forceinline__ float ex2(float x) { float y; asm("ex2.approx.ftz.f32 %0, %1;" : "=f"(y) : "f"(x)); return y; }
__device__ __forceinline__ float rcp(float x) { float y; asm("rcp.approx.ftz.f32 %0, %1;" : "=f"(y) : "f"(x)); return y; }
__device__ __forceinline__ float shfl_x(float v, int m) { return __shfl_xor_sync(0xffffffffu, v, m); }
constexpr float LOG2E = 1.4426950408889634f;
__device__ __forceinline__ float sigmoidf(float x) { return rcp(1.0f + ex2(-LOG2E * x)); }
__device__ __forceinline__ uint32_t ln_pair(uint32_t x, uint32_t m2, float rinv, uint32_t a, uint32_t s) {
    uint32_t d = hsub2(x, m2);
    uint32_t n = pack2(bf_lo(d) * rinv, bf_hi(d) * rinv);
    return hadd2(hmul2(n, a), s);
}
struct Recip { uint32_t hi, lo; };
__device__ __forceinline__ Recip split_recip(float r) { Recip q; q.hi = pack2(r, r); const float l = r - bf_hi(q.hi); q.lo = pack2(l, l); return q; }
__device__ __forceinline__ uint32_t hdiv2(uint32_t n, Recip r) { uint32_t d; asm("fma.rn.bf16x2 %0, %1, %2, %3;" : "=r"(d) : "r"(n), "r"(r.hi), "r"(hmul2(n, r.lo))); return d; }
__device__ __forceinline__ uint32_t ln_pair(uint32_t x, uint32_t m2, Recip r, uint32_t a, uint32_t s) { return hadd2(hmul2(hdiv2(hsub2(x, m2), r), a), s); }
__device__ __forceinline__ void ln_final(float s1, float s2, uint32_t& m2, float& rinv) {
    const float mean = s1 * (1.0f / 1024.0f), var = fmaf(-mean, mean, s2 * (1.0f / 1024.0f));
    m2 = pack2(mean, mean);
    float sd;
    asm("sqrt.approx.ftz.f32 %0, %1;" : "=f"(sd) : "f"(rbf(rbf(fmaxf(var, 0.f)) + 1e-5f)));
    rinv = rcp(rbf(sd));
}
__device__ __forceinline__ uint32_t f2key(float f) { uint32_t u = __float_as_uint(f); return (u & 0x80000000u) ? ~u : (u | 0x80000000u); }

__device__ __forceinline__ void fm_extrema(const uint32_t (&p)[16], float& cp, float& cn) {
    uint32_t mx = p[0], mn = p[0];
    #pragma unroll
    for (int k = 1; k < 15; k += 2) { mx = hmax2(hmax2(mx, p[k]), p[k + 1]); mn = hmin2(hmin2(mn, p[k]), p[k + 1]); }
    mx = hmax2(mx, p[15]); mn = hmin2(mn, p[15]);
    cp = -fmaxf(bf_lo(mx), bf_hi(mx)) * LOG2E; cn = fminf(bf_lo(mn), bf_hi(mn)) * LOG2E;
}
template<int TB> __device__ __forceinline__ void wgmma_n32_rs(float (&d)[16], uint32_t a0, uint32_t a1, uint32_t a2, uint32_t a3, uint64_t db, int sc) {
  asm volatile("{\n.reg .pred p;\nsetp.ne.b32 p, %21, 0;\n"
    "wgmma.mma_async.sync.aligned.m64n32k16.f32.bf16.bf16 {%0, %1, %2, %3, %4, %5, %6, %7, %8, %9, %10, %11, %12, %13, %14, %15}, {%16,%17,%18,%19}, %20, p, 1, 1, %22;\n}\n"
    : "+f"(d[0]), "+f"(d[1]), "+f"(d[2]), "+f"(d[3]), "+f"(d[4]), "+f"(d[5]), "+f"(d[6]), "+f"(d[7]), "+f"(d[8]), "+f"(d[9]), "+f"(d[10]), "+f"(d[11]), "+f"(d[12]), "+f"(d[13]), "+f"(d[14]), "+f"(d[15])
    : "r"(a0), "r"(a1), "r"(a2), "r"(a3), "l"(db), "r"(sc), "n"(TB));
}
template<int TA, int TB> __device__ __forceinline__ void wgmma_n40_ss(float (&d)[20], uint64_t da, uint64_t db, int sc) {
  asm volatile("{\n.reg .pred p;\nsetp.ne.b32 p, %22, 0;\n"
    "wgmma.mma_async.sync.aligned.m64n40k16.f32.bf16.bf16 {%0, %1, %2, %3, %4, %5, %6, %7, %8, %9, %10, %11, %12, %13, %14, %15, %16, %17, %18, %19}, %20, %21, p, 1, 1, %23, %24;\n}\n"
    : "+f"(d[0]), "+f"(d[1]), "+f"(d[2]), "+f"(d[3]), "+f"(d[4]), "+f"(d[5]), "+f"(d[6]), "+f"(d[7]), "+f"(d[8]), "+f"(d[9]), "+f"(d[10]), "+f"(d[11]), "+f"(d[12]), "+f"(d[13]), "+f"(d[14]), "+f"(d[15]), "+f"(d[16]), "+f"(d[17]), "+f"(d[18]), "+f"(d[19])
    : "l"(da), "l"(db), "r"(sc), "n"(TA), "n"(TB));
}
template<int TA, int TB> __device__ __forceinline__ void wgmma_n128_ss(float (&d)[64], uint64_t da, uint64_t db, int sc) {
  asm volatile("{\n.reg .pred p;\nsetp.ne.b32 p, %66, 0;\n"
    "wgmma.mma_async.sync.aligned.m64n128k16.f32.bf16.bf16 {%0, %1, %2, %3, %4, %5, %6, %7, %8, %9, %10, %11, %12, %13, %14, %15, %16, %17, %18, %19, %20, %21, %22, %23, %24, %25, %26, %27, %28, %29, %30, %31, %32, %33, %34, %35, %36, %37, %38, %39, %40, %41, %42, %43, %44, %45, %46, %47, %48, %49, %50, %51, %52, %53, %54, %55, %56, %57, %58, %59, %60, %61, %62, %63}, %64, %65, p, 1, 1, %67, %68;\n}\n"
    : "+f"(d[0]), "+f"(d[1]), "+f"(d[2]), "+f"(d[3]), "+f"(d[4]), "+f"(d[5]), "+f"(d[6]), "+f"(d[7]), "+f"(d[8]), "+f"(d[9]), "+f"(d[10]), "+f"(d[11]), "+f"(d[12]), "+f"(d[13]), "+f"(d[14]), "+f"(d[15]), "+f"(d[16]), "+f"(d[17]), "+f"(d[18]), "+f"(d[19]), "+f"(d[20]), "+f"(d[21]), "+f"(d[22]), "+f"(d[23]), "+f"(d[24]), "+f"(d[25]), "+f"(d[26]), "+f"(d[27]), "+f"(d[28]), "+f"(d[29]), "+f"(d[30]), "+f"(d[31]), "+f"(d[32]), "+f"(d[33]), "+f"(d[34]), "+f"(d[35]), "+f"(d[36]), "+f"(d[37]), "+f"(d[38]), "+f"(d[39]), "+f"(d[40]), "+f"(d[41]), "+f"(d[42]), "+f"(d[43]), "+f"(d[44]), "+f"(d[45]), "+f"(d[46]), "+f"(d[47]), "+f"(d[48]), "+f"(d[49]), "+f"(d[50]), "+f"(d[51]), "+f"(d[52]), "+f"(d[53]), "+f"(d[54]), "+f"(d[55]), "+f"(d[56]), "+f"(d[57]), "+f"(d[58]), "+f"(d[59]), "+f"(d[60]), "+f"(d[61]), "+f"(d[62]), "+f"(d[63])
    : "l"(da), "l"(db), "r"(sc), "n"(TA), "n"(TB));
}
template<int TB> __device__ __forceinline__ void wgmma_n128_rs(float (&d)[64], uint32_t a0, uint32_t a1, uint32_t a2, uint32_t a3, uint64_t db, int sc) {
  asm volatile("{\n.reg .pred p;\nsetp.ne.b32 p, %69, 0;\n"
    "wgmma.mma_async.sync.aligned.m64n128k16.f32.bf16.bf16 {%0, %1, %2, %3, %4, %5, %6, %7, %8, %9, %10, %11, %12, %13, %14, %15, %16, %17, %18, %19, %20, %21, %22, %23, %24, %25, %26, %27, %28, %29, %30, %31, %32, %33, %34, %35, %36, %37, %38, %39, %40, %41, %42, %43, %44, %45, %46, %47, %48, %49, %50, %51, %52, %53, %54, %55, %56, %57, %58, %59, %60, %61, %62, %63}, {%64,%65,%66,%67}, %68, p, 1, 1, %70;\n}\n"
    : "+f"(d[0]), "+f"(d[1]), "+f"(d[2]), "+f"(d[3]), "+f"(d[4]), "+f"(d[5]), "+f"(d[6]), "+f"(d[7]), "+f"(d[8]), "+f"(d[9]), "+f"(d[10]), "+f"(d[11]), "+f"(d[12]), "+f"(d[13]), "+f"(d[14]), "+f"(d[15]), "+f"(d[16]), "+f"(d[17]), "+f"(d[18]), "+f"(d[19]), "+f"(d[20]), "+f"(d[21]), "+f"(d[22]), "+f"(d[23]), "+f"(d[24]), "+f"(d[25]), "+f"(d[26]), "+f"(d[27]), "+f"(d[28]), "+f"(d[29]), "+f"(d[30]), "+f"(d[31]), "+f"(d[32]), "+f"(d[33]), "+f"(d[34]), "+f"(d[35]), "+f"(d[36]), "+f"(d[37]), "+f"(d[38]), "+f"(d[39]), "+f"(d[40]), "+f"(d[41]), "+f"(d[42]), "+f"(d[43]), "+f"(d[44]), "+f"(d[45]), "+f"(d[46]), "+f"(d[47]), "+f"(d[48]), "+f"(d[49]), "+f"(d[50]), "+f"(d[51]), "+f"(d[52]), "+f"(d[53]), "+f"(d[54]), "+f"(d[55]), "+f"(d[56]), "+f"(d[57]), "+f"(d[58]), "+f"(d[59]), "+f"(d[60]), "+f"(d[61]), "+f"(d[62]), "+f"(d[63])
    : "r"(a0), "r"(a1), "r"(a2), "r"(a3), "l"(db), "r"(sc), "n"(TB));
}
template<int TB> __device__ __forceinline__ void wgmma_n256_rs(float (&d)[128], uint32_t a0, uint32_t a1, uint32_t a2, uint32_t a3, uint64_t db, int sc) {
  asm volatile("{\n.reg .pred p;\nsetp.ne.b32 p, %133, 0;\n"
    "wgmma.mma_async.sync.aligned.m64n256k16.f32.bf16.bf16 {%0, %1, %2, %3, %4, %5, %6, %7, %8, %9, %10, %11, %12, %13, %14, %15, %16, %17, %18, %19, %20, %21, %22, %23, %24, %25, %26, %27, %28, %29, %30, %31, %32, %33, %34, %35, %36, %37, %38, %39, %40, %41, %42, %43, %44, %45, %46, %47, %48, %49, %50, %51, %52, %53, %54, %55, %56, %57, %58, %59, %60, %61, %62, %63, %64, %65, %66, %67, %68, %69, %70, %71, %72, %73, %74, %75, %76, %77, %78, %79, %80, %81, %82, %83, %84, %85, %86, %87, %88, %89, %90, %91, %92, %93, %94, %95, %96, %97, %98, %99, %100, %101, %102, %103, %104, %105, %106, %107, %108, %109, %110, %111, %112, %113, %114, %115, %116, %117, %118, %119, %120, %121, %122, %123, %124, %125, %126, %127}, {%128,%129,%130,%131}, %132, p, 1, 1, %134;\n}\n"
    : "+f"(d[0]), "+f"(d[1]), "+f"(d[2]), "+f"(d[3]), "+f"(d[4]), "+f"(d[5]), "+f"(d[6]), "+f"(d[7]), "+f"(d[8]), "+f"(d[9]), "+f"(d[10]), "+f"(d[11]), "+f"(d[12]), "+f"(d[13]), "+f"(d[14]), "+f"(d[15]), "+f"(d[16]), "+f"(d[17]), "+f"(d[18]), "+f"(d[19]), "+f"(d[20]), "+f"(d[21]), "+f"(d[22]), "+f"(d[23]), "+f"(d[24]), "+f"(d[25]), "+f"(d[26]), "+f"(d[27]), "+f"(d[28]), "+f"(d[29]), "+f"(d[30]), "+f"(d[31]), "+f"(d[32]), "+f"(d[33]), "+f"(d[34]), "+f"(d[35]), "+f"(d[36]), "+f"(d[37]), "+f"(d[38]), "+f"(d[39]), "+f"(d[40]), "+f"(d[41]), "+f"(d[42]), "+f"(d[43]), "+f"(d[44]), "+f"(d[45]), "+f"(d[46]), "+f"(d[47]), "+f"(d[48]), "+f"(d[49]), "+f"(d[50]), "+f"(d[51]), "+f"(d[52]), "+f"(d[53]), "+f"(d[54]), "+f"(d[55]), "+f"(d[56]), "+f"(d[57]), "+f"(d[58]), "+f"(d[59]), "+f"(d[60]), "+f"(d[61]), "+f"(d[62]), "+f"(d[63]), "+f"(d[64]), "+f"(d[65]), "+f"(d[66]), "+f"(d[67]), "+f"(d[68]), "+f"(d[69]), "+f"(d[70]), "+f"(d[71]), "+f"(d[72]), "+f"(d[73]), "+f"(d[74]), "+f"(d[75]), "+f"(d[76]), "+f"(d[77]), "+f"(d[78]), "+f"(d[79]), "+f"(d[80]), "+f"(d[81]), "+f"(d[82]), "+f"(d[83]), "+f"(d[84]), "+f"(d[85]), "+f"(d[86]), "+f"(d[87]), "+f"(d[88]), "+f"(d[89]), "+f"(d[90]), "+f"(d[91]), "+f"(d[92]), "+f"(d[93]), "+f"(d[94]), "+f"(d[95]), "+f"(d[96]), "+f"(d[97]), "+f"(d[98]), "+f"(d[99]), "+f"(d[100]), "+f"(d[101]), "+f"(d[102]), "+f"(d[103]), "+f"(d[104]), "+f"(d[105]), "+f"(d[106]), "+f"(d[107]), "+f"(d[108]), "+f"(d[109]), "+f"(d[110]), "+f"(d[111]), "+f"(d[112]), "+f"(d[113]), "+f"(d[114]), "+f"(d[115]), "+f"(d[116]), "+f"(d[117]), "+f"(d[118]), "+f"(d[119]), "+f"(d[120]), "+f"(d[121]), "+f"(d[122]), "+f"(d[123]), "+f"(d[124]), "+f"(d[125]), "+f"(d[126]), "+f"(d[127])
    : "r"(a0), "r"(a1), "r"(a2), "r"(a3), "l"(db), "r"(sc), "n"(TB));
}

#define CCOL 1
#define T_S0 3300
#define T_S1 5800
#define G1W 1
#define LNP 1
#define CG1 232
#define JU 2
#define WPF 0
#define FPF 0
#define KW 8
#define DEP 2
#define STAG 0
#define KVSH 0
#define KVDLY 900
#define PREWAIT 0
#define OUN 4
#define DNE 8
#define YGATE B_YP
#define YDLY 0
#define OUTGATE B_CAND
#define NEARLY 32
#define LN2P 1
#define LPACE 0
#define XGATE B_RED
#define MCW 0
#define JS 15
#define KT 3
#define KPAUSE 0
#define JEF 16
#define BDLY 0
#define PJ2 12
#define PM2 2
#define NPF 20
#define PSP 500
#define PS0 300
#define RJ 0
#define KVD2 0
#define STG23 0
#define CLRM 3
#define WPN 5
#define PRELD 1
#define SKIP3 0
#define LDPOS 0
#define OPN 4
#define OPS 400
#define OP0 500
#define RELN 2
#define FGATE 0
#define FDLY 0
#define PUBN 6
#define FPOS 4
#define BD0 0
#define T_OSC 24000
#define T_OSD 800
#define PIN 1
#define KX 0
#define SGATE 2
#define T_P0 1500
#define T_P1 3000
#define LATEFREE 1
#define NC 2
#define T_W1 2800
#define T_WD 0
#define NW0 32
#define PFN 3
#define PFJ 3
#define PFM 4
#define WOJ 10
#define WON 1
#define NLD (CCOL ? 0 : 1)
#define VFIRST 2
#define T_X0 450
#define T_XD 600
#define MCB 1
#define ORIENT 2
#define PFORDER 0x51634
#define PFORDER2 0x51
#define PFW0 2
#define CLRJ 3
#define CLRK 8
#define JPF 0
#define CLRGATE (B_FB + 4)
#define KVC0 0
#define CLRS 50
#define OGATE 0
#define PFD 0
#define GBN 6
#define BG1 99
#define BG2 99
#define BG3 99
#define BG4 99
#define BG5 99
#define SYNCQ 640
#define SYNCG 4
#define BSP 0
#define T_INI 500
#define T_WLATE 4000
#define T_REST 6000
#define T_COL 7000
#define T_COL2 14000
#define PF_START 9000
#define PF_FIRST 2
#define PFP 400
#define CREG 208
#define TMA_WO tma2_ef_e
#define TMA_M tma2_ef_e
#define TMA_F tma2_ef_e
#define JUN 4
constexpr int JUU = JUN, OUU = OUN;
constexpr bool GS2 = false;
struct Ptrs { const bf16 *x, *c, *wmod, *wr, *wg, *wu, *wd, *wqkv, *wo; bf16* out; Scratch* s; };

#define BAR(i) (sb + OFF_BAR + 8u * (i))

__device__ __forceinline__ int d_block(int hg, int n) {
    const int m = n - (n >= 9 ? 9 : 2);
    return n < 2 ? 2 * hg + n : 2 * (m + (m >= hg)) + (n >= 9);
}
__host__ __device__ constexpr uint32_t bar_count(int i) {
    return (MCB && i >= B_ED && i < B_ED + 16) ? 16 : ((i >= B_E1 && i < B_E1 + 3) || (i >= B_S0FREE && i < B_PHI + 4) || i == B_OWN || i == B_OWN + 1 || (i >= B_ED && i < B_ED + 16)
            || i == B_STFREE || i == B_X2 || i == B_OUTW || i == B_YP || i == B_RED) ? 8
         : ((i >= B_KVD && i < B_KVD + 2) || i == B_ST2 || i == B_TURN) ? 4 : (i == B_KVF || i == B_KVF + 1 ) ? 2 : 1;
}
template<int I0, int I1> __device__ __forceinline__ void init_barriers(uint32_t sb) {
    #pragma unroll
    for (int i = I0; i < I1; i++) mbar_init(BAR(i), bar_count(i));
}
template<int N> __device__ __forceinline__ uint32_t pop_max(uint32_t (&k)[N]) {
    uint32_t m = k[0];
    #pragma unroll
    for (int i = 1; i < N; i++) m = max(m, k[i]);
    m = __reduce_max_sync(0xffffffffu, m);
    #pragma unroll
    for (int i = 0; i < N; i++) k[i] = (k[i] == m) ? 0u : k[i];
    return m;
}
__device__ __forceinline__ uint32_t mod_pos(int step, int g) { return step * 64 + (g >> 1) * 16 + (g & 1) * 4; }
__device__ __forceinline__ void fma8(float (&a)[8], uint4 w, float s) {
    a[0] = fmaf(bf_lo(w.x), s, a[0]); a[1] = fmaf(bf_hi(w.x), s, a[1]); a[2] = fmaf(bf_lo(w.y), s, a[2]); a[3] = fmaf(bf_hi(w.y), s, a[3]);
    a[4] = fmaf(bf_lo(w.z), s, a[4]); a[5] = fmaf(bf_hi(w.z), s, a[5]); a[6] = fmaf(bf_lo(w.w), s, a[6]); a[7] = fmaf(bf_hi(w.w), s, a[7]);
}
__device__ __forceinline__ float reduce8(const float (&v)[8], int lane) {
    const bool b3 = lane & 16, b2 = lane & 8, b1 = lane & 4;
    float a[4], b[2];
    #pragma unroll
    for (int i = 0; i < 4; i++) { float keep = b3 ? v[4 + i] : v[i], send = b3 ? v[i] : v[4 + i]; a[i] = keep + shfl_x(send, 16); }
    #pragma unroll
    for (int i = 0; i < 2; i++) { float keep = b2 ? a[2 + i] : a[i], send = b2 ? a[i] : a[2 + i]; b[i] = keep + shfl_x(send, 8); }
    float keep = b1 ? b[1] : b[0], send = b1 ? b[0] : b[1];
    return keep + shfl_x(send, 4);
}
__device__ __forceinline__ bool mod_collect(uint4 w0, uint4 w1, uint4 w2, uint4 w3, uint32_t sb, int jb, int lane, uint32_t tag2) {
    const uint32_t add = lane < 16 ? ONE2 : 0u;
    const uint32_t lo = pack2((__uint_as_float(w0.x) + __uint_as_float(w1.x)) + (__uint_as_float(w2.x) + __uint_as_float(w3.x)),
                              (__uint_as_float(w0.y) + __uint_as_float(w1.y)) + (__uint_as_float(w2.y) + __uint_as_float(w3.y)));
    const uint32_t hi = pack2((__uint_as_float(w0.z) + __uint_as_float(w1.z)) + (__uint_as_float(w2.z) + __uint_as_float(w3.z)),
                              (__uint_as_float(w0.w) + __uint_as_float(w1.w)) + (__uint_as_float(w2.w) + __uint_as_float(w3.w)));
    sts64(sb + OFF_MODS + jb * 256 + (lane & 15) * 16 + (lane >> 4) * 8, hadd2(lo, add), hadd2(hi, add));
    return tagged2(w0.w, tag2) && tagged2(w1.w, tag2) && tagged2(w2.w, tag2) && tagged2(w3.w, tag2);
}
__device__ __forceinline__ void phi_issue(float (&pp)[2][16], const uint32_t* a, uint32_t sb, int pair) {
    const uint64_t dw = mk_desc(sb + OFF_WPHI + pair * 4096, 16, 512, 2);
    wg_fence();
    #pragma unroll
    for (int ks = 0; ks < 2; ks++)
        #pragma unroll
        for (int h = 0; h < 2; h++) wgmma_n32_rs<1>(pp[h], a[8 * h + 4 * ks], a[8 * h + 4 * ks + 1], a[8 * h + 4 * ks + 2], a[8 * h + 4 * ks + 3], desc_add(dw, h * 2048 + ks * 1024), ks);
    wg_commit();
}
__device__ __forceinline__ void phi_transpose(float (&pp)[2][16], uint32_t (&pt)[16], uint32_t wr, uint32_t rd) {
    wg_wait<0>();
    acc_fence(pp[0]); acc_fence(pp[1]);
    #pragma unroll
    for (int q = 0; q < 4; q++) {
        const float (&a)[16] = pp[q >> 1]; const int o = 8 * (q & 1);
        stsm4(wr ^ (q << 5), pack2(a[o], a[o + 1]), pack2(a[o + 2], a[o + 3]), pack2(a[o + 4], a[o + 5]), pack2(a[o + 6], a[o + 7]));
    }
    __syncwarp();
    #pragma unroll
    for (int i = 0; i < 4; i++) { const uint4 v = lds128(rd ^ (i << 4)); pt[4 * i] = v.x; pt[4 * i + 1] = v.y; pt[4 * i + 2] = v.z; pt[4 * i + 3] = v.w; }
    __syncwarp();
}

__global__ void __cluster_dims__(2, 1, 1) __launch_bounds__(NTHREADS, 1)
fused_kernel(const Ptrs p, const __grid_constant__ CUtensorMap tmW, const __grid_constant__ CUtensorMap tmWo, const __grid_constant__ CUtensorMap tmPhi,
             const __grid_constant__ CUtensorMap tmG, const __grid_constant__ CUtensorMap tmU, const __grid_constant__ CUtensorMap tmD,
             const __grid_constant__ CUtensorMap tmX, const __grid_constant__ CUtensorMap tmO, const __grid_constant__ CUtensorMap tmM,
             const __grid_constant__ CUtensorMap tmR, const __grid_constant__ CUtensorMap tmG8, const __grid_constant__ CUtensorMap tmU8,
             const __grid_constant__ CUtensorMap tmD8)
{
    extern __shared__ __align__(1024) uint8_t smem_raw[];
    const uint32_t sb = smem_u32(smem_raw);
    const int tid = threadIdx.x, lane = tid & 31, warp = __shfl_sync(0xffffffffu, tid >> 5, 0);
    const int b = blockIdx.x;
    const int pr = b >> 1, rank = b & 1;
    const int cls = pr < 4 ? 15 : pr < 36 ? 2 * ((pr - 4) & 7) : 2 * ((pr - 36) % 7) + 1, mem = pr < 4 ? pr : pr < 36 ? (pr - 4) >> 3 : (pr - 36) / 7;
    const int hg = (((cls + 1) >> 1) & 1) * 4 + mem, rb = (cls >> 1) * 2 + rank;
    const bool ffn = b < 112;
    const uint32_t cstart = clk32();

    if (warp >= 8) {
        const int t = tid & 127, w4 = warp & 3, g = lane >> 2, c = lane & 3;
        if (w4 == 0) TS(40);
        reg_dec<504 - 2 * CG1>();
        if (w4 == 2) TS(41);
        if (w4 == 0) { tmap_prefetch(&tmX); tmap_prefetch(&tmW); }
        if (w4 == 3) tmap_prefetch(&tmM);
        if (w4 < 2) while (clk32() - cstart < T_INI) {}
        if (elect_one()) {
            if (w4 & 2) { if (w4 & 1) init_barriers<B_WS, B_COUNT>(sb); else init_barriers<B_XS, B_WS>(sb); }
            else { if (w4 & 1) init_barriers<B_MP, B_XS>(sb); else init_barriers<0, B_MP>(sb); }
        }
        __syncwarp();
        if (w4 < 2) asm volatile("fence.mbarrier_init.release.cluster;" ::: "memory");
        if (w4 == 1) {
            expect_tx_e(BAR(B_PX), 2048); sts32(sb + OFF_SEEN, 0);
        }
        if (w4 == 0) TS(42);
        bar_arrive(0, 384);
        if (w4 == 2) {
            #pragma unroll 1
            for (int i = 0; i < 4; i++) {
                while (clk32() - cstart < T_X0 + i * T_XD) {}
                bulk_load_e(sb + OFF_XS + i * 8192u, p.x + (size_t)(b * 16 + i * 4) * 1024, 8192, BAR(B_XS + i));
                expect_tx_e(BAR(B_XS + i), 8192);
                if (i == 0) TS(43);
            }
        }
        if (w4 == 3 && b < 32 * NC) {
            while (b >= NW0 && clk32() - cstart < T_W1 + (b >> 5) * T_WD) {}
            #pragma unroll 1
            for (int i = 0; i < 4; i++) {
                tma2_ef_e(sb + OFF_WST + i * 8192u, &tmM, (((b >> 2) & 1) ? 0 : 1024) + (b >> 3) * 64, (b & 3) * 256 + i * 64, BAR(B_WS + i));
                expect_tx_e(BAR(B_WS + i), 8192);
            }
            TS(44);
        }
        cluster_arrive();
        const uint32_t tag = ld_rlx(p.s->done) + 1, tag2 = tag % 3u;
        if (w4 == 0) {
            uint4* clr = p.s->kvp + (hg * 1024 + rb) * 32 + lane;
            #pragma unroll 1
            for (int j = 0; j < 3; j++) {
                while (clk32() - cstart < (j ? T_P1 : T_P0)) {}
                if (lane < 24) asm volatile("prefetch.global.L2 [%0];" :: "l"((const char*)p.wqkv + ((j * 128 + b) * 24 + lane) * 128));
            }
            int s = 0, par = 1;
            #pragma unroll 1
            for (int j = 0; j < 19; j++) {
                if (j >= 2) mbar_wait(BAR(j == 2 ? B_STFREE : B_E1 + s), j == 2 ? 0 : par);
                else while (clk32() - cstart < (j ? T_S1 : T_S0)) {}
                const uint32_t st = sb + OFF_RING + s * 65536u;
                if (j < 16) {
                    tma4_e(st + 16384u, &tmW, j * 64, hg * 2, BAR(B_F1 + s), EF_W);
                    tma2_e(st, &tmX, j * 64, rb * 128, BAR(B_F1 + s));
                    expect_tx_e(BAR(B_F1 + s), 65536);
                    if (j >= WOJ && j < WOJ + 4) asm volatile("prefetch.global.L2 [%0];" :: "l"((const char*)p.wo + (j - WOJ) * 524288 + (b * 32 + lane) * 128));
                } else if (j == 17) {
                    #pragma unroll 1
                    for (int n = 0; n < 4; n++) {
                        if (!(n & 1)) expect_tx_e(BAR(B_FB + 4 + (n >> 1)), 16384);
                        TMA_WO(st + n * 8192u, &tmWo, hg * 128 + (n & 1) * 64, (2 * hg + (n >> 1)) * 64, BAR(B_FB + 4 + (n >> 1)));
                    }
                } else if (j == 18) {
                    expect_tx_e(BAR(B_S0), ffn ? 65536 : 32768);
                    #pragma unroll 1
                    for (int i = 0; i < (ffn ? 4 : 2); i++)
                        tma2_ef_e(st + i * 16384u, i < 2 ? &tmX : i == 2 ? &tmG : &tmU, i < 2 ? hg * 128 + i * 64 : pr * 64, i < 2 ? rb * 128 : rank * 512, BAR(B_S0));
                }
                if (j == 1) TS(50);
                par ^= s == 1;
                s = s == 0 ? 2 : s - 1;
                if (j >= 2 && j < 18) {
                    #pragma unroll
                    for (int i = 0; i < 4; i++) stg_fill(clr + i * 512, EMPTY);
                    clr += 2048;
                }
                const int piece = j - PFJ;
                if (ffn && piece >= 0 && piece < PND + 2 * PNG) {
                    if (piece < PND) asm volatile(EL "cp.async.bulk.tensor.3d.shared::cluster.global.mbarrier::complete_tx::bytes [%0], [%1, {0, %3, %4}], [%2];\n}"
                        :: "r"(sb + OFF_DUMMY), "l"(&tmD8), "r"(BAR(B_PF)), "r"(rank * 8), "r"(pr * 64 + piece * PRD) : "memory");
                    else tma2_e(sb + OFF_DUMMY, (piece & 1) ? &tmU8 : &tmG8, pr * 64, rank * 512 + 512 - PRG - ((piece - PND) >> 1) * PRG, BAR(B_PF));
                }
            }
            expect_tx_e(BAR(B_PF), ffn ? PND * PRD * 128 + 2 * PNG * PRG * 16 : 0);
        } else if (w4 == 1) {
            #pragma unroll 1
            for (int it = 0, jb = NW0 / 8; it < POLL_MAX && jb < 16; it++) {
                while (clk32() - cstart < (jb < 4 * NC ? T_COL : T_COL2)) {}
                const int n = min(4, (jb < 4 * NC ? 4 * NC : 16) - jb);
                bulk_load_e(sb + OFF_WPHI, p.s->mp + jb * 128, n * 2048, BAR(B_MP));
                expect_tx_e(BAR(B_MP), n * 2048);
                mbar_wait(BAR(B_MP), it & 1);
                #pragma unroll 1
                for (int q = 0; q < n; q++) {
                    const uint32_t a = sb + OFF_WPHI + q * 2048 + (lane >> 4) * 1024 + (lane & 15) * 16;
                    if (!__all_sync(0xffffffffu, mod_collect(lds128(a), lds128(a + 256), lds128(a + 512), lds128(a + 768), sb, jb, lane, tag2))) break;
                    arrive_many(BAR(B_MOD + jb), bar_count(B_MOD));
                    if (jb == 4) TS(5);
                    if (jb == 15) TS(8);
                    jb++;
                }
            }
            fence_async_smem();
            __syncwarp();
            expect_tx_e(BAR(B_WPHI), 8192);
            tma2_e(sb + OFF_WPHI, &tmPhi, 0, hg * 128, BAR(B_WPHI));
            #pragma unroll 1
            for (int i = 0; i < 4; i++) {
                uint4* rw = p.s->rowh + (rb * 8 + i * 2 + (lane >> 4)) * 128 + hg * 16 + (lane & 15);
                stg_fill(rw, EMPTY); stg_fill(rw + 16384, EMPTY);
                if (lane < 18) stg_fill(p.s->kvf + (hg * 4 + i) * 288 + (lane < 16 ? (rb >> 2) * 64 + (rb & 3) * 8 + (lane >> 3) * 32 + (lane & 7) : 240 + rb * 2 + lane), EMPTY);
            }
            if (hg == 0 && lane < 8) stg_fill(p.s->cand + rb * 8 + lane, 0);
            if (lane < 28) stg_fill(lane < 16 ? p.s->st2 + rb * 128 + hg * 16 + lane : lane < 20 ? p.s->flo + (rb * 16 + hg * 2) * 2 + lane - 16
                                    : p.s->rsc + ((rb * 4 + ((lane - 20) >> 1)) * 8 + hg) * 2 + (lane & 1), 0);
            if (FPOS == 1 || FPOS >= 3) fence_rel_gpu();
            #pragma unroll 1
            for (int i = 0; i < (ffn ? 9 : 8); i++) {
                while (T_OSC && clk32() - cstart < T_OSC + i * T_OSD) {}
                uint4* d = (i < 8 ? p.s->os + (rb * 16 + 2 * hg) * 1024 + i * 256 : p.s->yp + pr * 512 + rank * 128) + lane;
                #pragma unroll
                for (int q = 0; q < 4; q++) { stg_fill(d + q * 32, EMPTY); stg_fill(d + (i < 8 ? 128 : 256) + q * 32, EMPTY); }
            }
            if (FPOS == 0) fence_rel_gpu();
            TS(36);
        } else {
            const int hw = w4 & 1;
            const uint32_t fb = BAR(B_RF + 2 * hw);
            if (w4 == 2) {
                if (lane < 8) stg_fill(p.s->rest + b * 8 + lane, 0);
                else if (lane < 24 && b >= 32 * NC) stg_fill(p.s->mp + b * 16 + lane - 8, EMPTY);
            }
            bar_sync(3, 320);
            const uint32_t buf = sb + OFF_SP + hw * 8192u;
            #pragma unroll 1
            for (int job = b < 32 * NC; job < 2; job++) {
                const int nr = job ? 8 : 4;
                const int c0 = job ? 2048 + b * 32 : (((b >> 2) & 1) ? 0 : 1024) + (b >> 3) * 64 + hw * 32;
                const int row0 = job ? hw * 512 : (b & 3) * 256;
                while (clk32() - cstart < (job ? T_REST : T_WLATE)) __nanosleep(100);
                float macc[8] = {0.f, 0.f, 0.f, 0.f, 0.f, 0.f, 0.f, 0.f};
                #pragma unroll 1
                for (int q = -2; q < nr; q++) {
                    if (q >= 0) {
                        mbar_wait(fb + (q & 1) * 8, (q >> 1) & 1);
                        const uint32_t sv0 = sb + OFF_SILU + (row0 + q * 64 + g) * 2, wa = buf + (q & 1) * 4096u + lane * 16u;
                        #pragma unroll JUU
                        for (int i = 0; i < 8; i += 2) {
                            const uint32_t s0 = lds16(sv0 + i * 16), s1 = lds16(sv0 + i * 16 + 16);
                            const uint4 w0 = lds128(wa + i * 512u), w1 = lds128(wa + i * 512u + 512u);
                            fma8(macc, w0, bf_lo(s0)); fma8(macc, w1, bf_lo(s1));
                        }
                    }
                    __syncwarp();
                    if (q + 2 < nr) {
                        expect_tx_e(fb + (q & 1) * 8, 4096);
                        TMA_M(buf + (q & 1) * 4096u, &tmR, c0, row0 + (q + 2) * 64, fb + (q & 1) * 8);
                    }
                }
                stsf(sb + OFF_RED0 + (job ? hw * 256 + (c * 8 + g) * 4 : mod_pos(hw * 2 + (c >> 1), g) + (c & 1) * 8), reduce8(macc, lane));
                bar_sync(4, 64);
                if (w4 == 2) {
                    const uint4 u0 = lds128(sb + OFF_RED0 + (lane & 15) * 16), u1 = lds128(sb + OFF_RED0 + 256 + (lane & 15) * 16);
                    const float v0 = __uint_as_float(u0.x) + __uint_as_float(u1.x), v1 = __uint_as_float(u0.y) + __uint_as_float(u1.y);
                    const float v2 = __uint_as_float(u0.z) + __uint_as_float(u1.z), v3 = __uint_as_float(u0.w) + __uint_as_float(u1.w);
                    const uint32_t add = (b >> 5) == 2 ? ONE2 : 0u;
                    if (job == 0) { if (lane < 16) st_ll(p.s->mp + b * 16 + lane, u0.x, u0.y, u0.z, low_bits(__uint_as_float(u0.w), tag2)); TS(13); }
                    else { if (lane < 8) st_ll(p.s->rest + b * 8 + lane, hadd2(pack2(v0, v1), add), hadd2(pack2(v2, v3), add), 0, tag); TS(33); }
                }
                bar_sync(4, 64);
            }
            tmap_prefetch(hw ? &tmWo : &tmG); tmap_prefetch(hw ? &tmU : &tmD); tmap_prefetch(hw ? &tmPhi : &tmO);
        }
        __syncwarp();
        cluster_wait();
        bar_sync(2, 128);
        if ((FPOS == 1 || FPOS == 2) && w4 == 1) fence_rel_gpu();
        if (FPOS == 2) bar_sync(2, 128);
        reg_inc<504 - 2 * CREG>();
        if (w4 == 0) TS(6);
        #pragma unroll 1
        for (int pp = 0; pp < 2; pp++) {
            mbar_wait(BAR(B_PHI + pp), 0);
            if (w4 == 0) TS(pp ? 59 : 52);
            fence_async_smem();
            float o[2][20];
            const uint32_t vb = OFF_V + pp * 16384u;
            const uint64_t dp = mk_desc(sb + (pp ? OFF_PHI1 : OFF_PHI0), 16, 1024, 1), dv = mk_desc(sb + vb, OFF_ONES - vb, 512, 2);
            wg_fence();
            #pragma unroll
            for (int hh = 0; hh < 2; hh++) {
                #pragma unroll
                for (int ks = 0; ks < 8; ks++)
                    wgmma_n40_ss<1, 1>(o[hh], desc_add(dp, hh * 16384 + ks * 2048), desc_raw(dv, (hh * 8 + ks) * (64 - (64 << 16))), ks);
                wg_commit();
            }
            #pragma unroll
            for (int hh = 0; hh < 2; hh++) {
                if (hh) wg_wait<0>(); else wg_wait<1>();
                acc_fence(o[hh]);
                if (hh) arrive_one(BAR(B_KVD + pp));
                if (hh == KVSH && pp && w4 < 2) {
                    mbar_wait(BAR(B_KVD), 0);
                    bulk_load_e(sb + OFF_KVS + w4 * 8192u, p.s->kvp + ((hg * 4 + w4) * 16 + rb) * 512, 8192, BAR(B_RF + w4));
                    expect_tx_e(BAR(B_RF + w4), 8192);
                }
                uint4* dst = p.s->kvp + (((hg * 4 + 2 * pp + hh) * 16 + (t >> 3)) * 16 + rb) * 32 + (t & 7);
                const float (&a)[20] = o[hh];
                #pragma unroll
                for (int k = 0; k < 2; k++) {
                    const uint32_t z = __float_as_uint(a[16 + 2 * k]);
                    st_ll(dst + k * 8, low_byte<1>(a[4 * k], z), low_byte<2>(a[4 * k + 1], z), low_byte<3>(a[4 * k + 2], z), low_bits(a[4 * k + 3], tag2));
                    st_ll(dst + 16 + k * 8, __float_as_uint(a[8 + 4 * k]), __float_as_uint(a[9 + 4 * k]), __float_as_uint(a[10 + 4 * k]), low_bits(a[11 + 4 * k], tag2));
                }
            }
        }
        if (w4 == 0) TS(17);
        {
            uint4* const fin = p.s->kvf + (hg * 4 + w4) * 288;
            {
                const uint4* src = p.s->kvp + ((hg * 4 + w4) * 16 + rb) * 512 + lane;
                uint4 w[16];
                if (w4 >= 2) {
                    const uint32_t c0 = clk32();
                    mbar_wait(BAR(B_KVD + 1), 0);
                    while (clk32() - c0 < KVDLY - (3 - w4) * KVD2) {}
                    if (STG23) {
                        bulk_load_e(sb + OFF_KVS + w4 * 8192u, src - lane, 8192, BAR(B_RF + w4));
                        expect_tx_e(BAR(B_RF + w4), 8192);
                    }
                }
                if (STG23 || w4 < 2) {
                    mbar_wait(BAR(B_RF + w4), 0);
                    if (w4 == 3) TS(58);
                    #pragma unroll
                    for (int i = 0; i < 16; i++) w[i] = lds128(sb + OFF_KVS + w4 * 8192u + i * 512u + lane * 16u);
                } else {
                    #pragma unroll
                    for (int i = 0; i < 16; i++) w[i].w = EMPTY;
                }
                #pragma unroll 1
                for (int it = 0; it < POLL_MAX; it++) {
                    uint32_t bad = 0;
                    #pragma unroll
                    for (int i = 0; i < 16; i++) bad |= w[i].w ^ tag2;
                    if (__all_sync(0xffffffffu, !(bad & 3))) break;
                    #pragma unroll
                    for (int i = 0; i < 16; i++) ld_ll_if(w[i], src + i * 32, !tagged2(w[i].w, tag2));
                }
                if (w4 == 0) TS(18);
                if (w4 == 3) TS(10);
                float s[5], s2[5];
                #pragma unroll
                for (int i = 0; i < 16; i++) {
                    const float z = __uint_as_float(__byte_perm(__byte_perm(w[i].x, w[i].y, 0x0400), w[i].z, 0x4210));
                    float (&a)[5] = (i & 1) ? s2 : s;
                    if (i < 2) { a[0] = __uint_as_float(w[i].x); a[1] = __uint_as_float(w[i].y); a[2] = __uint_as_float(w[i].z); a[3] = __uint_as_float(w[i].w); a[4] = z; }
                    else { a[0] += __uint_as_float(w[i].x); a[1] += __uint_as_float(w[i].y); a[2] += __uint_as_float(w[i].z); a[3] += __uint_as_float(w[i].w); a[4] += z; }
                }
                #pragma unroll
                for (int i = 0; i < 5; i++) s[i] += s2[i];
                char* d = (char*)fin + ((rb >> 2) * 16 + (rb & 3) * 2 + (g & 1)) * 64 + (((lane >> 3) ^ (rb & 3)) << 4) + c * 4;
                st_ll4(d, pack2(s[0], s[1]));
                st_ll4(d + 512, pack2(s[2], s[3]));
                if (lane < 16 && c < 2) st_ll4((char*)fin + 4096 + rb * 32 + (g * 2 + c) * 4, pack2(s[4], s[4]));
            }
            if (w4 == 3) TS(48);
            mbar_wait(BAR(B_PF), 1);
            fence_acq_gpu();
            uint4 v[9];
            #pragma unroll 1
            for (int it = 0; it < POLL_MAX; it++) {
                uint32_t m = 0;
                #pragma unroll
                for (int k = 0; k < 9; k++) v[k] = ld_ll(fin + k * 32 + lane);
                #pragma unroll
                for (int k = 0; k < 9; k++) m = max(m, umax4(v[k]));
                if (__all_sync(0xffffffffu, m != EMPTY)) break;
            }
            #pragma unroll
            for (int k = 0; k < 8; k++) sts128(sb + OFF_SP + w4 * 4096u + k * 512u + lane * 16u, v[k]);
            const uint32_t za = sb + OFF_Z + ((lane >> 3) * 16 + ((lane >> 1) & 3) * 2 + (lane & 1) * 8) * 64u + ((w4 ^ ((lane >> 1) & 3)) << 4);
            sts128(za, make_uint4(v[8].x, v[8].x, v[8].x, v[8].x)); sts128(za + 64, make_uint4(v[8].z, v[8].z, v[8].z, v[8].z));
            __syncwarp();
            arrive_one(BAR(B_KVF + (w4 >> 1)));
            if (w4 == 0) TS(19);
            if (w4 == 3) TS(1);
        }
        if (w4 == 0) {
            const unsigned* f = (const unsigned*)(p.s->flo + (rb * 16 + d_block(hg, lane & 15)) * 2);
            const uint4* const a0 = p.s->os + rb * 16384;
            uint32_t seen = 0;
            uint32_t kb = hg ? 0 : 2, s = 4, freeb = BAR(B_OWN), par = 0;
            if (FDLY) { pause(FDLY); seen |= __ballot_sync(0xffffffffu, ld_rlx(f) == tag); fence_acq_gpu(); }
            mbar_wait(BAR(B_OWN), 0);
            fence_async_smem();
            bulk_store_e(p.s->os + (rb * 16 + 2 * hg) * 1024, sb + OFF_OWN, 16384);
            bulk_commit();
            bool flagged = false;
            #pragma unroll 1
            for (int n = 2; n < 16; n++) {
                if (!flagged && (n == 4 || !((seen >> n) & 1))) {
                    flagged = true;
                    if (FPOS == 4) mbar_wait(BAR(B_REL), 0);
                    bulk_wait();
                    st_flag_e(p.s->flo + (rb * 16 + 2 * hg) * 2, tag);
                    TS(3);
                    TR(0);
                }
                if (!((seen >> n) & 1)) {
                    if (n >= 8) asm volatile("ld.acquire.cta.shared.u32 %0, [%1];" : "=r"(seen) : "r"(sb + OFF_SEEN) : "memory");
                    #pragma unroll 1
                    for (int it = 0; it < POLL_MAX && !((seen >> n) & 1); it++) { seen = __ballot_sync(0xffffffffu, ld_rlx(f) == tag); fence_acq_gpu(); }
                }
                mbar_wait(freeb, par);
                TR(64 + n);
                bulk_load_e(sb + OFF_DA + s * 16384u, a0 + kb * 1024, 16384, BAR(B_FA + s));
                expect_tx_e(BAR(B_FA + s), 16384);
                if (n == 2) TS(2);
                TR(16 + n);
                if (n == OGATE) arrive_one(BAR(B_OGO));
                if (n == 6) mbar_wait(BAR(B_PUB + 1), 0);
                kb = n == 8 ? 1 : kb + 2;
                if ((kb >> 1) == hg) kb += 2;
                s = (SLOT_A >> (4 * n + 4)) & 7;
                if (n >= 5) { freeb = BAR(B_ED + n - 5); par = 1; } else if (n == 3) freeb = BAR(B_OWN + 1);
            }
        } else if (w4 == 1) {
            if (ffn) { expect_tx_e(BAR(B_GU), 98304); expect_tx_e(BAR(B_WD), 65536); }
            if (FPOS == 4) { fence_rel_gpu(); arrive_one(BAR(B_REL)); }
            mbar_wait(BAR(B_S0FREE), 0);
            if (BD0) pause(BD0);
            #pragma unroll 1
            for (int n = 2; n < (ffn ? 20 : 16); n++) {
                if (n == BG1) mbar_wait(BAR(B_KVF + 1), 0);
                if (n == BG2) mbar_wait(BAR(B_OWN), 0);
                if (BSP && n < 6) pause(BSP);
                if (n == BG5) mbar_wait(BAR(B_OGO), 1);
                if (n >= 6) mbar_wait(BAR(B_ED + n - 6), 1);
                if (n < 16) {
                    const uint32_t s = (SLOT_B >> (4 * n)) & 7, bar = BAR(B_FB + s), dst = sb + OFF_DB + s * 16384u;
                    expect_tx_e(bar, 16384);
                    if (MCB && n >= 6) tma2_mc_e(dst + rank * 8192u, &tmWo, hg * 128 + rank * 64, d_block(hg, n) * 64, bar);
                    else { TMA_WO(dst, &tmWo, hg * 128, d_block(hg, n) * 64, bar); TMA_WO(dst + 8192u, &tmWo, hg * 128 + 64, d_block(hg, n) * 64, bar); }
                    if (ffn && n >= GBN && n < GBN + 2) TMA_F(sb + OFF_GB + (n - GBN) * 16384u, n > GBN ? &tmU : &tmG, pr * 64, rank * 512 + 128, BAR(B_GU));
                } else if (n < 18) {
                    if (n == 16) TS(49);
                    TMA_F(sb + OFF_UP0 + (n & 1) * 16384u, (n & 1) ? &tmU : &tmG, pr * 64, rank * 512 + 256, BAR(B_GU));
                    TMA_F(sb + OFF_UP1 + (n & 1) * 16384u, (n & 1) ? &tmU : &tmG, pr * 64, rank * 512 + 384, BAR(B_GU));
                } else {
                    tma3_ef_e(sb + OFF_DN0 + (n & 1) * 16384u, &tmD, pr * 64, rank * 8 + (n & 1) * 2, BAR(B_WD));
                    tma3_ef_e(sb + OFF_DN1 + (n & 1) * 16384u, &tmD, pr * 64, rank * 8 + 4 + (n & 1) * 2, BAR(B_WD));
                }
            }
        } else if (w4 == 3) {
            const unsigned* f = (const unsigned*)(p.s->flo + (rb * 16 + d_block(hg, lane & 15)) * 2);
            uint32_t seen = 0xffff0003u;
            mbar_wait(BAR(B_PUB + 1), 0);
            #pragma unroll 1
            for (int it = 0; it < POLL_MAX && seen != 0xffffffffu; it++) {
                const uint32_t m = seen | __ballot_sync(0xffffffffu, !((seen >> lane) & 1) && ld_rlx(f) == tag);
                if (m != seen) {
                    seen = m;
                    fence_acq_gpu();
                    __syncwarp();
                    asm volatile(EL "st.release.cta.shared.u32 [%0], %1;\n}" :: "r"(sb + OFF_SEEN), "r"(seen) : "memory");
                }
            }
        } else {
            if (OGATE) mbar_wait(BAR(B_OGO), 1);
            mbar_wait(BAR(B_OWN + 1), 0);
            fence_async_smem();
            #pragma unroll 1
            for (uint32_t i = 0, due = clk32() + OP0; i < OPN; i++, due += OPS) {
                while ((int)(clk32() - due) < 0) {}
                bulk_store_e(p.s->os + (rb * 16 + 2 * hg + 1) * 1024 + i * (1024 / OPN), sb + OFF_OWN + 16384u + i * (16384 / OPN), 16384 / OPN);
            }
            bulk_commit();
            if (FPOS == 4) mbar_wait(BAR(B_REL), 0);
            bulk_wait();
            st_flag_e(p.s->flo + (rb * 16 + 2 * hg + 1) * 2, tag);
            arrive_one(BAR(B_PUB + 1));
            TR(1);
            {
                uint4 w[4];
                poll_words<4>(w, p.s->rest + hg * 32 + lane, 256, tag);
                sts64(sb + OFF_PAR + lane * 8, w[2].x, w[2].y); sts64(sb + OFF_PAR + 256 + lane * 8, w[1].x, w[1].y);
                sts64(sb + OFF_PAR + 512 + lane * 8, w[3].x, w[3].y); sts64(sb + OFF_PAR + 768 + lane * 8, w[0].x, w[0].y);
                const uint2 wr = ldg64(p.wr + hg * 128 + lane * 4);
                sts64(sb + OFF_BQ + lane * 8, hmul2(w[2].x, wr.x), hmul2(w[2].y, wr.y));
            }
            float s = 0.f;
            #pragma unroll 1
            for (int i = 0; i < 2; i++) {
                uint4 w[4]; uint2 wr[4];
                #pragma unroll
                for (int q = 0; q < 4; q++) wr[q] = ldg64(p.wr + (lane + 32 * q + 128 * i) * 4);
                poll_words<4>(w, p.s->rest + 512 + i * 128 + lane, 32, tag);
                #pragma unroll
                for (int q = 0; q < 4; q++) { const uint32_t r0 = hmul2(w[q].x, wr[q].x), r1 = hmul2(w[q].y, wr[q].y); s += (bf_lo(r0) + bf_hi(r0)) + (bf_lo(r1) + bf_hi(r1)); }
            }
            __syncwarp();
            #pragma unroll
            for (int m = 16; m >= 1; m >>= 1) s += shfl_x(s, m);
            if (lane == 0) { stsf(sb + OFF_ATOT, s); sts128(sb + OFF_BQ + 272, make_uint4(ONE2, ONE2, ONE2, ONE2)); }
            __syncwarp();
            arrive_one(BAR(B_PAR));
        }
        __syncwarp();
        {
            mbar_wait(BAR(B_PAR), 0);
            const uint4 pa = lds128(sb + OFF_PAR + (lane & 15) * 16), ps = lds128(sb + OFF_PAR + 256 + (lane & 15) * 16);
            const uint4 wr = ldg128(p.wr + hg * 128 + (lane & 15) * 8);
            const float atot = ldsf(sb + OFF_ATOT);
            mbar_wait(BAR(XGATE), 0);
            if (w4 == 0) TS(37);
            uint4 w;
            #pragma unroll 1
            for (int it = 0; it < POLL_MAX; it++) {
                w = ld_ll(p.s->st2 + rb * 128 + t);
                if (__all_sync(0xffffffffu, __uint_as_float(w.w) == 8.0f)) break;
            }
            if (w4 == 0) TS(31);
            uint32_t m2; float rinv;
            ln_final(__uint_as_float(w.x), __uint_as_float(w.y), m2, rinv);
            uint32_t k[1] = {(f2key(fmaf(-bf_lo(m2), atot, __uint_as_float(w.z)) * rinv) & ~0xfffu) | ((2047 - rb * 128 - t) << 1)};
            const uint32_t best0 = pop_max(k), best1 = pop_max(k) | 1u, grp = rb * 4 + w4;
            if (hg == 0 && lane < 2) st_ll(p.s->cand + grp * 2 + lane, best0, best1, 0, tag);
            if (w4 == 3) TS(23);
            const uint32_t row = 127 - (((lane < 16 ? best0 : best1) >> 1) & 127u);
            mbar_wait(BAR(B_X2), 0);
            const uint4 xv = lds128(sb + OFF_OUT + (row >> 3) * 2048u + ((lane >> 3) & 1) * 1024u + (row & 7) * 128u + (((lane ^ row) & 7) << 4));
            sts64(sb + OFF_ST2 + t * 8, m2, __float_as_uint(rinv));
            __syncwarp();
            arrive_one(BAR(B_ST2));
            const uint32_t rm = __shfl_sync(0xffffffffu, m2, row & 31);
            const Recip rr = split_recip(__shfl_sync(0xffffffffu, rinv, row & 31));
            const uint32_t h0 = ln_pair(xv.x, rm, rr, pa.x, ps.x), h1 = ln_pair(xv.y, rm, rr, pa.y, ps.y);
            const uint32_t h2 = ln_pair(xv.z, rm, rr, pa.z, ps.z), h3 = ln_pair(xv.w, rm, rr, pa.w, ps.w);
            uint4* d = p.s->rowh + (grp * 2 + (lane >> 4)) * 128 + hg * 16 + (lane & 15);
            st_ll(d, h0, h1, h2, h3);
            st_ll(d + 16384, xv.x, xv.y, xv.z, xv.w);
            float r = (fmaf(bf_lo(h0), bf_lo(wr.x), bf_hi(h0) * bf_hi(wr.x)) + fmaf(bf_lo(h1), bf_lo(wr.y), bf_hi(h1) * bf_hi(wr.y)))
                    + (fmaf(bf_lo(h2), bf_lo(wr.z), bf_hi(h2) * bf_hi(wr.z)) + fmaf(bf_lo(h3), bf_lo(wr.w), bf_hi(h3) * bf_hi(wr.w)));
            #pragma unroll
            for (int m = 8; m >= 1; m >>= 1) r += shfl_x(r, m);
            if (!(lane & 15)) st_ll(p.s->rsc + (grp * 8 + hg) * 2 + (lane >> 4), __float_as_uint(r), 0, 0, tag);
            if (w4 == 3) TS(24);
        }
        if (w4 == 0) {
            uint4 cv[2];
            poll_words<2>(cv, p.s->cand + lane * 2, 64, tag);
            __syncwarp();
            TS(11);
            const uint32_t ka = min(cv[0].x, cv[1].x), kb = max(cv[0].y, cv[1].y);
            uint32_t k0 = max(cv[0].x, cv[1].x), k1 = max(ka, kb), k2 = min(ka, kb), k3 = min(cv[0].y, cv[1].y), id[4];
            uint4 hv[4][2], sc;
            const uint4* ha[4];
            #pragma unroll
            for (int i = 0; i < 4; i++) {
                const uint32_t m = __reduce_max_sync(0xffffffffu, k0);
                if (k0 == m) { k0 = k1; k1 = k2; k2 = k3; }
                id[i] = (m & 0xfffu) ^ 0xffeu;
                ha[i] = p.s->rowh + ((id[i] >> 6) * 2 + (id[i] & 1)) * 128 + rank * 64 + lane;
                hv[i][0] = ld_ll(ha[i]); hv[i][1] = ld_ll(ha[i] + 32);
            }
            const uint32_t myid = lane < 16 ? (lane < 8 ? id[0] : id[1]) : (lane < 24 ? id[2] : id[3]), row = myid >> 1;
            const uint4* sa = p.s->rsc + ((myid >> 6) * 8 + (lane & 7)) * 2 + (myid & 1);
            sc = ld_ll(sa);
            sts32(sb + OFF_SEL + 32 + (lane >> 3) * 4, row);
            __syncwarp();
            arrive_one(BAR(B_CAND));
            #pragma unroll 1
            for (int it = 0; it < POLL_MAX; it++) {
                uint32_t m = 0;
                #pragma unroll
                for (int i = 0; i < 4; i++) m = max(m, max(hv[i][0].x, hv[i][1].x));
                if (__all_sync(0xffffffffu, m != EMPTY && sc.w == tag)) break;
                #pragma unroll
                for (int i = 0; i < 4; i++) { hv[i][0] = ld_ll(ha[i]); hv[i][1] = ld_ll(ha[i] + 32); }
                sc = ld_ll(sa);
            }
            TS(12);
            #pragma unroll
            for (int i = 0; i < 4; i++) { sts128(sb + OFF_ROWS + i * 1056u + lane * 16u, hv[i][0]); sts128(sb + OFF_ROWS + i * 1056u + 528u + lane * 16u, hv[i][1]); }
            __syncwarp();
            arrive_one(BAR(B_ROWS));
            TS(25);
            float r = __uint_as_float(sc.x);
            r += shfl_x(r, 1); r += shfl_x(r, 2); r += shfl_x(r, 4);
            r = rbf(r);
            const uint32_t key = (f2key(r) & 0xffff0000u) | (0xffffu - row);
            uint32_t kq[1] = {key};
            const uint32_t best0 = pop_max(kq), best1 = pop_max(kq), tok = key == best0 ? 0 : key == best1 ? 1 : 2;
            sts32(sb + OFF_SEL + 48 + (lane >> 3) * 4, tok);
            if (tok < 2) sts128(sb + OFF_SEL + tok * 16, make_uint4(row, (myid >> 6) * 2 + (myid & 1), __float_as_uint(r), 0));
            __syncwarp();
            arrive_one(BAR(B_SEL));
        } else if (w4 == 1) {
            mbar_wait(BAR(B_SEL), 0);
            const uint4 sel = lds128(sb + OFF_SEL + rank * 16);
            const int col = pr * 16 + c * 2 + (lane >> 4) + (lane & 8);
            uint32_t xs, hs; uint4 gw;
            #pragma unroll 1
            for (int it = 0; it < POLL_MAX; it++) {
                const char* a = (const char*)(p.s->rowh + sel.y * 128) + (col >> 1) * 4;
                hs = ld_rlx(a); xs = ld_rlx(a + 262144); gw = ld_ll(p.s->rest + 768 + (col >> 2));
                if (__all_sync(0xffffffffu, hs != EMPTY && xs != EMPTY && gw.w == tag)) break;
            }
            const uint32_t gq = (col & 2) ? gw.y : gw.x;
            const float fx = (col & 1) ? bf_hi(xs) : bf_lo(xs), fh = (col & 1) ? bf_hi(hs) : bf_lo(hs), fg = (col & 1) ? bf_hi(gq) : bf_lo(gq);
            const float sg = rbf(sigmoidf(__uint_as_float(sel.z)));
            const uint4* src = p.s->yp + g * 512 + rank * 256 + pr * 4 + c;
            bf16* optr = p.out + (size_t)sel.x * 1024 + col;
            asm volatile("" : "+l"(optr));
            uint4 w[7];
            #pragma unroll
            for (int i = 0; i < 7; i++) w[i] = make_uint4(0, EMPTY, 0, EMPTY);
            if (ffn) mbar_wait(BAR(YGATE), 0);
            if (YDLY) { const uint32_t c0 = clk32(); while (clk32() - c0 < (ffn ? YDLY : YDLY + 1500)) {} }
            #pragma unroll 1
            for (int it = 0; it < POLL_MAX; it++) {
                bool ok = true;
                #pragma unroll
                for (int i = 0; i < 7; i++) ld_ll_if(w[i], src + i * 4096, !(tagged2(w[i].y, tag2) && tagged2(w[i].w, tag2)));
                #pragma unroll
                for (int i = 0; i < 7; i++) ok = ok && tagged2(w[i].y, tag2) && tagged2(w[i].w, tag2);
                if (__all_sync(0xffffffffu, ok)) break;
            }
            TS(29);
            float y0 = __uint_as_float(w[0].x), y1 = __uint_as_float(w[0].y), y2 = __uint_as_float(w[0].z), y3 = __uint_as_float(w[0].w);
            #pragma unroll
            for (int i = 1; i < 7; i++) { y0 += __uint_as_float(w[i].x); y1 += __uint_as_float(w[i].y); y2 += __uint_as_float(w[i].z); y3 += __uint_as_float(w[i].w); }
            const bool b4 = lane & 16, b3 = lane & 8;
            const float a0 = (b4 ? y2 : y0) + shfl_x(b4 ? y0 : y2, 16), a1 = (b4 ? y3 : y1) + shfl_x(b4 ? y1 : y3, 16);
            float y = (b3 ? a1 : a0) + shfl_x(b3 ? a0 : a1, 8);
            y += shfl_x(y, 4);
            const float upd = rbf(rbf(y) * sg);
            if (!(lane & 4)) *optr = __float2bfloat16(fx + rbf(fg * rbf(fh + upd)));
            if (b == 0 && lane == 0) p.s->done[0] = tag;
            TS(28);
            if (!GS2) GS(6);
        } else if (w4 == 2) {
            mbar_wait(BAR(OUTGATE), 0);
            const uint32_t cg = (lds32(sb + OFF_SEL + 32 + c * 4) >> 3) - rb * 16;
            uint32_t late = __reduce_or_sync(0xffffffffu, cg < 16 ? 1u << cg : 0u);
            mbar_wait(BAR(B_OUTW), 0);
            fence_async_smem();
            #pragma unroll 1
            for (uint32_t i = 0; i < 16; i++)
                if (!((late >> i) & 1))
                    asm volatile(EL "cp.async.bulk.tensor.3d.global.shared::cta.bulk_group [%0, {0, %2, %3}], [%1];\n}"
                        :: "l"(&tmO), "r"(sb + OFF_OUT + i * 2048u), "r"(rb * 128 + i * 8), "r"(hg * 2) : "memory");
            bulk_commit();
            mbar_wait(BAR(B_SEL), 0);
            const uint32_t row0 = lds32(sb + OFF_SEL) - rb * 128, row1 = lds32(sb + OFF_SEL + 16) - rb * 128;
            #pragma unroll 1
            for (; late; late &= late - 1) {
                const uint32_t i = __ffs(late) - 1;
                #pragma unroll 1
                for (uint32_t q = 0; q < 4; q++) {
                    const uint32_t r = q * 2 + (lane >> 4), ch = lane & 15;
                    const uint4 v = lds128(sb + OFF_OUT + i * 2048u + (ch >> 3) * 1024u + r * 128u + (((ch ^ r) & 7) << 4));
                    if (i * 8 + r != row0 && i * 8 + r != row1) stg128(p.out + (size_t)(rb * 128 + i * 8 + r) * 1024 + hg * 128 + ch * 8, v);
                }
            }
            bulk_wait();
            TS(35);
        }
    } else {
        const int w4 = warp & 3, wgi = warp >> 2;
        uint32_t m2[2], r[4]; Recip ri0, ri1;
        uint32_t tag2;
        {
            const int g = lane >> 2, c = lane & 3, xrow = b * 16 + warp * 2;
            if (b < NW0)
                asm volatile("prefetch.global.L2 [%0];" :: "l"(p.wmod + (size_t)((b & 3) * 256 + tid) * 6144 + (((b >> 2) & 1) ? 0 : 1024) + (b >> 3) * 64));
            const uint2 cv = ldg64(p.c + tid * 4);
            const uint32_t tag = ld_rlx(p.s->done) + 1;
            if (lane < 2) stg_fill(p.s->st1 + xrow + lane, 0);
            if (warp == 0 && lane < 16 && b < 32 * NC) stg_fill(p.s->mp + b * 16 + lane, EMPTY);
            if (tid < 64) { int s = tid >> 2; sts128(sb + OFF_ONES + tid * 16, make_uint4(((tid & 3) == ((s >> 1) & 3)) ? 0x3F80u : 0u, 0, 0, 0)); }
            cluster_arrive();
            reg_inc<CG1>();
            {
                const float c0 = bf_lo(cv.x), c1 = bf_hi(cv.x), c2 = bf_lo(cv.y), c3 = bf_hi(cv.y);
                sts64(sb + OFF_SILU + tid * 8, pack2(c0 * sigmoidf(c0), c1 * sigmoidf(c1)), pack2(c2 * sigmoidf(c2), c3 * sigmoidf(c3)));
            }
            tag2 = tag % 3u;
            bar_sync(0, 384);
            bar_arrive(3, 320);
            if (warp == 0) TS(47);
            if (!GS2 && warp == 1) GS(0);
            #pragma unroll 1
            for (int part = 0; part < 2; part++)
            if (part == (b < NW0)) {
                mbar_wait(BAR(B_XS + (warp >> 1)), 0);
                if (warp == 7) TS(60);
                if (warp == 0) TS(54);
                float sd[2][4], q1[2][4], q2[2][4];
                #pragma unroll
                for (int e = 0; e < 4; e++) { sd[0][e] = sd[1][e] = q1[0][e] = q1[1][e] = q2[0][e] = q2[1][e] = 0.f; }
                #pragma unroll
                for (int i = 0; i < 8; i++) {
                    uint32_t a0, a1, a2, a3;
                    ldsm4(a0, a1, a2, a3, sb + OFF_XS + warp * 4096u + ((lane >> 3) & 1) * 2048u + i * 256u + (lane >> 4) * 128u + (lane & 7) * 16u);
                    mma16816(sd[i & 1], a0, a1, a2, a3, ONE2, ONE2);
                    mma1688(q1[0], a0, a1, a0); mma1688(q2[0], a0, a1, a1); mma1688(q1[1], a2, a3, a2); mma1688(q2[1], a2, a3, a3);
                }
                if (warp == 0) TS(30);
                const float d0 = __shfl_sync(0xffffffffu, (g & 1) ? q1[0][1] + q1[1][1] : q1[0][0] + q1[1][0], g * 4 + (g >> 1));
                const float d1 = __shfl_sync(0xffffffffu, (g & 1) ? q2[0][3] + q2[1][3] : q2[0][2] + q2[1][2], g * 4 + (g >> 1));
                float sk = (c & 1) ? sd[0][2] + sd[1][2] : sd[0][0] + sd[1][0], qk = (c & 1) ? d1 : d0;
                #pragma unroll
                for (int m = 4; m <= 16; m <<= 1) { sk += shfl_x(sk, m); qk += shfl_x(qk, m); }
                uint32_t mm; float ri;
                ln_final(sk, qk, mm, ri);
                const Recip rr = split_recip(ri);
                if (lane < 2) st_ll(p.s->st1 + xrow + lane, mm, rr.hi, rr.lo, tag);
                if (warp == 0) TS(14);
                if (warp == 7) TS(61);
            } else if (b < 32 * NC) {
                float m[4][4];
                uint32_t sv[4];
                ldsm4(sv[0], sv[1], sv[2], sv[3], sb + OFF_SILU + ((b & 3) * 256 + warp * 32) * 2 + (lane >> 3) * 16);
                mbar_wait(BAR(B_WS + (warp >> 1)), 0);
                if (warp == 7) TS(55);
                #pragma unroll
                for (int tt = 0; tt < 4; tt++) {
                    m[tt][0] = m[tt][1] = m[tt][2] = m[tt][3] = 0.f;
                    #pragma unroll
                    for (int e = 0; e < 2; e++) {
                        uint32_t a0, a1, a2, a3;
                        ldsm4t(a0, a1, a2, a3, sb + OFF_WST + warp * 4096u + (e * 16 + (lane & 7) + ((lane >> 4) << 3)) * 128u + (((2 * tt + ((lane >> 3) & 1)) ^ (lane & 7)) << 4));
                        mma16816(m[tt], a0, a1, a2, a3, sv[2 * e], sv[2 * e + 1]);
                    }
                }
                if (warp == 0) TS(46);
                const uint32_t ra = sb + OFF_RED0 + warp * 256 + mod_pos(c, g);
                stsf(ra, (c & 2) ? ((c & 1) ? m[3][0] : m[2][0]) : ((c & 1) ? m[1][0] : m[0][0]));
                stsf(ra + 8, (c & 2) ? ((c & 1) ? m[3][2] : m[2][2]) : ((c & 1) ? m[1][2] : m[0][2]));
                if (warp != 7) bar_arrive(5, 256);
                else {
                    bar_sync(5, 256);
                    float v0 = 0.f, v1 = 0.f, v2 = 0.f, v3 = 0.f;
                    #pragma unroll
                    for (int w = 0; w < 4; w++) {
                        const uint4 u = lds128(sb + OFF_RED0 + w * 512 + lane * 16);
                        v0 += __uint_as_float(u.x); v1 += __uint_as_float(u.y); v2 += __uint_as_float(u.z); v3 += __uint_as_float(u.w);
                    }
                    v0 += shfl_x(v0, 16); v1 += shfl_x(v1, 16); v2 += shfl_x(v2, 16); v3 += shfl_x(v3, 16);
                    if (lane < 16) st_ll(p.s->mp + b * 16 + lane, __float_as_uint(v0), __float_as_uint(v1), __float_as_uint(v2), low_bits(v3, tag2));
                    TS(45);
                }
            }
            if (!LATEFREE) arrive_one(BAR(B_STFREE));
            cluster_wait();
            uint4 st[2];
            bool need = warp < NW0 / 8;
            #pragma unroll 1
            for (int it = 0; it < POLL_MAX; it++) {
                st[0] = ld_ll(p.s->st1 + rb * 128 + warp * 16 + g); st[1] = ld_ll(p.s->st1 + rb * 128 + warp * 16 + g + 8);
                if (need) {
                    const uint4* src = p.s->mp + (warp * 8 + (lane >> 4) * 4) * 16 + (lane & 15);
                    const uint4 w0 = ld_ll(src), w1 = ld_ll(src + 16), w2 = ld_ll(src + 32), w3 = ld_ll(src + 48);
                    if (__all_sync(0xffffffffu, mod_collect(w0, w1, w2, w3, sb, warp, lane, tag2))) {
                        need = false;
                        arrive_many(BAR(B_MOD + warp), bar_count(B_MOD));
                        if (warp == 0) TS(51);
                    }
                }
                if (PRELD && it == 0) {
                    mbar_wait(BAR(B_F1), 0);
                    ldsm4(r[0], r[1], r[2], r[3], sb + OFF_RING + (warp * 16 + (lane & 15)) * 128u + ((((lane >> 4) ^ lane) & 7) << 4));
                }
                if (__all_sync(0xffffffffu, st[0].w == tag && st[1].w == tag) && !need) break;
            }
            m2[0] = st[0].x; ri0.hi = st[0].y; ri0.lo = st[0].z; m2[1] = st[1].x; ri1.hi = st[1].y; ri1.lo = st[1].z;
            if (LATEFREE) arrive_one(BAR(B_STFREE));
            if (warp == 0) TS(4);
        }
        const int lane = lane_id(), g = lane >> 2, c = lane & 3;
        const int srow = warp * 16 + (lane & 15);
        const uint32_t aoff = srow * 128u + ((((lane >> 4) ^ srow) & 7) << 4);
        uint32_t pt[16], qf[32];
        float pp[2][16];
        const uint32_t roff = srow * 128u + ((lane & 7) << 4);
        {
            float accKV[128], accQ[64];
            {
                uint32_t f[2][4];
                if (!PRELD) {
                    mbar_wait(BAR(B_F1), 0);
                    ldsm4(r[0], r[1], r[2], r[3], sb + OFF_RING + aoff);
                }
                mbar_wait(BAR(B_MOD), 0);
                if (warp == 0) TS(15);
                if (!GS2 && warp == 1) GS(1);
                uint4 md = lds128(sb + OFF_MODS + c * 16);
                int s = 0, sp = 1, par = 0;
                #pragma unroll 1
                for (int j = 0; j < 16; j++) {
                    const int sn = s == 0 ? 2 : s - 1;
                    par ^= s == 1;
                    const uint32_t modb = (JS && wgi && j == JS) ? BAR(B_TURN) : BAR(B_MOD + ((j + 1) & 15));
                    const uint64_t db = mk_desc(sb + OFF_RING + s * 65536u + 16384u, 8192, 1024, 1);
                    #pragma unroll
                    for (int ks = 0; ks < 4; ks++) {
                        uint32_t (&ff)[4] = f[ks & 1];
                        ff[0] = ln_pair(r[0], m2[0], ri0, md.x, md.z); ff[1] = ln_pair(r[1], m2[1], ri1, md.x, md.z);
                        ff[2] = ln_pair(r[2], m2[0], ri0, md.y, md.w); ff[3] = ln_pair(r[3], m2[1], ri1, md.y, md.w);
                        const int kn = (ks + 1) & 3;
                        ldsm4(r[0], r[1], r[2], r[3], sb + OFF_RING + (ks == 3 ? sn : s) * 65536u + (aoff ^ (kn << 5)));
                        md = lds128(sb + OFF_MODS + ((ks == 3 ? j + 1 : j) * 4 + kn) * 64 + c * 16);
                        wg_fence();
                        wgmma_n256_rs<1>(accKV, ff[0], ff[1], ff[2], ff[3], desc_add(db, 16384 + ks * 2048), ks ? 1 : j);
                        wgmma_n128_rs<1>(accQ, ff[0], ff[1], ff[2], ff[3], desc_add(db, ks * 2048), ks ? 1 : j);
                        wg_commit();
                        if (JS && ks == KT) arrive_if(BAR(B_TURN), j == 15 && !wgi);
                        if (ks == 1) mbar_wait(modb, 0);
                        if (ks == 2) { WT0(); mbar_wait(BAR(j < 15 ? B_F1 + sn : B_WPHI), j < 15 ? par : 0);
                        }
                        wg_wait<1>();
                        if (ks == 0) arrive_if(BAR(B_E1 + sp), j);
                    }
                    sp = s; s = sn;
                }
            }
            mbar_wait(BAR(B_E1 + 2), 0);
            wg_wait<0>();
            acc_fence(accKV); acc_fence(accQ);
            arrive_one(BAR(B_E1));
            if (warp == 4) TS(16);
            if (!GS2 && warp == 1) GS(2);
            uint32_t kf[32];
            #pragma unroll
            for (int h = 0; h < 4; h++) {
                if (h == VFIRST) {
                    #pragma unroll
                    for (int i = 0; i < 16; i++) kf[i] = pack2(accKV[2 * i], accKV[2 * i + 1]);
                    phi_issue(pp, kf, sb, 0);
                }
                #pragma unroll
                for (int q = 0; q < 2; q++) {
                    const int o = 64 + 16 * h + 8 * q;
                    stsm4(sb + OFF_V + h * 8192u + srow * 64u + (((2 * q + (lane >> 4)) ^ ((srow >> 1) & 3)) << 4),
                          pack2(accKV[o], accKV[o + 1]), pack2(accKV[o + 2], accKV[o + 3]), pack2(accKV[o + 4], accKV[o + 5]), pack2(accKV[o + 6], accKV[o + 7]));
                }
            }
            #pragma unroll
            for (int i = 16; i < 32; i++) kf[i] = pack2(accKV[2 * i], accKV[2 * i + 1]);
            phi_transpose(pp, pt, sb + OFF_PHI0 + aoff, sb + OFF_PHI0 + (roff ^ ((lane >> 4) << 6)));
            phi_issue(pp, kf + 16, sb, 1);
            #pragma unroll
            for (int i = 0; i < 32; i++) qf[i] = pack2(accQ[2 * i], accQ[2 * i + 1]);
            if (PREWAIT) { wg_wait<0>(); acc_fence(pp[0]); acc_fence(pp[1]); }
        }
        reg_dec<CREG>();
        if (warp == 0) TS(56);
        {
            float cp, cn;
            fm_extrema(pt, cp, cn);
            if (STAG && wgi) { const uint32_t c0 = clk32(); while (clk32() - c0 < STAG) {} }
            #pragma unroll 1
            for (int u = 0; u < 4; u++) {
                const uint32_t cur = sb + ((u & 1) ? OFF_PHI1 : OFF_PHI0);
                float e[64], s[4], cpn, cnn;
                uint32_t pn[16];
                #pragma unroll
                for (int k = 0; k < 16; k++) {
                    if (PIN && k == KW) stsf(cur + aoff, e[31 + 2 * k]);
                    if (k == KW && (!SKIP3 || u < 3)) phi_transpose(pp, pn, cur + aoff, cur + (roff ^ ((lane >> 4) << 6)));
                    if (KX && k == KX) fm_extrema(pn, cpn, cnn);
                    const float dep = (KX && k == KX) ? fabsf(cpn) + fabsf(cnn) : k >= DEP ? e[33 + 2 * (k >= DEP ? k - DEP : 0)] : 0.f, f0 = bf_lo_after(pt[k], dep), f1 = bf_hi_after(pt[k], dep);
                    e[2 * k] = ex2(fmaf(f0, LOG2E, cp)); e[2 * k + 1] = ex2(fmaf(f1, LOG2E, cp));
                    e[32 + 2 * k] = ex2(fmaf(f0, -LOG2E, cn)); e[33 + 2 * k] = ex2(fmaf(f1, -LOG2E, cn));
                    if (k == 0) { s[0] = e[0]; s[1] = e[1]; s[2] = e[32]; s[3] = e[33]; }
                    else { s[0] += e[2 * k]; s[1] += e[2 * k + 1]; s[2] += e[32 + 2 * k]; s[3] += e[33 + 2 * k]; }
                }
                if (KX) { cp = cpn; cn = cnn; } else fm_extrema(pn, cp, cn);
                #pragma unroll
                for (int i = 0; i < 16; i++) pt[i] = pn[i];
                const float sp = s[0] + s[1], sn = s[2] + s[3], r = rcp(sp * sn), rp = r * sn, rn = r * sp;
                #pragma unroll
                for (int i = 0; i < 8; i++) {
                    const float q = i < 4 ? rp : rn;
                    sts128((cur + (lane >> 4) * 16384u + roff) ^ (i << 4), make_uint4(pack2(e[8 * i] * q, e[8 * i + 1] * q), pack2(e[8 * i + 2] * q, e[8 * i + 3] * q),
                                                                                   pack2(e[8 * i + 4] * q, e[8 * i + 5] * q), pack2(e[8 * i + 6] * q, e[8 * i + 7] * q)));
                }
                __syncwarp();
                arrive_one(BAR(B_PHI + u));
                if (u == 0) { mbar_wait(BAR(B_E1 + 1), 0); phi_issue(pp, qf, sb, 0); }
                else {
                    if (KPAUSE) mbar_wait(BAR(B_PHI + 1), 0);
                    mbar_wait(BAR(B_KVD + (u != 1)), 0);
                    if (u == 1) phi_issue(pp, qf + 16, sb, 1);
                }
            }
            wg_wait<0>();
        }
        if (warp == 4) TS(57);
        if (!GS2 && warp == 1) GS(3);
        uint32_t x2[16][2], wf[32][4];
        const uint32_t woff = ((lane >> 3) & 1) * 16384u + ((lane & 7) + ((lane >> 4) << 3)) * 128u + (((warp ^ lane) & 7) << 4);
        if (LDPOS == 0) {
            mbar_wait(BAR(B_S0), 0);
            #pragma unroll
            for (int q = 0; q < 8; q++) {
                ldsm4(x2[2 * q][0], x2[2 * q][1], x2[2 * q + 1][0], x2[2 * q + 1][1], sb + OFF_XT + (q >> 2) * 16384u + (aoff ^ ((q & 3) << 5)));
                ldsm4t(wf[q][0], wf[q][1], wf[q][2], wf[q][3], sb + OFF_GA + q * 2048u + woff);
            }
            __syncwarp();
            arrive_one(BAR(B_S0FREE));
        }
        float acc[64];
        const uint64_t da0 = mk_desc(sb + OFF_DA + wgi * 8192u, 16, 1024, 1), db0 = mk_desc(sb + OFF_DB, 8192, 1024, 1);
        #pragma unroll 1
        for (int pp = 0; pp < 2; pp++) {
            float o0[20], o1[20];
            const uint64_t dk = mk_desc(sb + OFF_SP + pp * 8192u, OFF_Z - OFF_SP - pp * 8160u, 512, 2);
            const uint64_t dq = mk_desc(sb + (pp ? OFF_PHI1 : OFF_PHI0) + wgi * 8192u, 16, 1024, 1);
            mbar_wait(BAR(B_FB + 4 + pp), 0);
            mbar_wait(BAR(B_PHI + 2 + pp), 0);
            mbar_wait(BAR(B_KVF + pp), 0);
            fence_async_smem();
            wg_fence();
            #pragma unroll
            for (int ks = 0; ks < 4; ks++) {
                wgmma_n40_ss<0, 1>(o0, desc_add(dq, ks * 32), desc_add(dk, ks * 1024), ks);
                wgmma_n40_ss<0, 1>(o1, desc_add(dq, 16384 + ks * 32), desc_raw(dk, 256 + ks * 64 - (255 << 16)), ks);
            }
            wg_commit();
            wg_wait<0>();
            acc_fence(o0); acc_fence(o1);
            if (MCB) arrive_both_if(BAR(B_ED), pp); else arrive_if(BAR(B_ED), pp);
            uint32_t op[16];
            #pragma unroll
            for (int hh = 0; hh < 2; hh++) {
                const float (&o)[20] = hh ? o1 : o0;
                const Recip rd0 = split_recip(rcp(rbf(rbf(o[16]) + 1e-6f)));
                const Recip rd1 = split_recip(rcp(rbf(rbf(o[18]) + 1e-6f)));
                #pragma unroll
                for (int j = 0; j < 4; j++) { op[8 * hh + 2 * j] = hdiv2(pack2(o[4 * j], o[4 * j + 1]), rd0); op[8 * hh + 2 * j + 1] = hdiv2(pack2(o[4 * j + 2], o[4 * j + 3]), rd1); }
                #pragma unroll
                for (int q = 2 * hh; q < 2 * hh + 2; q++) stsm4(sb + OFF_OWN + pp * 16384u + (aoff ^ (q << 5)), op[4 * q], op[4 * q + 1], op[4 * q + 2], op[4 * q + 3]);
            }
            __syncwarp();
            arrive_one(BAR(B_OWN + pp));
            if (warp == 0) TS(20 + pp);
            wg_fence();
            #pragma unroll
            for (int ks = 0; ks < 4; ks++) wgmma_n128_rs<1>(acc, op[4 * ks], op[4 * ks + 1], op[4 * ks + 2], op[4 * ks + 3], desc_add(db0, (4 + pp) * 16384u + ks * 2048), ks ? 1 : pp);
            wg_commit();
        }
        const uint32_t ooff = sb + OFF_OUT + (srow >> 3) * 1024u + aoff;
        {
            const uint32_t vchk = lane * 32u + g * 4u;
            if (!GS2 && warp == 1) GS(4);
            #pragma unroll 1
            for (int n = 2; n < 16; n++) {
                const uint32_t s = (SLOT_A >> (4 * n)) & 7, sB = (SLOT_B >> (4 * n)) & 7;
                WT0();
                mbar_wait(BAR(B_FB + sB), (PAR_B >> n) & 1);
                WTJ(16 + n);
                mbar_wait(BAR(B_FA + s), (PAR_A >> n) & 1);
                WTJ(n);
                {
                    const uint32_t ra = sb + OFF_DA + s * 16384u + warp * 2048u;
                    if (__any_sync(0xffffffffu, max(lds32(ra + vchk), lds32(ra + vchk + 1024)) == EMPTY)) {
                        #pragma unroll 1
                        for (int i = 0; i < 4; i++) {
                            uint4 v;
                            #pragma unroll 1
                            for (int it = 0; it < POLL_MAX; it++) {
                                v = ld_ll(p.s->os + (rb * 16 + d_block(hg, n)) * 1024 + warp * 128 + i * 32 + lane);
                                if (umax4(v) != EMPTY) break;
                            }
                            sts128(ra + i * 512 + lane * 16, v);
                        }
                        fence_async_smem();
                        __syncwarp();
                    }
                }
                TR(32 + 16 * wgi + n);
                const uint64_t da = desc_add(da0, s * 16384u), db = desc_add(db0, sB * 16384u);
                wg_fence();
                #pragma unroll
                for (int ks = 0; ks < 4; ks++) wgmma_n128_ss<0, 1>(acc, desc_add(da, ks * 32), desc_add(db, ks * 2048), 1);
                wg_commit();
                wg_wait<1>();
                if (MCB) arrive_both_if(BAR(B_ED - 1 + n), 1); else arrive_one(BAR(B_ED - 1 + n));
            }
            mbar_wait(BAR(B_PAR), 0);
            uint32_t gar[16], bfr[16];
            #pragma unroll
            for (int j = 0; j < 16; j += 4) {
                ldsm4(gar[j], gar[j + 1], gar[j + 2], gar[j + 3], sb + OFF_PAR + 768 + (j + (lane >> 3)) * 16);
                ldsm4(bfr[j], bfr[j + 1], bfr[j + 2], bfr[j + 3], sb + OFF_BQ + ((lane & 1) ? (j + (lane >> 3)) * 16 : 272));
            }
            wg_wait<0>();
            acc_fence(acc);
            bar_arrive(6 + wgi, 256);
            if (warp == 0) TS(9);
            if (!GS2 && warp == 1) GS(5);
            float sd[2][4], q1[2][4], q2[2][4];
            #pragma unroll
            for (int e = 0; e < 4; e++) { sd[0][e] = sd[1][e] = q1[0][e] = q1[1][e] = q2[0][e] = q2[1][e] = 0.f; }
            #pragma unroll
            for (int s = 0; s < 8; s++) {
                #pragma unroll
                for (int e = 0; e < 4; e++) { const int j = 2 * s + (e >> 1), h = e & 1; x2[j][h] = hadd2(x2[j][h], hmul2(gar[j], pack2(acc[4 * j + 2 * h], acc[4 * j + 2 * h + 1]))); }
                mma16816(sd[s & 1], x2[2 * s][0], x2[2 * s][1], x2[2 * s + 1][0], x2[2 * s + 1][1], bfr[2 * s], bfr[2 * s + 1]);
                #pragma unroll
                for (int e = 0; e < 2; e++) { mma1688(q1[e], x2[2 * s + e][0], x2[2 * s + e][1], x2[2 * s + e][0]); mma1688(q2[e], x2[2 * s + e][0], x2[2 * s + e][1], x2[2 * s + e][1]); }
            }
            if (c == (g >> 1)) {
                uint4* d = p.s->st2 + rb * 128 + warp * 16 + g;
                red_add4(d, sd[0][0] + sd[1][0], (g & 1) ? q1[0][1] + q1[1][1] : q1[0][0] + q1[1][0], sd[0][1] + sd[1][1], 1.0f);
                red_add4(d + 8, sd[0][2] + sd[1][2], (g & 1) ? q2[0][3] + q2[1][3] : q2[0][2] + q2[1][2], sd[0][3] + sd[1][3], 1.0f);
            }
            arrive_one(BAR(B_RED));
            if (warp == 0) TS(22);
            bar_sync(7 - wgi, 256);
            #pragma unroll
            for (int q = 0; q < 8; q++) stsm4((ooff + (q >> 2) * 1024u) ^ ((q & 3) << 5), x2[2 * q][0], x2[2 * q][1], x2[2 * q + 1][0], x2[2 * q + 1][1]);
            __syncwarp();
            arrive_one(BAR(B_X2));
            if (warp == 0) TS(62);
        }
        const uint32_t xa = sb + OFF_OUT + warp * 4096u + ((lane >> 3) & 1) * 1024u + (lane >> 4) * 128u + (((lane ^ (lane >> 4)) & 7) << 4);
        const uint4 pa = lds128(sb + OFF_PAR + (lane & 15) * 16), ps = lds128(sb + OFF_PAR + 256 + (lane & 15) * 16), pg = lds128(sb + OFF_PAR + 512 + (lane & 15) * 16);
        if (ffn) mbar_wait(BAR(B_GU), 0);
        if (warp == 0) TS(38);
        #pragma unroll
        for (int q = 8; q < NEARLY; q++) {
            ldsm4t(wf[q][0], wf[q][1], wf[q][2], wf[q][3], sb + (q < 16 ? OFF_GB : q < 24 ? OFF_UP0 : OFF_UP1) + (q & 7) * 2048u + woff);
            if (LPACE && (q & 1)) { const uint32_t c0 = clk32(); while (clk32() - c0 < LPACE) {} }
        }
        {
            if (warp == 0) TS(39);
            mbar_wait(BAR(B_ST2), 0);
            if (warp == 0) TS(53);
            #pragma unroll 1
            for (int q0 = 0; q0 < 8; q0 += OUU) {
                uint4 x[OUU]; uint2 st[OUU];
                const uint32_t a = (xa + (q0 >> 2) * 2048u + (q0 & 3) * 256u) ^ ((q0 & 3) << 5);
                #pragma unroll
                for (int q = 0; q < OUU; q++) { x[q] = lds128((a + q * 256u) ^ (q << 5)); st[q] = lds64(sb + OFF_ST2 + (warp * 16 + (q0 + q) * 2 + (lane >> 4)) * 8); }
                #pragma unroll
                for (int q = 0; q < OUU; q++) {
                    const Recip r = split_recip(__uint_as_float(st[q].y));
                    sts128((a + q * 256u) ^ (q << 5), make_uint4(
                        hadd2(x[q].x, hmul2(pg.x, ln_pair(x[q].x, st[q].x, r, pa.x, ps.x))), hadd2(x[q].y, hmul2(pg.y, ln_pair(x[q].y, st[q].x, r, pa.y, ps.y))),
                        hadd2(x[q].z, hmul2(pg.z, ln_pair(x[q].z, st[q].x, r, pa.z, ps.z))), hadd2(x[q].w, hmul2(pg.w, ln_pair(x[q].w, st[q].x, r, pa.w, ps.w)))));
                }
            }
            __syncwarp();
            arrive_one(BAR(B_OUTW));
            if (warp == 0) TS(32);
        }
        if (ffn) {
            float acc[4][4];
            uint32_t df[4][4][4];
            {
                #pragma unroll
                for (int i = 0; i < 4; i++) { acc[i][0] = acc[i][1] = acc[i][2] = acc[i][3] = 0.f; }
                const uint32_t da = sb + (wgi ? OFF_DN1 : OFF_DN0) + w4 * 8192u + ((lane & 7) + ((lane >> 4) << 3)) * 128u;
                #pragma unroll
                for (int q = NEARLY; q < 32; q++) ldsm4t(wf[q][0], wf[q][1], wf[q][2], wf[q][3], sb + (q < 16 ? OFF_GB : q < 24 ? OFF_UP0 : OFF_UP1) + (q & 7) * 2048u + woff);
                mbar_wait(BAR(B_WD), 0);
                #pragma unroll
                for (int q = 0; q < DNE; q++)
                    ldsm4t(df[q >> 2][q & 3][0], df[q >> 2][q & 3][1], df[q >> 2][q & 3][2], df[q >> 2][q & 3][3], da + (q & 3) * 2048u + (((2 * (q >> 2) + ((lane >> 3) & 1)) ^ (lane & 7)) << 4));
                mbar_wait(BAR(B_ROWS), 0);
                #pragma unroll
                for (int q = 0; q < 8; q++) {
                    uint32_t b0, b1, b2, b3;
                    ldsm4(b0, b1, b2, b3, sb + OFF_ROWS + (lane & 7) * 528u + (lane >> 3) * 16u + q * 64u);
                    #pragma unroll
                    for (int hf = 0; hf < 2; hf++) {
                        const int k = 16 * hf + 2 * q;
                        mma16816(acc[2 * hf], wf[k][0], wf[k][1], wf[k][2], wf[k][3], b0, b1);
                        mma16816(acc[2 * hf + 1], wf[k + 1][0], wf[k + 1][1], wf[k + 1][2], wf[k + 1][3], b2, b3);
                    }
                }
                const float gs = (acc[0][0] + acc[1][0]) + (acc[2][1] + acc[3][1]), us = (acc[0][2] + acc[1][2]) + (acc[2][3] + acc[3][3]);
                st_partner64(sb + OFF_PX + warp * 256 + lane * 8, BAR(B_PX), rank ^ 1, gs, us);
                if (warp == 0) TS(34);
                #pragma unroll
                for (int q = DNE; q < 16; q++)
                    ldsm4t(df[q >> 2][q & 3][0], df[q >> 2][q & 3][1], df[q >> 2][q & 3][2], df[q >> 2][q & 3][3], da + (q & 3) * 2048u + (((2 * (q >> 2) + ((lane >> 3) & 1)) ^ (lane & 7)) << 4));
                mbar_wait(BAR(B_SEL), 0);
                const uint32_t tok = lds32(sb + OFF_SEL + 48 + c * 4);
                mbar_wait(BAR(B_PX), 0);
                const uint2 q = lds64(sb + OFF_PX + warp * 256 + lane * 8);
                float gt = rbf(gs + __uint_as_float(q.x));
                gt = rbf(gt * sigmoidf(gt));
                if (tok < 2) sts16(sb + OFF_HID + tok * 144 + (warp * 8 + g) * 2, pack2(gt * rbf(us + __uint_as_float(q.y)), 0.f));
            }
            if (warp == 0) TS(26);
            bar_sync(1, 256);
            uint32_t bh[8];
            ldsm4(bh[0], bh[1], bh[2], bh[3], sb + OFF_HID + (lane & 1) * 144u + (lane >> 3) * 16u);
            ldsm4(bh[4], bh[5], bh[6], bh[7], sb + OFF_HID + (lane & 1) * 144u + (lane >> 3) * 16u + 64u);
            float y[4][4];
            #pragma unroll
            for (int tt = 0; tt < 4; tt++) { y[tt][0] = y[tt][1] = y[tt][2] = y[tt][3] = 0.f; }
            #pragma unroll
            for (int ks = 0; ks < 4; ks++)
                #pragma unroll
                for (int tt = 0; tt < 4; tt++) mma16816(y[tt], df[tt][ks][0], df[tt][ks][1], df[tt][ks][2], df[tt][ks][3], bh[2 * ks], bh[2 * ks + 1]);
            float e[4];
            #pragma unroll
            for (int i = 0; i < 4; i++) e[i] = (c & 2) ? ((c & 1) ? y[3][i] : y[2][i]) : ((c & 1) ? y[1][i] : y[0][i]);
            char* d = (char*)(p.s->yp + pr * 512 + rank * 128 + (warp * 4 + c) * 4) + g * 8;
            st_ll8(d, __float_as_uint(e[0]), low_bits(e[2], tag2));
            st_ll8(d + 4096, __float_as_uint(e[1]), low_bits(e[3], tag2));
            arrive_one(BAR(B_YP));
            if (warp == 0) TS(27);
        }
    }
}

typedef CUresult (*EncodeFn)(CUtensorMap*, CUtensorMapDataType, cuuint32_t, void*, const cuuint64_t*, const cuuint64_t*, const cuuint32_t*,
                             const cuuint32_t*, CUtensorMapInterleave, CUtensorMapSwizzle, CUtensorMapL2promotion, CUtensorMapFloatOOBfill);

CUtensorMap make_map(EncodeFn enc, const void* ptr, uint64_t cols, uint64_t rows, uint32_t bc, uint32_t br, CUtensorMapSwizzle swz, CUtensorMapL2promotion promo) {
    CUtensorMap m;
    cuuint64_t dims[2] = {cols, rows}, strides[1] = {cols * 2};
    cuuint32_t box[2] = {bc, br}, es[2] = {1, 1};
    enc(&m, CU_TENSOR_MAP_DATA_TYPE_BFLOAT16, 2, const_cast<void*>(ptr), dims, strides, box, es, CU_TENSOR_MAP_INTERLEAVE_NONE, swz, promo,
        CU_TENSOR_MAP_FLOAT_OOB_FILL_NONE);
    return m;
}
CUtensorMap make_block_map(EncodeFn enc, const void* ptr, uint32_t sections, uint64_t rows, uint32_t br, CUtensorMapL2promotion promo) {
    CUtensorMap m;
    cuuint64_t dims[4] = {64, rows, 16, sections}, strides[3] = {sections * 2048ull, 128, 2048};
    cuuint32_t box[4] = {64, br, 2, sections}, es[4] = {1, 1, 1, 1};
    enc(&m, CU_TENSOR_MAP_DATA_TYPE_BFLOAT16, sections > 1 ? 4 : 3, const_cast<void*>(ptr), dims, strides, box, es, CU_TENSOR_MAP_INTERLEAVE_NONE,
        CU_TENSOR_MAP_SWIZZLE_128B, promo, CU_TENSOR_MAP_FLOAT_OOB_FILL_NONE);
    return m;
}

}

extern "C" void kernel_launch(void* const* d_in, const int* in_sizes, int n_in, void* d_out, int out_size) {
    (void)in_sizes; (void)n_in; (void)out_size;
    void* fn = nullptr; cudaDriverEntryPointQueryResult qr;
    cudaGetDriverEntryPoint("cuTensorMapEncodeTiled", &fn, cudaEnableDefault, &qr);
    EncodeFn enc = (EncodeFn)fn;
    void* hs = nullptr;
    cudaGetSymbolAddress(&hs, g_scratch);
    const CUtensorMapL2promotion P256 = CU_TENSOR_MAP_L2_PROMOTION_L2_256B, P128 = CU_TENSOR_MAP_L2_PROMOTION_L2_128B;
    CUtensorMap tmW = make_block_map(enc, d_in[1], 3, 1024, 64, P256);
    CUtensorMap tmWo = make_map(enc, d_in[3], 1024, 1024, 64, 64, CU_TENSOR_MAP_SWIZZLE_128B, P256);
    CUtensorMap tmPhi = make_map(enc, d_in[2], 32, 1024, 32, 128, CU_TENSOR_MAP_SWIZZLE_64B, P128);
    CUtensorMap tmG = make_map(enc, d_in[6], 3584, 1024, 64, 128, CU_TENSOR_MAP_SWIZZLE_128B, P128);
    CUtensorMap tmU = make_map(enc, d_in[7], 3584, 1024, 64, 128, CU_TENSOR_MAP_SWIZZLE_128B, P128);
    CUtensorMap tmD = make_block_map(enc, d_in[8], 1, 3584, 64, P128);
    CUtensorMap tmX = make_map(enc, d_in[0], 1024, 2048, 64, 128, CU_TENSOR_MAP_SWIZZLE_128B, P128);
    CUtensorMap tmO = make_block_map(enc, d_out, 1, 2048, 8, P128);
    CUtensorMap tmM = make_map(enc, d_in[10], 6144, 1024, 64, 64, CU_TENSOR_MAP_SWIZZLE_128B, P128);
    CUtensorMap tmR = make_map(enc, d_in[10], 6144, 1024, 32, 64, CU_TENSOR_MAP_SWIZZLE_NONE, P128);
    CUtensorMap tmG8 = make_map(enc, d_in[6], 3584, 1024, 8, PRG, CU_TENSOR_MAP_SWIZZLE_NONE, P128);
    CUtensorMap tmU8 = make_map(enc, d_in[7], 3584, 1024, 8, PRG, CU_TENSOR_MAP_SWIZZLE_NONE, P128);
    CUtensorMap tmD8;
    {
        cuuint64_t dims[3] = {64, 16, 3584}, strides[2] = {128, 2048};
        cuuint32_t box[3] = {8, 8, PRD}, es[3] = {1, 1, 1};
        enc(&tmD8, CU_TENSOR_MAP_DATA_TYPE_BFLOAT16, 3, d_in[8], dims, strides, box, es, CU_TENSOR_MAP_INTERLEAVE_NONE, CU_TENSOR_MAP_SWIZZLE_NONE, P128,
            CU_TENSOR_MAP_FLOAT_OOB_FILL_NONE);
    }
    Ptrs p;
    p.x = (const bf16*)d_in[0]; p.c = (const bf16*)d_in[9]; p.wmod = (const bf16*)d_in[10]; p.wr = (const bf16*)d_in[5];
    p.wg = (const bf16*)d_in[6]; p.wu = (const bf16*)d_in[7]; p.wd = (const bf16*)d_in[8]; p.out = (bf16*)d_out; p.s = (Scratch*)hs;
    p.wqkv = (const bf16*)d_in[1]; p.wo = (const bf16*)d_in[3];
    cudaFuncSetAttribute(fused_kernel, cudaFuncAttributeMaxDynamicSharedMemorySize, SMEM_BYTES);
    fused_kernel<<<128, NTHREADS, SMEM_BYTES, cudaStreamPerThread>>>(p, tmW, tmWo, tmPhi, tmG, tmU, tmD, tmX, tmO, tmM, tmR, tmG8, tmU8, tmD8);
}
```

```cpp
#include <cuda_runtime.h>
#include <cuda.h>
#include <cuda_bf16.h>
#include <stdint.h>

namespace {

typedef __nv_bfloat16 bf16;

constexpr int NTHREADS = 384;
constexpr int POLL_MAX = 400000;
constexpr uint32_t EMPTY = 0xffffffffu;

constexpr int PND = 6;
constexpr int PNG = 5;
constexpr int PRD = (64 + PND - 1) / PND, PRG = (384 + PNG - 1) / PNG;
constexpr uint32_t OFF_RING = 0;
constexpr uint32_t OFF_XS   = 65536;
constexpr uint32_t OFF_WST  = 98304;
constexpr uint32_t OFF_XT   = 0;
constexpr uint32_t OFF_GA   = 32768;
constexpr uint32_t OFF_PHI0 = 163840, OFF_PHI1 = 98304;
constexpr uint32_t OFF_V    = 131072;
constexpr uint32_t OFF_KVS  = 131072;
constexpr uint32_t OFF_DB   = 0;
constexpr uint32_t OFF_DA   = 98304;
constexpr uint64_t SLOT_A   = 0x5432105432105432ull, SLOT_B = 0x1054321054321054ull;
constexpr uint32_t PAR_A    = 0x3f00, PAR_B = 0x0fc0;
constexpr uint32_t OFF_OWN  = OFF_DA + 32768;
constexpr uint32_t OFF_OUT  = OFF_DA + 65536;
constexpr uint32_t OFF_UP0  = OFF_DA, OFF_UP1 = OFF_DB + 32768, OFF_DN0 = OFF_DA + 32768, OFF_DN1 = OFF_DB + 65536;
constexpr uint32_t OFF_WPHI = 196608;
constexpr uint32_t OFF_SP   = 204800;
constexpr uint32_t OFF_Z    = 221184;
constexpr uint32_t OFF_ONES = 225280;
constexpr uint32_t OFF_MODS = 226304;
constexpr uint32_t OFF_GB   = 196608;
constexpr uint32_t OFF_BQ   = 229376;
constexpr uint32_t OFF_ATOT = OFF_BQ + 256;
constexpr uint32_t OFF_BAR  = 230400;
constexpr uint32_t OFF_SEEN = OFF_BAR + 632;
constexpr uint32_t OFF_PAR  = OFF_BAR + 640;
constexpr uint32_t SMEM_BYTES = 232448;
constexpr uint32_t OFF_SILU = OFF_Z;
constexpr uint32_t OFF_RED0 = OFF_Z + 2048;
constexpr uint32_t OFF_DUMMY = OFF_RED0 + 512;
constexpr uint32_t OFF_ST2  = OFF_DB;
constexpr uint32_t OFF_SEL  = OFF_ST2 + 1024;
constexpr uint32_t OFF_ROWS = OFF_ST2 + 2048;
constexpr uint32_t OFF_PX   = OFF_ROWS + 4608;
constexpr uint32_t OFF_HID  = OFF_PX + 2048;

enum {
    B_F1 = 0, B_E1 = 3, B_STFREE = 6, B_WPHI = 7, B_FA = 8, B_FB = 14, B_RF = 20, B_KVD = 24, B_PAR = 26, B_S0 = 27, B_GU = 28, B_WD = 29,
    B_X2 = 30, B_ST2 = 31, B_CAND = 32, B_TURN = 33,
    B_MP = 34, B_MOD = 35, B_PX = 51, B_S0FREE = 52, B_PHI = 53, B_OUTW = 57, B_PUB = 58, B_KVF = 59, B_OWN = 61, B_REL = 63, B_ROWS = 64,
    B_SEL = 65, B_YP = 66, B_RED = 67,
    B_XS = 68,
    B_WS = 72, B_COUNT = 76,
    B_ED = B_MOD, B_PF = B_XS + 3, B_KVS = B_RF
};

struct Scratch {
    uint4 os[256 * 1024];
    uint4 kvp[32 * 256 * 32];
    uint4 kvf[32 * 288];
    uint4 st1[2048];
    uint4 mp[128 * 16];
    uint4 rest[1024];
    uint4 flo[256 * 2];
    uint4 st2[2048];
    uint4 cand[64 * 2];
    uint4 rowh[128 * 128];
    uint4 rowx[128 * 128];
    uint4 rsc[64 * 8 * 2];
    uint4 yp[56 * 512];
    unsigned done[4];
};
__device__ __align__(1024) Scratch g_scratch;

__device__ __forceinline__ uint32_t smem_u32(const void* p) { return (uint32_t)__cvta_generic_to_shared(p); }
__device__ __forceinline__ int lane_id() { int l; asm volatile("mov.u32 %0, %%laneid;" : "=r"(l)); return l; }
__device__ __forceinline__ uint32_t clk32() { uint32_t c; asm volatile("mov.u32 %0, %%clock;" : "=r"(c) :: "memory"); return c; }
__device__ __forceinline__ void arrive_one(uint32_t bar) {
    asm volatile("{\n.reg .pred p;\nelect.sync _|p, 0xffffffff;\n@p mbarrier.arrive.shared::cta.b64 _, [%0];\n}" :: "r"(bar) : "memory");
}
__device__ __forceinline__ void arrive_many(uint32_t bar, uint32_t n) {
    asm volatile("{\n.reg .pred p;\nelect.sync _|p, 0xffffffff;\n@p mbarrier.arrive.shared::cta.b64 _, [%0], %1;\n}" :: "r"(bar), "r"(n) : "memory");
}
__device__ __forceinline__ void arrive_if(uint32_t bar, uint32_t on) {
    asm volatile("{\n.reg .pred q, p;\nelect.sync _|q, 0xffffffff;\nsetp.ne.and.u32 p, %1, 0, q;\n@p mbarrier.arrive.shared::cta.b64 _, [%0];\n}" :: "r"(bar), "r"(on) : "memory");
}
__device__ __forceinline__ void st_partner64(uint32_t a, uint32_t bar, uint32_t cta, float x, float y) {
    asm volatile("{\n.reg .b32 ra, rb;\nmapa.shared::cluster.u32 ra, %0, %2;\nmapa.shared::cluster.u32 rb, %1, %2;\n"
        "st.async.weak.shared::cluster.mbarrier::complete_tx::bytes.v2.f32 [ra], {%3, %4}, [rb];\n}" :: "r"(a), "r"(bar), "r"(cta), "f"(x), "f"(y) : "memory");
}
__device__ __forceinline__ void mbar_wait(uint32_t bar, uint32_t parity) {
    asm volatile("{\n.reg .pred P1;\n.reg .u32 cnt;\nmbarrier.try_wait.parity.shared::cta.b64 P1, [%0], %1;\n@P1 bra DONE;\nmov.u32 cnt, 0;\nLAB_WAIT:\n"
        "mbarrier.try_wait.parity.shared::cta.b64 P1, [%0], %1;\n@P1 bra DONE;\n"
        "add.u32 cnt, cnt, 1;\nsetp.lt.u32 P1, cnt, 1000000;\n@P1 bra LAB_WAIT;\ntrap;\nDONE:\n}" :: "r"(bar), "r"(parity) : "memory");
}
__device__ __forceinline__ uint64_t policy_evict_first() { uint64_t p; asm("createpolicy.fractional.L2::evict_first.b64 %0, 1.0;" : "=l"(p)); return p; }
__device__ __forceinline__ void bulk_commit() { asm volatile("cp.async.bulk.commit_group;" ::: "memory"); }
__device__ __forceinline__ void bulk_wait() { asm volatile("cp.async.bulk.wait_group 0;" ::: "memory"); }
__device__ __forceinline__ void tmap_prefetch(const CUtensorMap* tm) { asm volatile("prefetch.tensormap [%0];" :: "l"(tm) : "memory"); }
#define EL "{\n.reg .pred e;\nelect.sync _|e, 0xffffffff;\n@e "
__device__ __forceinline__ void expect_tx_e(uint32_t bar, uint32_t bytes) { asm volatile(EL "mbarrier.arrive.expect_tx.shared::cta.b64 _, [%0], %1;\n}" :: "r"(bar), "r"(bytes) : "memory"); }
__device__ __forceinline__ void tma2_e(uint32_t dst, const CUtensorMap* tm, int c0, int c1, uint32_t bar) {
    asm volatile(EL "cp.async.bulk.tensor.2d.shared::cluster.global.mbarrier::complete_tx::bytes [%0], [%1, {%3, %4}], [%2];\n}"
        :: "r"(dst), "l"(tm), "r"(bar), "r"(c0), "r"(c1) : "memory");
}
__device__ __forceinline__ void tma2_ef_e(uint32_t dst, const CUtensorMap* tm, int c0, int c1, uint32_t bar) {
    asm volatile(EL "cp.async.bulk.tensor.2d.shared::cluster.global.mbarrier::complete_tx::bytes.L2::cache_hint [%0], [%1, {%3, %4}], [%2], %5;\n}"
        :: "r"(dst), "l"(tm), "r"(bar), "r"(c0), "r"(c1), "l"(policy_evict_first()) : "memory");
}
__device__ __forceinline__ void tma3_e(uint32_t dst, const CUtensorMap* tm, int c1, int c2, uint32_t bar) {
    asm volatile(EL "cp.async.bulk.tensor.3d.shared::cluster.global.mbarrier::complete_tx::bytes [%0], [%1, {0, %3, %4}], [%2];\n}"
        :: "r"(dst), "l"(tm), "r"(bar), "r"(c1), "r"(c2) : "memory");
}
__device__ __forceinline__ void tma3_ef_e(uint32_t dst, const CUtensorMap* tm, int row, int blk, uint32_t bar) {
    asm volatile(EL "cp.async.bulk.tensor.3d.shared::cluster.global.mbarrier::complete_tx::bytes.L2::cache_hint [%0], [%1, {0, %3, %4}], [%2], %5;\n}"
        :: "r"(dst), "l"(tm), "r"(bar), "r"(row), "r"(blk), "l"(policy_evict_first()) : "memory");
}
__device__ __forceinline__ void tma4_ef_e(uint32_t dst, const CUtensorMap* tm, int row, int blk, uint32_t bar) {
    asm volatile(EL "cp.async.bulk.tensor.4d.shared::cluster.global.mbarrier::complete_tx::bytes.L2::cache_hint [%0], [%1, {0, %3, %4, 0}], [%2], %5;\n}"
        :: "r"(dst), "l"(tm), "r"(bar), "r"(row), "r"(blk), "l"(policy_evict_first()) : "memory");
}
__device__ __forceinline__ void bulk_load_e(uint32_t dst, const void* src, uint32_t bytes, uint32_t bar) {
    asm volatile(EL "cp.async.bulk.shared::cluster.global.mbarrier::complete_tx::bytes [%0], [%1], %2, [%3];\n}" :: "r"(dst), "l"(src), "r"(bytes), "r"(bar) : "memory");
}
__device__ __forceinline__ void bulk_store_e(void* dst, uint32_t src, uint32_t bytes) {
    asm volatile(EL "cp.async.bulk.global.shared::cta.bulk_group [%0], [%1], %2;\n}" :: "l"(dst), "r"(src), "r"(bytes) : "memory");
}
__device__ __forceinline__ void st_flag_e(void* p, unsigned v) { asm volatile(EL "st.relaxed.gpu.global.u32 [%0], %1;\n}" :: "l"(p), "r"(v) : "memory"); }
__device__ __forceinline__ void mbar_init(uint32_t bar, uint32_t cnt) { asm volatile("mbarrier.init.shared::cta.b64 [%0], %1;" :: "r"(bar), "r"(cnt) : "memory"); }
__device__ __forceinline__ bool elect_one() {
    uint32_t p;
    asm volatile("{\n.reg .pred P;\nelect.sync _|P, 0xffffffff;\nselp.u32 %0, 1, 0, P;\n}" : "=r"(p));
    return p;
}
__device__ __forceinline__ void wg_fence() { asm volatile("wgmma.fence.sync.aligned;" ::: "memory"); }
__device__ __forceinline__ void wg_commit() { asm volatile("wgmma.commit_group.sync.aligned;" ::: "memory"); }
template<int N> __device__ __forceinline__ void wg_wait() { asm volatile("wgmma.wait_group.sync.aligned %0;" :: "n"(N) : "memory"); }
template<int N> __device__ __forceinline__ void acc_fence(float (&d)[N]) {
    #pragma unroll
    for (int i = 0; i < N; i++) asm volatile("" : "+f"(d[i]) :: "memory");
}
__device__ __forceinline__ uint64_t mk_desc(uint32_t addr, uint32_t lbo, uint32_t sbo, uint32_t swz) {
    uint32_t lo = ((addr & 0x3FFFF) >> 4) | (((lbo & 0x3FFFF) >> 4) << 16);
    uint32_t hi = (sbo >> 4) | (swz << 30);
    return ((uint64_t)hi << 32) | lo;
}
__device__ __forceinline__ uint64_t desc_add(uint64_t d, uint32_t bytes) { return (d & 0xffffffff00000000ull) | (uint32_t)((uint32_t)d + (bytes >> 4)); }
__device__ __forceinline__ uint64_t desc_raw(uint64_t d, uint32_t inc) { return (d & 0xffffffff00000000ull) | (uint32_t)((uint32_t)d + inc); }
__device__ __forceinline__ void fence_async_smem() { asm volatile("fence.proxy.async.shared::cta;" ::: "memory"); }
__device__ __forceinline__ void bar_sync(int id, int n) { asm volatile("bar.sync %0, %1;" :: "r"(id), "r"(n) : "memory"); }
__device__ __forceinline__ void bar_arrive(int id, int n) { asm volatile("bar.arrive %0, %1;" :: "r"(id), "r"(n) : "memory"); }
template<int R> __device__ __forceinline__ void reg_inc() { asm volatile("setmaxnreg.inc.sync.aligned.u32 %0;" :: "n"(R)); }
template<int R> __device__ __forceinline__ void reg_dec() { asm volatile("setmaxnreg.dec.sync.aligned.u32 %0;" :: "n"(R)); }
__device__ __forceinline__ void cluster_arrive() { asm volatile("barrier.cluster.arrive.relaxed.aligned;" ::: "memory"); }
__device__ __forceinline__ void cluster_wait() { asm volatile("barrier.cluster.wait.acquire.aligned;" ::: "memory"); }

__device__ __forceinline__ void stsm4(uint32_t addr, uint32_t r0, uint32_t r1, uint32_t r2, uint32_t r3) {
    asm volatile("stmatrix.sync.aligned.m8n8.x4.shared.b16 [%0], {%1,%2,%3,%4};" :: "r"(addr), "r"(r0), "r"(r1), "r"(r2), "r"(r3) : "memory");
}
__device__ __forceinline__ void ldsm4(uint32_t& r0, uint32_t& r1, uint32_t& r2, uint32_t& r3, uint32_t addr) {
    asm volatile("ldmatrix.sync.aligned.m8n8.x4.shared.b16 {%0,%1,%2,%3}, [%4];" : "=r"(r0), "=r"(r1), "=r"(r2), "=r"(r3) : "r"(addr) : "memory");
}
__device__ __forceinline__ void ldsm4t(uint32_t& r0, uint32_t& r1, uint32_t& r2, uint32_t& r3, uint32_t addr) {
    asm volatile("ldmatrix.sync.aligned.m8n8.x4.trans.shared.b16 {%0,%1,%2,%3}, [%4];" : "=r"(r0), "=r"(r1), "=r"(r2), "=r"(r3) : "r"(addr) : "memory");
}
__device__ __forceinline__ void mma16816(float (&d)[4], uint32_t a0, uint32_t a1, uint32_t a2, uint32_t a3, uint32_t b0, uint32_t b1) {
    asm("mma.sync.aligned.m16n8k16.row.col.f32.bf16.bf16.f32 {%0,%1,%2,%3}, {%4,%5,%6,%7}, {%8,%9}, {%0,%1,%2,%3};"
        : "+f"(d[0]), "+f"(d[1]), "+f"(d[2]), "+f"(d[3]) : "r"(a0), "r"(a1), "r"(a2), "r"(a3), "r"(b0), "r"(b1));
}
__device__ __forceinline__ void mma1688(float (&d)[4], uint32_t a0, uint32_t a1, uint32_t b0) {
    asm("mma.sync.aligned.m16n8k8.row.col.f32.bf16.bf16.f32 {%0,%1,%2,%3}, {%4,%5}, {%6}, {%0,%1,%2,%3};"
        : "+f"(d[0]), "+f"(d[1]), "+f"(d[2]), "+f"(d[3]) : "r"(a0), "r"(a1), "r"(b0));
}
__device__ __forceinline__ uint4 lds128(uint32_t a) { uint4 v; asm volatile("ld.shared.v4.b32 {%0,%1,%2,%3}, [%4];" : "=r"(v.x), "=r"(v.y), "=r"(v.z), "=r"(v.w) : "r"(a) : "memory"); return v; }
__device__ __forceinline__ uint2 lds64(uint32_t a) { uint2 v; asm volatile("ld.shared.v2.b32 {%0,%1}, [%2];" : "=r"(v.x), "=r"(v.y) : "r"(a) : "memory"); return v; }
__device__ __forceinline__ uint32_t lds32(uint32_t a) { uint32_t v; asm volatile("ld.shared.b32 %0, [%1];" : "=r"(v) : "r"(a) : "memory"); return v; }
__device__ __forceinline__ float ldsf(uint32_t a) { float v; asm volatile("ld.shared.f32 %0, [%1];" : "=f"(v) : "r"(a) : "memory"); return v; }
__device__ __forceinline__ uint32_t lds16(uint32_t a) { uint16_t v; asm volatile("ld.shared.b16 %0, [%1];" : "=h"(v) : "r"(a) : "memory"); return v; }
__device__ __forceinline__ void sts128(uint32_t a, uint4 v) { asm volatile("st.shared.v4.b32 [%0], {%1,%2,%3,%4};" :: "r"(a), "r"(v.x), "r"(v.y), "r"(v.z), "r"(v.w) : "memory"); }
__device__ __forceinline__ void sts64(uint32_t a, uint32_t x, uint32_t y) { asm volatile("st.shared.v2.b32 [%0], {%1,%2};" :: "r"(a), "r"(x), "r"(y) : "memory"); }
__device__ __forceinline__ void sts32(uint32_t a, uint32_t x) { asm volatile("st.shared.b32 [%0], %1;" :: "r"(a), "r"(x) : "memory"); }
__device__ __forceinline__ void stsf(uint32_t a, float x) { asm volatile("st.shared.f32 [%0], %1;" :: "r"(a), "f"(x) : "memory"); }
__device__ __forceinline__ void sts16(uint32_t a, uint32_t x) { asm volatile("st.shared.b16 [%0], %1;" :: "r"(a), "h"((uint16_t)x) : "memory"); }

__device__ __forceinline__ uint4 ldg128(const void* p) { uint4 v; asm volatile("ld.global.nc.v4.b32 {%0,%1,%2,%3}, [%4];" : "=r"(v.x), "=r"(v.y), "=r"(v.z), "=r"(v.w) : "l"(p)); return v; }
__device__ __forceinline__ uint2 ldg64(const void* p) { uint2 v; asm volatile("ld.global.nc.v2.b32 {%0,%1}, [%2];" : "=r"(v.x), "=r"(v.y) : "l"(p)); return v; }
__device__ __forceinline__ void stg128(void* p, uint4 v) { asm volatile("st.global.v4.b32 [%0], {%1,%2,%3,%4};" :: "l"(p), "r"(v.x), "r"(v.y), "r"(v.z), "r"(v.w) : "memory"); }
__device__ __forceinline__ void stg_fill(void* p, uint32_t v) { asm volatile("st.global.v4.b32 [%0], {%1,%1,%1,%1};" :: "l"(p), "r"(v) : "memory"); }
__device__ __forceinline__ void st_ll(void* p, uint32_t x, uint32_t y, uint32_t z, uint32_t w) {
    asm volatile("{\n.reg .b128 t;\n.reg .b64 a, b;\nmov.b64 a, {%1, %2};\nmov.b64 b, {%3, %4};\nmov.b128 t, {a, b};\nst.relaxed.gpu.global.b128 [%0], t;\n}"
        :: "l"(p), "r"(x), "r"(y), "r"(z), "r"(w) : "memory");
}
__device__ __forceinline__ uint4 ld_ll(const void* p) {
    uint4 v;
    asm volatile("{\n.reg .b128 t;\n.reg .b64 a, b;\nld.relaxed.gpu.global.b128 t, [%4];\nmov.b128 {a, b}, t;\nmov.b64 {%0, %1}, a;\nmov.b64 {%2, %3}, b;\n}"
        : "=r"(v.x), "=r"(v.y), "=r"(v.z), "=r"(v.w) : "l"(p) : "memory");
    return v;
}
__device__ __forceinline__ void ld_ll_if(uint4& v, const void* p, bool go) {
    asm volatile("{\n.reg .b128 t;\n.reg .b64 a, b;\n.reg .pred q;\nsetp.ne.u32 q, %5, 0;\nmov.b64 a, {%0, %1};\nmov.b64 b, {%2, %3};\nmov.b128 t, {a, b};\n"
        "@q ld.relaxed.gpu.global.b128 t, [%4];\nmov.b128 {a, b}, t;\nmov.b64 {%0, %1}, a;\nmov.b64 {%2, %3}, b;\n}"
        : "+r"(v.x), "+r"(v.y), "+r"(v.z), "+r"(v.w) : "l"(p), "r"((uint32_t)go) : "memory");
}
__device__ __forceinline__ void st_ll8(void* p, uint32_t x, uint32_t y) {
    asm volatile("{\n.reg .b64 a;\nmov.b64 a, {%1, %2};\nst.relaxed.gpu.global.b64 [%0], a;\n}" :: "l"(p), "r"(x), "r"(y) : "memory");
}
__device__ __forceinline__ void st_ll4(void* p, uint32_t x) { asm volatile("st.relaxed.gpu.global.b32 [%0], %1;" :: "l"(p), "r"(x) : "memory"); }
__device__ __forceinline__ unsigned ld_rlx(const void* p) { unsigned v; asm volatile("ld.relaxed.gpu.global.u32 %0, [%1];" : "=r"(v) : "l"(p) : "memory"); return v; }
__device__ __forceinline__ void red_add4(void* p, float x, float y, float z, float w) {
    asm volatile("red.relaxed.gpu.global.add.v4.f32 [%0], {%1, %2, %3, %4};" :: "l"(p), "f"(x), "f"(y), "f"(z), "f"(w) : "memory");
}
__device__ __forceinline__ void fence_rel_gpu() { asm volatile("fence.proxy.async.global;\nfence.release.gpu;" ::: "memory"); }
__device__ __forceinline__ void fence_acq_gpu() { asm volatile("fence.acquire.gpu;" ::: "memory"); }
template<int N> __device__ __forceinline__ void poll_words(uint4 (&v)[N], const uint4* p, int stride, uint32_t tag) {
    #pragma unroll 1
    for (int it = 0; it < POLL_MAX; it++) {
        bool ok = true;
        #pragma unroll
        for (int i = 0; i < N; i++) v[i] = ld_ll(p + i * stride);
        #pragma unroll
        for (int i = 0; i < N; i++) ok = ok && (v[i].w == tag);
        if (__all_sync(0xffffffffu, ok)) break;
    }
}
__device__ __forceinline__ void pause(uint32_t n) { const uint32_t c0 = clk32(); while (clk32() - c0 < n) {} }
template<int B> __device__ __forceinline__ uint32_t low_byte(float v, uint32_t src) { return __byte_perm(__float_as_uint(v), src, 0x3214 + B); }
__device__ __forceinline__ uint32_t low_bits(float v, uint32_t tag2) { return (__float_as_uint(v) & ~3u) | tag2; }
__device__ __forceinline__ bool tagged2(uint32_t w, uint32_t tag2) { return (w & 3u) == tag2; }
__device__ __forceinline__ uint32_t umax4(uint4 v) { return max(max(v.x, v.y), max(v.z, v.w)); }
constexpr uint32_t ONE2 = 0x3F803F80u;
__device__ __forceinline__ uint32_t pack2(float lo, float hi) { uint32_t d; asm("cvt.rn.bf16x2.f32 %0, %1, %2;" : "=r"(d) : "f"(hi), "f"(lo)); return d; }
__device__ __forceinline__ float bf_lo(uint32_t v) { return __uint_as_float(v << 16); }
__device__ __forceinline__ float bf_lo_after(uint32_t v, float nonneg) { float d; asm("prmt.b32 %0, %1, %2, 0x10ff;" : "=f"(d) : "r"(v), "f"(nonneg)); return d; }
__device__ __forceinline__ float bf_hi_after(uint32_t v, float nonneg) { float d; asm("prmt.b32 %0, %1, %2, 0x32ff;" : "=f"(d) : "r"(v), "f"(nonneg)); return d; }
__device__ __forceinline__ float bf_hi(uint32_t v) { return __uint_as_float(v & 0xffff0000u); }
__device__ __forceinline__ float rbf(float x) { return bf_lo(pack2(x, 0.f)); }
__device__ __forceinline__ uint32_t hsub2(uint32_t a, uint32_t b) { uint32_t d; asm("sub.rn.bf16x2 %0, %1, %2;" : "=r"(d) : "r"(a), "r"(b)); return d; }
__device__ __forceinline__ uint32_t hadd2(uint32_t a, uint32_t b) { uint32_t d; asm("add.rn.bf16x2 %0, %1, %2;" : "=r"(d) : "r"(a), "r"(b)); return d; }
__device__ __forceinline__ uint32_t hmul2(uint32_t a, uint32_t b) { uint32_t d; asm("mul.rn.bf16x2 %0, %1, %2;" : "=r"(d) : "r"(a), "r"(b)); return d; }
__device__ __forceinline__ uint32_t hmax2(uint32_t a, uint32_t b) { uint32_t d; asm("max.bf16x2 %0, %1, %2;" : "=r"(d) : "r"(a), "r"(b)); return d; }
__device__ __forceinline__ uint32_t hmin2(uint32_t a, uint32_t b) { uint32_t d; asm("min.bf16x2 %0, %1, %2;" : "=r"(d) : "r"(a), "r"(b)); return d; }
__device__ __forceinline__ float ex2(float x) { float y; asm("ex2.approx.ftz.f32 %0, %1;" : "=f"(y) : "f"(x)); return y; }
__device__ __forceinline__ float rcp(float x) { float y; asm("rcp.approx.ftz.f32 %0, %1;" : "=f"(y) : "f"(x)); return y; }
__device__ __forceinline__ float shfl_x(float v, int m) { return __shfl_xor_sync(0xffffffffu, v, m); }
constexpr float LOG2E = 1.4426950408889634f;
__device__ __forceinline__ float sigmoidf(float x) { return rcp(1.0f + ex2(-LOG2E * x)); }
struct Recip { uint32_t hi, lo; };
__device__ __forceinline__ Recip split_recip(float r) { Recip q; q.hi = pack2(r, r); const float l = r - bf_hi(q.hi); q.lo = pack2(l, l); return q; }
__device__ __forceinline__ uint32_t hdiv2(uint32_t n, Recip r) { uint32_t d; asm("fma.rn.bf16x2 %0, %1, %2, %3;" : "=r"(d) : "r"(n), "r"(r.hi), "r"(hmul2(n, r.lo))); return d; }
__device__ __forceinline__ uint32_t ln_pair(uint32_t x, uint32_t m2, Recip r, uint32_t a, uint32_t s) { return hadd2(hmul2(hdiv2(hsub2(x, m2), r), a), s); }
__device__ __forceinline__ void ln_final(float s1, float s2, uint32_t& m2, float& rinv) {
    const float mean = s1 * (1.0f / 1024.0f), var = fmaf(-mean, mean, s2 * (1.0f / 1024.0f));
    m2 = pack2(mean, mean);
    float sd;
    asm("sqrt.approx.ftz.f32 %0, %1;" : "=f"(sd) : "f"(rbf(rbf(fmaxf(var, 0.f)) + 1e-5f)));
    rinv = rcp(rbf(sd));
}
__device__ __forceinline__ uint32_t f2key(float f) { uint32_t u = __float_as_uint(f); return (u & 0x80000000u) ? ~u : (u | 0x80000000u); }

__device__ __forceinline__ void fm_extrema(const uint32_t (&p)[16], float& cp, float& cn) {
    uint32_t mx = p[0], mn = p[0];
    #pragma unroll
    for (int k = 1; k < 15; k += 2) { mx = hmax2(hmax2(mx, p[k]), p[k + 1]); mn = hmin2(hmin2(mn, p[k]), p[k + 1]); }
    mx = hmax2(mx, p[15]); mn = hmin2(mn, p[15]);
    cp = -fmaxf(bf_lo(mx), bf_hi(mx)) * LOG2E; cn = fminf(bf_lo(mn), bf_hi(mn)) * LOG2E;
}
template<int TB> __device__ __forceinline__ void wgmma_n32_rs(float (&d)[16], uint32_t a0, uint32_t a1, uint32_t a2, uint32_t a3, uint64_t db, int sc) {
  asm volatile("{\n.reg .pred p;\nsetp.ne.b32 p, %21, 0;\n"
    "wgmma.mma_async.sync.aligned.m64n32k16.f32.bf16.bf16 {%0, %1, %2, %3, %4, %5, %6, %7, %8, %9, %10, %11, %12, %13, %14, %15}, {%16,%17,%18,%19}, %20, p, 1, 1, %22;\n}\n"
    : "+f"(d[0]), "+f"(d[1]), "+f"(d[2]), "+f"(d[3]), "+f"(d[4]), "+f"(d[5]), "+f"(d[6]), "+f"(d[7]), "+f"(d[8]), "+f"(d[9]), "+f"(d[10]), "+f"(d[11]), "+f"(d[12]), "+f"(d[13]), "+f"(d[14]), "+f"(d[15])
    : "r"(a0), "r"(a1), "r"(a2), "r"(a3), "l"(db), "r"(sc), "n"(TB));
}
template<int TA, int TB> __device__ __forceinline__ void wgmma_n40_ss(float (&d)[20], uint64_t da, uint64_t db, int sc) {
  asm volatile("{\n.reg .pred p;\nsetp.ne.b32 p, %22, 0;\n"
    "wgmma.mma_async.sync.aligned.m64n40k16.f32.bf16.bf16 {%0, %1, %2, %3, %4, %5, %6, %7, %8, %9, %10, %11, %12, %13, %14, %15, %16, %17, %18, %19}, %20, %21, p, 1, 1, %23, %24;\n}\n"
    : "+f"(d[0]), "+f"(d[1]), "+f"(d[2]), "+f"(d[3]), "+f"(d[4]), "+f"(d[5]), "+f"(d[6]), "+f"(d[7]), "+f"(d[8]), "+f"(d[9]), "+f"(d[10]), "+f"(d[11]), "+f"(d[12]), "+f"(d[13]), "+f"(d[14]), "+f"(d[15]), "+f"(d[16]), "+f"(d[17]), "+f"(d[18]), "+f"(d[19])
    : "l"(da), "l"(db), "r"(sc), "n"(TA), "n"(TB));
}
template<int TA, int TB> __device__ __forceinline__ void wgmma_n128_ss(float (&d)[64], uint64_t da, uint64_t db, int sc) {
  asm volatile("{\n.reg .pred p;\nsetp.ne.b32 p, %66, 0;\n"
    "wgmma.mma_async.sync.aligned.m64n128k16.f32.bf16.bf16 {%0, %1, %2, %3, %4, %5, %6, %7, %8, %9, %10, %11, %12, %13, %14, %15, %16, %17, %18, %19, %20, %21, %22, %23, %24, %25, %26, %27, %28, %29, %30, %31, %32, %33, %34, %35, %36, %37, %38, %39, %40, %41, %42, %43, %44, %45, %46, %47, %48, %49, %50, %51, %52, %53, %54, %55, %56, %57, %58, %59, %60, %61, %62, %63}, %64, %65, p, 1, 1, %67, %68;\n}\n"
    : "+f"(d[0]), "+f"(d[1]), "+f"(d[2]), "+f"(d[3]), "+f"(d[4]), "+f"(d[5]), "+f"(d[6]), "+f"(d[7]), "+f"(d[8]), "+f"(d[9]), "+f"(d[10]), "+f"(d[11]), "+f"(d[12]), "+f"(d[13]), "+f"(d[14]), "+f"(d[15]), "+f"(d[16]), "+f"(d[17]), "+f"(d[18]), "+f"(d[19]), "+f"(d[20]), "+f"(d[21]), "+f"(d[22]), "+f"(d[23]), "+f"(d[24]), "+f"(d[25]), "+f"(d[26]), "+f"(d[27]), "+f"(d[28]), "+f"(d[29]), "+f"(d[30]), "+f"(d[31]), "+f"(d[32]), "+f"(d[33]), "+f"(d[34]), "+f"(d[35]), "+f"(d[36]), "+f"(d[37]), "+f"(d[38]), "+f"(d[39]), "+f"(d[40]), "+f"(d[41]), "+f"(d[42]), "+f"(d[43]), "+f"(d[44]), "+f"(d[45]), "+f"(d[46]), "+f"(d[47]), "+f"(d[48]), "+f"(d[49]), "+f"(d[50]), "+f"(d[51]), "+f"(d[52]), "+f"(d[53]), "+f"(d[54]), "+f"(d[55]), "+f"(d[56]), "+f"(d[57]), "+f"(d[58]), "+f"(d[59]), "+f"(d[60]), "+f"(d[61]), "+f"(d[62]), "+f"(d[63])
    : "l"(da), "l"(db), "r"(sc), "n"(TA), "n"(TB));
}
template<int TB> __device__ __forceinline__ void wgmma_n128_rs(float (&d)[64], uint32_t a0, uint32_t a1, uint32_t a2, uint32_t a3, uint64_t db, int sc) {
  asm volatile("{\n.reg .pred p;\nsetp.ne.b32 p, %69, 0;\n"
    "wgmma.mma_async.sync.aligned.m64n128k16.f32.bf16.bf16 {%0, %1, %2, %3, %4, %5, %6, %7, %8, %9, %10, %11, %12, %13, %14, %15, %16, %17, %18, %19, %20, %21, %22, %23, %24, %25, %26, %27, %28, %29, %30, %31, %32, %33, %34, %35, %36, %37, %38, %39, %40, %41, %42, %43, %44, %45, %46, %47, %48, %49, %50, %51, %52, %53, %54, %55, %56, %57, %58, %59, %60, %61, %62, %63}, {%64,%65,%66,%67}, %68, p, 1, 1, %70;\n}\n"
    : "+f"(d[0]), "+f"(d[1]), "+f"(d[2]), "+f"(d[3]), "+f"(d[4]), "+f"(d[5]), "+f"(d[6]), "+f"(d[7]), "+f"(d[8]), "+f"(d[9]), "+f"(d[10]), "+f"(d[11]), "+f"(d[12]), "+f"(d[13]), "+f"(d[14]), "+f"(d[15]), "+f"(d[16]), "+f"(d[17]), "+f"(d[18]), "+f"(d[19]), "+f"(d[20]), "+f"(d[21]), "+f"(d[22]), "+f"(d[23]), "+f"(d[24]), "+f"(d[25]), "+f"(d[26]), "+f"(d[27]), "+f"(d[28]), "+f"(d[29]), "+f"(d[30]), "+f"(d[31]), "+f"(d[32]), "+f"(d[33]), "+f"(d[34]), "+f"(d[35]), "+f"(d[36]), "+f"(d[37]), "+f"(d[38]), "+f"(d[39]), "+f"(d[40]), "+f"(d[41]), "+f"(d[42]), "+f"(d[43]), "+f"(d[44]), "+f"(d[45]), "+f"(d[46]), "+f"(d[47]), "+f"(d[48]), "+f"(d[49]), "+f"(d[50]), "+f"(d[51]), "+f"(d[52]), "+f"(d[53]), "+f"(d[54]), "+f"(d[55]), "+f"(d[56]), "+f"(d[57]), "+f"(d[58]), "+f"(d[59]), "+f"(d[60]), "+f"(d[61]), "+f"(d[62]), "+f"(d[63])
    : "r"(a0), "r"(a1), "r"(a2), "r"(a3), "l"(db), "r"(sc), "n"(TB));
}
template<int TB> __device__ __forceinline__ void wgmma_n256_rs(float (&d)[128], uint32_t a0, uint32_t a1, uint32_t a2, uint32_t a3, uint64_t db, int sc) {
  asm volatile("{\n.reg .pred p;\nsetp.ne.b32 p, %133, 0;\n"
    "wgmma.mma_async.sync.aligned.m64n256k16.f32.bf16.bf16 {%0, %1, %2, %3, %4, %5, %6, %7, %8, %9, %10, %11, %12, %13, %14, %15, %16, %17, %18, %19, %20, %21, %22, %23, %24, %25, %26, %27, %28, %29, %30, %31, %32, %33, %34, %35, %36, %37, %38, %39, %40, %41, %42, %43, %44, %45, %46, %47, %48, %49, %50, %51, %52, %53, %54, %55, %56, %57, %58, %59, %60, %61, %62, %63, %64, %65, %66, %67, %68, %69, %70, %71, %72, %73, %74, %75, %76, %77, %78, %79, %80, %81, %82, %83, %84, %85, %86, %87, %88, %89, %90, %91, %92, %93, %94, %95, %96, %97, %98, %99, %100, %101, %102, %103, %104, %105, %106, %107, %108, %109, %110, %111, %112, %113, %114, %115, %116, %117, %118, %119, %120, %121, %122, %123, %124, %125, %126, %127}, {%128,%129,%130,%131}, %132, p, 1, 1, %134;\n}\n"
    : "+f"(d[0]), "+f"(d[1]), "+f"(d[2]), "+f"(d[3]), "+f"(d[4]), "+f"(d[5]), "+f"(d[6]), "+f"(d[7]), "+f"(d[8]), "+f"(d[9]), "+f"(d[10]), "+f"(d[11]), "+f"(d[12]), "+f"(d[13]), "+f"(d[14]), "+f"(d[15]), "+f"(d[16]), "+f"(d[17]), "+f"(d[18]), "+f"(d[19]), "+f"(d[20]), "+f"(d[21]), "+f"(d[22]), "+f"(d[23]), "+f"(d[24]), "+f"(d[25]), "+f"(d[26]), "+f"(d[27]), "+f"(d[28]), "+f"(d[29]), "+f"(d[30]), "+f"(d[31]), "+f"(d[32]), "+f"(d[33]), "+f"(d[34]), "+f"(d[35]), "+f"(d[36]), "+f"(d[37]), "+f"(d[38]), "+f"(d[39]), "+f"(d[40]), "+f"(d[41]), "+f"(d[42]), "+f"(d[43]), "+f"(d[44]), "+f"(d[45]), "+f"(d[46]), "+f"(d[47]), "+f"(d[48]), "+f"(d[49]), "+f"(d[50]), "+f"(d[51]), "+f"(d[52]), "+f"(d[53]), "+f"(d[54]), "+f"(d[55]), "+f"(d[56]), "+f"(d[57]), "+f"(d[58]), "+f"(d[59]), "+f"(d[60]), "+f"(d[61]), "+f"(d[62]), "+f"(d[63]), "+f"(d[64]), "+f"(d[65]), "+f"(d[66]), "+f"(d[67]), "+f"(d[68]), "+f"(d[69]), "+f"(d[70]), "+f"(d[71]), "+f"(d[72]), "+f"(d[73]), "+f"(d[74]), "+f"(d[75]), "+f"(d[76]), "+f"(d[77]), "+f"(d[78]), "+f"(d[79]), "+f"(d[80]), "+f"(d[81]), "+f"(d[82]), "+f"(d[83]), "+f"(d[84]), "+f"(d[85]), "+f"(d[86]), "+f"(d[87]), "+f"(d[88]), "+f"(d[89]), "+f"(d[90]), "+f"(d[91]), "+f"(d[92]), "+f"(d[93]), "+f"(d[94]), "+f"(d[95]), "+f"(d[96]), "+f"(d[97]), "+f"(d[98]), "+f"(d[99]), "+f"(d[100]), "+f"(d[101]), "+f"(d[102]), "+f"(d[103]), "+f"(d[104]), "+f"(d[105]), "+f"(d[106]), "+f"(d[107]), "+f"(d[108]), "+f"(d[109]), "+f"(d[110]), "+f"(d[111]), "+f"(d[112]), "+f"(d[113]), "+f"(d[114]), "+f"(d[115]), "+f"(d[116]), "+f"(d[117]), "+f"(d[118]), "+f"(d[119]), "+f"(d[120]), "+f"(d[121]), "+f"(d[122]), "+f"(d[123]), "+f"(d[124]), "+f"(d[125]), "+f"(d[126]), "+f"(d[127])
    : "r"(a0), "r"(a1), "r"(a2), "r"(a3), "l"(db), "r"(sc), "n"(TB));
}

constexpr uint32_t T_INI = 500;
constexpr uint32_t T_X0 = 450;
constexpr uint32_t T_XD = 600;
constexpr uint32_t T_P0 = 1500;
constexpr uint32_t T_P1 = 3000;
constexpr uint32_t T_W1 = 2800;
constexpr uint32_t T_S0 = 3300;
constexpr uint32_t T_S1 = 5800;
constexpr uint32_t T_WLATE = 4000;
constexpr uint32_t T_REST = 6000;
constexpr uint32_t T_COL = 7000;
constexpr uint32_t T_COL2 = 14000;
constexpr uint32_t T_OSC = 24000;
constexpr uint32_t T_OSD = 800;
constexpr uint32_t KVDLY = 700;
constexpr uint32_t OP0 = 500;
constexpr uint32_t OPS = 400;
constexpr int PFJ = 3;
constexpr int WOJ = 10;
constexpr int CREG = 208;
constexpr int KW = 8;
constexpr int DEP = 2;
constexpr int DNE = 12;
struct Ptrs { const bf16 *x, *c, *wmod, *wr, *wqkv, *wo; bf16* out; Scratch* s; };

#define BAR(i) (sb + OFF_BAR + 8u * (i))

__device__ __forceinline__ int d_block(int hg, int n) {
    const int m = n - (n >= 9 ? 9 : 2);
    return n < 2 ? 2 * hg + n : 2 * (m + (m >= hg)) + (n >= 9);
}
__host__ __device__ constexpr uint32_t bar_count(int i) {
    return ((i >= B_E1 && i < B_E1 + 3) || (i >= B_S0FREE && i < B_PHI + 4) || i == B_OWN || i == B_OWN + 1 || (i >= B_ED && i < B_ED + 16)
            || i == B_STFREE || i == B_X2 || i == B_OUTW || i == B_YP || i == B_RED) ? 8
         : ((i >= B_KVD && i < B_KVD + 2) || i == B_ST2 || i == B_TURN) ? 4 : (i == B_KVF || i == B_KVF + 1) ? 2 : 1;
}
template<int I0, int I1> __device__ __forceinline__ void init_barriers(uint32_t sb) {
    #pragma unroll
    for (int i = I0; i < I1; i++) mbar_init(BAR(i), bar_count(i));
}
__device__ __forceinline__ uint32_t pop_max(uint32_t& k) {
    const uint32_t m = __reduce_max_sync(0xffffffffu, k);
    k = k == m ? 0u : k;
    return m;
}
__device__ __forceinline__ uint32_t mod_pos(int step, int g) { return step * 64 + (g >> 1) * 16 + (g & 1) * 4; }
__device__ __forceinline__ void fma8(float (&a)[8], uint4 w, float s) {
    a[0] = fmaf(bf_lo(w.x), s, a[0]); a[1] = fmaf(bf_hi(w.x), s, a[1]); a[2] = fmaf(bf_lo(w.y), s, a[2]); a[3] = fmaf(bf_hi(w.y), s, a[3]);
    a[4] = fmaf(bf_lo(w.z), s, a[4]); a[5] = fmaf(bf_hi(w.z), s, a[5]); a[6] = fmaf(bf_lo(w.w), s, a[6]); a[7] = fmaf(bf_hi(w.w), s, a[7]);
}
__device__ __forceinline__ float reduce8(const float (&v)[8], int lane) {
    const bool b3 = lane & 16, b2 = lane & 8, b1 = lane & 4;
    float a[4], b[2];
    #pragma unroll
    for (int i = 0; i < 4; i++) { float keep = b3 ? v[4 + i] : v[i], send = b3 ? v[i] : v[4 + i]; a[i] = keep + shfl_x(send, 16); }
    #pragma unroll
    for (int i = 0; i < 2; i++) { float keep = b2 ? a[2 + i] : a[i], send = b2 ? a[i] : a[2 + i]; b[i] = keep + shfl_x(send, 8); }
    float keep = b1 ? b[1] : b[0], send = b1 ? b[0] : b[1];
    return keep + shfl_x(send, 4);
}
__device__ __forceinline__ bool mod_collect(uint4 w0, uint4 w1, uint4 w2, uint4 w3, uint32_t sb, int jb, int lane, uint32_t tag2) {
    const uint32_t add = lane < 16 ? ONE2 : 0u;
    const uint32_t lo = pack2((__uint_as_float(w0.x) + __uint_as_float(w1.x)) + (__uint_as_float(w2.x) + __uint_as_float(w3.x)),
                              (__uint_as_float(w0.y) + __uint_as_float(w1.y)) + (__uint_as_float(w2.y) + __uint_as_float(w3.y)));
    const uint32_t hi = pack2((__uint_as_float(w0.z) + __uint_as_float(w1.z)) + (__uint_as_float(w2.z) + __uint_as_float(w3.z)),
                              (__uint_as_float(w0.w) + __uint_as_float(w1.w)) + (__uint_as_float(w2.w) + __uint_as_float(w3.w)));
    sts64(sb + OFF_MODS + jb * 256 + (lane & 15) * 16 + (lane >> 4) * 8, hadd2(lo, add), hadd2(hi, add));
    return tagged2(w0.w, tag2) && tagged2(w1.w, tag2) && tagged2(w2.w, tag2) && tagged2(w3.w, tag2);
}
__device__ __forceinline__ void phi_issue(float (&pp)[2][16], const uint32_t* a, uint32_t sb, int pair) {
    const uint64_t dw = mk_desc(sb + OFF_WPHI + pair * 4096, 16, 512, 2);
    wg_fence();
    #pragma unroll
    for (int ks = 0; ks < 2; ks++)
        #pragma unroll
        for (int h = 0; h < 2; h++) wgmma_n32_rs<1>(pp[h], a[8 * h + 4 * ks], a[8 * h + 4 * ks + 1], a[8 * h + 4 * ks + 2], a[8 * h + 4 * ks + 3], desc_add(dw, h * 2048 + ks * 1024), ks);
    wg_commit();
}
__device__ __forceinline__ void phi_transpose(float (&pp)[2][16], uint32_t (&pt)[16], uint32_t wr, uint32_t rd) {
    wg_wait<0>();
    acc_fence(pp[0]); acc_fence(pp[1]);
    #pragma unroll
    for (int q = 0; q < 4; q++) {
        const float (&a)[16] = pp[q >> 1]; const int o = 8 * (q & 1);
        stsm4(wr ^ (q << 5), pack2(a[o], a[o + 1]), pack2(a[o + 2], a[o + 3]), pack2(a[o + 4], a[o + 5]), pack2(a[o + 6], a[o + 7]));
    }
    __syncwarp();
    #pragma unroll
    for (int i = 0; i < 4; i++) { const uint4 v = lds128(rd ^ (i << 4)); pt[4 * i] = v.x; pt[4 * i + 1] = v.y; pt[4 * i + 2] = v.z; pt[4 * i + 3] = v.w; }
    __syncwarp();
}

__global__ void __cluster_dims__(2, 1, 1) __launch_bounds__(NTHREADS, 1)
fused_kernel(const Ptrs p, const __grid_constant__ CUtensorMap tmW, const __grid_constant__ CUtensorMap tmWo, const __grid_constant__ CUtensorMap tmPhi,
             const __grid_constant__ CUtensorMap tmG, const __grid_constant__ CUtensorMap tmU, const __grid_constant__ CUtensorMap tmD,
             const __grid_constant__ CUtensorMap tmX, const __grid_constant__ CUtensorMap tmO, const __grid_constant__ CUtensorMap tmM,
             const __grid_constant__ CUtensorMap tmR, const __grid_constant__ CUtensorMap tmG8, const __grid_constant__ CUtensorMap tmU8,
             const __grid_constant__ CUtensorMap tmD8)
{
    extern __shared__ __align__(1024) uint8_t smem_raw[];
    const uint32_t sb = smem_u32(smem_raw);
    const int tid = threadIdx.x, lane = tid & 31, warp = __shfl_sync(0xffffffffu, tid >> 5, 0);
    const int b = blockIdx.x;
    const int pr = b >> 1, rank = b & 1;
    const int cls = pr < 4 ? 15 : pr < 36 ? 2 * ((pr - 4) & 7) : 2 * ((pr - 36) % 7) + 1, mem = pr < 4 ? pr : pr < 36 ? (pr - 4) >> 3 : (pr - 36) / 7;
    const int hg = (((cls + 1) >> 1) & 1) * 4 + mem, rb = (cls >> 1) * 2 + rank;
    const bool ffn = b < 112;
    const uint32_t cstart = clk32();

    if (warp >= 8) {
        const int t = tid & 127, w4 = warp & 3, g = lane >> 2, c = lane & 3;
        reg_dec<40>();
        if (w4 == 0) { tmap_prefetch(&tmX); tmap_prefetch(&tmW); }
        if (w4 == 3) tmap_prefetch(&tmM);
        if (w4 < 2) while (clk32() - cstart < T_INI) {}
        if (elect_one()) {
            if (w4 & 2) { if (w4 & 1) init_barriers<B_WS, B_COUNT>(sb); else init_barriers<B_XS, B_WS>(sb); }
            else { if (w4 & 1) init_barriers<B_MP, B_XS>(sb); else init_barriers<0, B_MP>(sb); }
        }
        __syncwarp();
        if (w4 == 1) {
            asm volatile("fence.mbarrier_init.release.cluster;" ::: "memory");
            expect_tx_e(BAR(B_PX), 2048); sts32(sb + OFF_SEEN, 0);
        }
        bar_arrive(0, 384);
        if (w4 == 2) {
            #pragma unroll 1
            for (int i = 0; i < 4; i++) {
                while (clk32() - cstart < T_X0 + i * T_XD) {}
                bulk_load_e(sb + OFF_XS + i * 8192u, p.x + (size_t)(b * 16 + i * 4) * 1024, 8192, BAR(B_XS + i));
                expect_tx_e(BAR(B_XS + i), 8192);
            }
        }
        if (w4 == 3 && b < 64) {
            while (b >= 32 && clk32() - cstart < T_W1) {}
            #pragma unroll 1
            for (int i = 0; i < 4; i++) {
                tma2_ef_e(sb + OFF_WST + i * 8192u, &tmM, (((b >> 2) & 1) ? 0 : 1024) + (b >> 3) * 64, (b & 3) * 256 + i * 64, BAR(B_WS + i));
                expect_tx_e(BAR(B_WS + i), 8192);
            }
        }
        cluster_arrive();
        const uint32_t tag = ld_rlx(p.s->done) + 1, tag2 = tag % 3u;
        if (w4 == 0) {
            uint4* clr = p.s->kvp + (hg * 1024 + rb) * 32 + lane;
            #pragma unroll 1
            for (int j = 0; j < 3; j++) {
                while (clk32() - cstart < (j ? T_P1 : T_P0)) {}
                if (lane < 24) asm volatile("prefetch.global.L2 [%0];" :: "l"((const char*)p.wqkv + ((j * 128 + b) * 24 + lane) * 128));
            }
            int s = 0, par = 1;
            #pragma unroll 1
            for (int j = 0; j < 19; j++) {
                if (j >= 2) mbar_wait(BAR(j == 2 ? B_STFREE : B_E1 + s), j == 2 ? 0 : par);
                else while (clk32() - cstart < (j ? T_S1 : T_S0)) {}
                const uint32_t st = sb + OFF_RING + s * 65536u;
                if (j < 16) {
                    tma4_ef_e(st + 16384u, &tmW, j * 64, hg * 2, BAR(B_F1 + s));
                    tma2_e(st, &tmX, j * 64, rb * 128, BAR(B_F1 + s));
                    expect_tx_e(BAR(B_F1 + s), 65536);
                    if (j >= WOJ && j < WOJ + 4) asm volatile("prefetch.global.L2 [%0];" :: "l"((const char*)p.wo + (j - WOJ) * 524288 + (b * 32 + lane) * 128));
                } else if (j == 17) {
                    #pragma unroll 1
                    for (int n = 0; n < 2; n++) {
                        expect_tx_e(BAR(B_FB + 4 + n), 16384);
                        tma3_ef_e(st + n * 16384u, &tmWo, (2 * hg + n) * 64, hg * 2, BAR(B_FB + 4 + n));
                    }
                } else if (j == 18) {
                    expect_tx_e(BAR(B_S0), ffn ? 65536 : 32768);
                    #pragma unroll 1
                    for (int i = 0; i < (ffn ? 4 : 2); i++)
                        tma2_ef_e(st + i * 16384u, i < 2 ? &tmX : i == 2 ? &tmG : &tmU, i < 2 ? hg * 128 + i * 64 : pr * 64, i < 2 ? rb * 128 : rank * 512, BAR(B_S0));
                }
                par ^= s == 1;
                s = s == 0 ? 2 : s - 1;
                if (j >= 2 && j < 18) {
                    #pragma unroll
                    for (int i = 0; i < 4; i++) stg_fill(clr + i * 512, EMPTY);
                    clr += 2048;
                }
                const int piece = j - PFJ;
                if (ffn && piece >= 0 && piece < PND + 2 * PNG) {
                    if (piece < PND) tma3_e(sb + OFF_DUMMY, &tmD8, rank * 8, pr * 64 + piece * PRD, BAR(B_PF));
                    else tma2_e(sb + OFF_DUMMY, (piece & 1) ? &tmU8 : &tmG8, pr * 64, rank * 512 + 512 - PRG - ((piece - PND) >> 1) * PRG, BAR(B_PF));
                }
            }
            expect_tx_e(BAR(B_PF), ffn ? PND * PRD * 128 + 2 * PNG * PRG * 16 : 0);
        } else if (w4 == 1) {
            #pragma unroll 1
            for (int it = 0, jb = 4; it < POLL_MAX && jb < 16; it++) {
                while (clk32() - cstart < (jb < 8 ? T_COL : T_COL2)) {}
                const int n = min(4, (jb < 8 ? 8 : 16) - jb);
                bulk_load_e(sb + OFF_WPHI, p.s->mp + jb * 128, n * 2048, BAR(B_MP));
                expect_tx_e(BAR(B_MP), n * 2048);
                mbar_wait(BAR(B_MP), it & 1);
                #pragma unroll 1
                for (int q = 0; q < n; q++) {
                    const uint32_t a = sb + OFF_WPHI + q * 2048 + (lane >> 4) * 1024 + (lane & 15) * 16;
                    if (!__all_sync(0xffffffffu, mod_collect(lds128(a), lds128(a + 256), lds128(a + 512), lds128(a + 768), sb, jb, lane, tag2))) break;
                    arrive_many(BAR(B_MOD + jb), bar_count(B_MOD));
                    jb++;
                }
            }
            fence_async_smem();
            __syncwarp();
            expect_tx_e(BAR(B_WPHI), 8192);
            tma2_e(sb + OFF_WPHI, &tmPhi, 0, hg * 128, BAR(B_WPHI));
            #pragma unroll 1
            for (int i = 0; i < 4; i++) {
                uint4* rw = p.s->rowh + (rb * 8 + i * 2 + (lane >> 4)) * 128 + hg * 16 + (lane & 15);
                stg_fill(rw, EMPTY); stg_fill(rw + 16384, EMPTY);
                if (lane < 18) stg_fill(p.s->kvf + (hg * 4 + i) * 288 + (lane < 16 ? (rb >> 2) * 64 + (rb & 3) * 8 + (lane >> 3) * 32 + (lane & 7) : 240 + rb * 2 + lane), EMPTY);
            }
            if (hg == 0 && lane < 8) stg_fill(p.s->cand + rb * 8 + lane, 0);
            if (lane < 28) stg_fill(lane < 16 ? p.s->st2 + rb * 128 + hg * 16 + lane : lane < 20 ? p.s->flo + (rb * 16 + hg * 2) * 2 + lane - 16
                                    : p.s->rsc + ((rb * 4 + ((lane - 20) >> 1)) * 8 + hg) * 2 + (lane & 1), 0);
            fence_rel_gpu();
            #pragma unroll 1
            for (int i = 0; i < (ffn ? 9 : 8); i++) {
                while (clk32() - cstart < T_OSC + i * T_OSD) {}
                uint4* d = (i < 8 ? p.s->os + (rb * 16 + 2 * hg) * 1024 + i * 256 : p.s->yp + pr * 512 + rank * 128) + lane;
                #pragma unroll
                for (int q = 0; q < 4; q++) { stg_fill(d + q * 32, EMPTY); stg_fill(d + (i < 8 ? 128 : 256) + q * 32, EMPTY); }
            }
        } else {
            const int hw = w4 & 1;
            const uint32_t fb = BAR(B_RF + 2 * hw);
            if (w4 == 2) {
                if (lane < 8) stg_fill(p.s->rest + b * 8 + lane, 0);
                else if (lane < 24 && b >= 64) stg_fill(p.s->mp + b * 16 + lane - 8, EMPTY);
            }
            bar_sync(3, 320);
            const uint32_t buf = sb + OFF_SP + hw * 8192u;
            #pragma unroll 1
            for (int job = b < 64; job < 2; job++) {
                const int nr = job ? 8 : 4;
                const int c0 = job ? 2048 + b * 32 : (((b >> 2) & 1) ? 0 : 1024) + (b >> 3) * 64 + hw * 32;
                const int row0 = job ? hw * 512 : (b & 3) * 256;
                while (clk32() - cstart < (job ? T_REST : T_WLATE)) __nanosleep(100);
                float macc[8] = {0.f, 0.f, 0.f, 0.f, 0.f, 0.f, 0.f, 0.f};
                #pragma unroll 1
                for (int q = -2; q < nr; q++) {
                    if (q >= 0) {
                        mbar_wait(fb + (q & 1) * 8, (q >> 1) & 1);
                        const uint32_t sv0 = sb + OFF_SILU + (row0 + q * 64 + g) * 2, wa = buf + (q & 1) * 4096u + lane * 16u;
                        #pragma unroll
                        for (int i = 0; i < 8; i += 2) {
                            const uint32_t s0 = lds16(sv0 + i * 16), s1 = lds16(sv0 + i * 16 + 16);
                            const uint4 w0 = lds128(wa + i * 512u), w1 = lds128(wa + i * 512u + 512u);
                            fma8(macc, w0, bf_lo(s0)); fma8(macc, w1, bf_lo(s1));
                        }
                    }
                    __syncwarp();
                    if (q + 2 < nr) {
                        expect_tx_e(fb + (q & 1) * 8, 4096);
                        tma2_ef_e(buf + (q & 1) * 4096u, &tmR, c0, row0 + (q + 2) * 64, fb + (q & 1) * 8);
                    }
                }
                stsf(sb + OFF_RED0 + (job ? hw * 256 + (c * 8 + g) * 4 : mod_pos(hw * 2 + (c >> 1), g) + (c & 1) * 8), reduce8(macc, lane));
                bar_sync(4, 64);
                if (w4 == 2) {
                    const uint4 u0 = lds128(sb + OFF_RED0 + (lane & 15) * 16), u1 = lds128(sb + OFF_RED0 + 256 + (lane & 15) * 16);
                    const float v0 = __uint_as_float(u0.x) + __uint_as_float(u1.x), v1 = __uint_as_float(u0.y) + __uint_as_float(u1.y);
                    const float v2 = __uint_as_float(u0.z) + __uint_as_float(u1.z), v3 = __uint_as_float(u0.w) + __uint_as_float(u1.w);
                    const uint32_t add = (b >> 5) == 2 ? ONE2 : 0u;
                    if (job == 0) { if (lane < 16) st_ll(p.s->mp + b * 16 + lane, u0.x, u0.y, u0.z, low_bits(__uint_as_float(u0.w), tag2)); }
                    else { if (lane < 8) st_ll(p.s->rest + b * 8 + lane, hadd2(pack2(v0, v1), add), hadd2(pack2(v2, v3), add), 0, tag); }
                }
                bar_sync(4, 64);
            }
            tmap_prefetch(hw ? &tmWo : &tmG); tmap_prefetch(hw ? &tmU : &tmD); tmap_prefetch(hw ? &tmPhi : &tmO);
        }
        __syncwarp();
        cluster_wait();
        bar_sync(2, 128);
        reg_inc<504 - 2 * CREG>();
        #pragma unroll 1
        for (int pp = 0; pp < 2; pp++) {
            mbar_wait(BAR(B_PHI + pp), 0);
            fence_async_smem();
            float o[2][20];
            const uint32_t vb = OFF_V + pp * 16384u;
            const uint64_t dp = mk_desc(sb + (pp ? OFF_PHI1 : OFF_PHI0), 16, 1024, 1), dv = mk_desc(sb + vb, OFF_ONES - vb, 512, 2);
            wg_fence();
            #pragma unroll
            for (int hh = 0; hh < 2; hh++) {
                #pragma unroll
                for (int ks = 0; ks < 8; ks++)
                    wgmma_n40_ss<1, 1>(o[hh], desc_add(dp, hh * 16384 + ks * 2048), desc_raw(dv, (hh * 8 + ks) * (64 - (64 << 16))), ks);
                wg_commit();
            }
            #pragma unroll
            for (int hh = 0; hh < 2; hh++) {
                if (hh) wg_wait<0>(); else wg_wait<1>();
                acc_fence(o[hh]);
                if (hh) arrive_one(BAR(B_KVD + pp));
                if (hh == 0 && pp && w4 < 2) {
                    mbar_wait(BAR(B_KVD), 0);
                    bulk_load_e(sb + OFF_KVS + w4 * 8192u, p.s->kvp + ((hg * 4 + w4) * 16 + rb) * 512, 8192, BAR(B_KVS + w4));
                    expect_tx_e(BAR(B_KVS + w4), 8192);
                }
                uint4* dst = p.s->kvp + (((hg * 4 + 2 * pp + hh) * 16 + (t >> 3)) * 16 + rb) * 32 + (t & 7);
                const float (&a)[20] = o[hh];
                #pragma unroll
                for (int k = 0; k < 2; k++) {
                    const uint32_t z = __float_as_uint(a[16 + 2 * k]);
                    st_ll(dst + k * 8, low_byte<1>(a[4 * k], z), low_byte<2>(a[4 * k + 1], z), low_byte<3>(a[4 * k + 2], z), low_bits(a[4 * k + 3], tag2));
                    st_ll(dst + 16 + k * 8, __float_as_uint(a[8 + 4 * k]), __float_as_uint(a[9 + 4 * k]), __float_as_uint(a[10 + 4 * k]), low_bits(a[11 + 4 * k], tag2));
                }
            }
        }
        {
            uint4* const fin = p.s->kvf + (hg * 4 + w4) * 288;
            {
                const uint4* src = p.s->kvp + ((hg * 4 + w4) * 16 + rb) * 512 + lane;
                uint4 w[16];
                if (w4 < 2) {
                    mbar_wait(BAR(B_KVS + w4), 0);
                    #pragma unroll
                    for (int i = 0; i < 16; i++) w[i] = lds128(sb + OFF_KVS + w4 * 8192u + i * 512u + lane * 16u);
                } else {
                    pause(KVDLY);
                    #pragma unroll
                    for (int i = 0; i < 16; i++) w[i].w = EMPTY;
                }
                #pragma unroll 1
                for (int it = 0; it < POLL_MAX; it++) {
                    uint32_t bad = 0;
                    #pragma unroll
                    for (int i = 0; i < 16; i++) bad |= w[i].w ^ tag2;
                    if (__all_sync(0xffffffffu, !(bad & 3))) break;
                    #pragma unroll
                    for (int i = 0; i < 16; i++) ld_ll_if(w[i], src + i * 32, !tagged2(w[i].w, tag2));
                }
                float s[5], s2[5];
                #pragma unroll
                for (int i = 0; i < 16; i++) {
                    const float z = __uint_as_float(__byte_perm(__byte_perm(w[i].x, w[i].y, 0x0400), w[i].z, 0x4210));
                    float (&a)[5] = (i & 1) ? s2 : s;
                    if (i < 2) { a[0] = __uint_as_float(w[i].x); a[1] = __uint_as_float(w[i].y); a[2] = __uint_as_float(w[i].z); a[3] = __uint_as_float(w[i].w); a[4] = z; }
                    else { a[0] += __uint_as_float(w[i].x); a[1] += __uint_as_float(w[i].y); a[2] += __uint_as_float(w[i].z); a[3] += __uint_as_float(w[i].w); a[4] += z; }
                }
                #pragma unroll
                for (int i = 0; i < 5; i++) s[i] += s2[i];
                char* d = (char*)fin + ((rb >> 2) * 16 + (rb & 3) * 2 + (g & 1)) * 64 + (((lane >> 3) ^ (rb & 3)) << 4) + c * 4;
                st_ll4(d, pack2(s[0], s[1]));
                st_ll4(d + 512, pack2(s[2], s[3]));
                if (lane < 16 && c < 2) st_ll4((char*)fin + 4096 + rb * 32 + (g * 2 + c) * 4, pack2(s[4], s[4]));
            }
            mbar_wait(BAR(B_PF), 1);
            fence_acq_gpu();
            uint4 v[9];
            #pragma unroll 1
            for (int it = 0; it < POLL_MAX; it++) {
                uint32_t m = 0;
                #pragma unroll
                for (int k = 0; k < 9; k++) v[k] = ld_ll(fin + k * 32 + lane);
                #pragma unroll
                for (int k = 0; k < 9; k++) m = max(m, umax4(v[k]));
                if (__all_sync(0xffffffffu, m != EMPTY)) break;
            }
            #pragma unroll
            for (int k = 0; k < 8; k++) sts128(sb + OFF_SP + w4 * 4096u + k * 512u + lane * 16u, v[k]);
            const uint32_t za = sb + OFF_Z + ((lane >> 3) * 16 + ((lane >> 1) & 3) * 2 + (lane & 1) * 8) * 64u + ((w4 ^ ((lane >> 1) & 3)) << 4);
            sts128(za, make_uint4(v[8].x, v[8].x, v[8].x, v[8].x)); sts128(za + 64, make_uint4(v[8].z, v[8].z, v[8].z, v[8].z));
            __syncwarp();
            arrive_one(BAR(B_KVF + (w4 >> 1)));
        }
        if (w4 == 0) {
            const unsigned* f = (const unsigned*)(p.s->flo + (rb * 16 + d_block(hg, lane & 15)) * 2);
            const uint4* const a0 = p.s->os + rb * 16384;
            uint32_t seen = 0;
            uint32_t kb = hg ? 0 : 2, s = 4, freeb = BAR(B_OWN), par = 0;
            mbar_wait(BAR(B_OWN), 0);
            fence_async_smem();
            bulk_store_e(p.s->os + (rb * 16 + 2 * hg) * 1024, sb + OFF_OWN, 16384);
            bulk_commit();
            mbar_wait(BAR(B_REL), 0);
            bulk_wait();
            st_flag_e(p.s->flo + (rb * 16 + 2 * hg) * 2, tag);
            #pragma unroll 1
            for (int n = 2; n < 16; n++) {
                if (!((seen >> n) & 1)) {
                    if (n >= 8) asm volatile("ld.acquire.cta.shared.u32 %0, [%1];" : "=r"(seen) : "r"(sb + OFF_SEEN) : "memory");
                    #pragma unroll 1
                    for (int it = 0; it < POLL_MAX && !((seen >> n) & 1); it++) { seen = __ballot_sync(0xffffffffu, ld_rlx(f) == tag); fence_acq_gpu(); }
                }
                mbar_wait(freeb, par);
                bulk_load_e(sb + OFF_DA + s * 16384u, a0 + kb * 1024, 16384, BAR(B_FA + s));
                expect_tx_e(BAR(B_FA + s), 16384);
                if (n == 6) mbar_wait(BAR(B_PUB), 0);
                kb = n == 8 ? 1 : kb + 2;
                if ((kb >> 1) == hg) kb += 2;
                s = (SLOT_A >> (4 * n + 4)) & 7;
                if (n >= 5) { freeb = BAR(B_ED + n - 5); par = 1; } else if (n == 3) freeb = BAR(B_OWN + 1);
            }
        } else if (w4 == 1) {
            if (ffn) { expect_tx_e(BAR(B_GU), 98304); expect_tx_e(BAR(B_WD), 65536); }
            fence_rel_gpu();
            arrive_one(BAR(B_REL));
            mbar_wait(BAR(B_S0FREE), 0);
            #pragma unroll 1
            for (int n = 2; n < (ffn ? 20 : 16); n++) {
                if (n >= 6) mbar_wait(BAR(B_ED + n - 6), 1);
                if (n < 16) {
                    const uint32_t s = (SLOT_B >> (4 * n)) & 7, bar = BAR(B_FB + s), dst = sb + OFF_DB + s * 16384u;
                    expect_tx_e(bar, 16384);
                    tma3_ef_e(dst, &tmWo, d_block(hg, n) * 64, hg * 2, bar);
                    if (ffn && (n == 6 || n == 7)) tma2_ef_e(sb + OFF_GB + (n & 1) * 16384u, (n & 1) ? &tmU : &tmG, pr * 64, rank * 512 + 128, BAR(B_GU));
                } else if (n < 18) {
                    tma2_ef_e(sb + OFF_UP0 + (n & 1) * 16384u, (n & 1) ? &tmU : &tmG, pr * 64, rank * 512 + 256, BAR(B_GU));
                    tma2_ef_e(sb + OFF_UP1 + (n & 1) * 16384u, (n & 1) ? &tmU : &tmG, pr * 64, rank * 512 + 384, BAR(B_GU));
                } else {
                    tma3_ef_e(sb + OFF_DN0 + (n & 1) * 16384u, &tmD, pr * 64, rank * 8 + (n & 1) * 2, BAR(B_WD));
                    tma3_ef_e(sb + OFF_DN1 + (n & 1) * 16384u, &tmD, pr * 64, rank * 8 + 4 + (n & 1) * 2, BAR(B_WD));
                }
            }
        } else if (w4 == 3) {
            const unsigned* f = (const unsigned*)(p.s->flo + (rb * 16 + d_block(hg, lane & 15)) * 2);
            uint32_t seen = 0xffff0003u;
            mbar_wait(BAR(B_PUB), 0);
            #pragma unroll 1
            for (int it = 0; it < POLL_MAX && seen != 0xffffffffu; it++) {
                const uint32_t m = seen | __ballot_sync(0xffffffffu, !((seen >> lane) & 1) && ld_rlx(f) == tag);
                if (m != seen) {
                    seen = m;
                    fence_acq_gpu();
                    __syncwarp();
                    asm volatile(EL "st.release.cta.shared.u32 [%0], %1;\n}" :: "r"(sb + OFF_SEEN), "r"(seen) : "memory");
                }
            }
        } else {
            mbar_wait(BAR(B_OWN + 1), 0);
            fence_async_smem();
            #pragma unroll 1
            for (uint32_t i = 0, due = clk32() + OP0; i < 4; i++, due += OPS) {
                while ((int)(clk32() - due) < 0) {}
                bulk_store_e(p.s->os + (rb * 16 + 2 * hg + 1) * 1024 + i * 256, sb + OFF_OWN + 16384u + i * 4096u, 4096);
            }
            bulk_commit();
            mbar_wait(BAR(B_REL), 0);
            bulk_wait();
            st_flag_e(p.s->flo + (rb * 16 + 2 * hg + 1) * 2, tag);
            arrive_one(BAR(B_PUB));
            {
                uint4 w[4];
                poll_words<4>(w, p.s->rest + hg * 32 + lane, 256, tag);
                sts64(sb + OFF_PAR + lane * 8, w[2].x, w[2].y); sts64(sb + OFF_PAR + 256 + lane * 8, w[1].x, w[1].y);
                sts64(sb + OFF_PAR + 512 + lane * 8, w[3].x, w[3].y); sts64(sb + OFF_PAR + 768 + lane * 8, w[0].x, w[0].y);
                const uint2 wr = ldg64(p.wr + hg * 128 + lane * 4);
                sts64(sb + OFF_BQ + lane * 8, hmul2(w[2].x, wr.x), hmul2(w[2].y, wr.y));
            }
            float s = 0.f;
            #pragma unroll 1
            for (int i = 0; i < 2; i++) {
                uint4 w[4]; uint2 wr[4];
                #pragma unroll
                for (int q = 0; q < 4; q++) wr[q] = ldg64(p.wr + (lane + 32 * q + 128 * i) * 4);
                poll_words<4>(w, p.s->rest + 512 + i * 128 + lane, 32, tag);
                #pragma unroll
                for (int q = 0; q < 4; q++) { const uint32_t r0 = hmul2(w[q].x, wr[q].x), r1 = hmul2(w[q].y, wr[q].y); s += (bf_lo(r0) + bf_hi(r0)) + (bf_lo(r1) + bf_hi(r1)); }
            }
            __syncwarp();
            #pragma unroll
            for (int m = 16; m >= 1; m >>= 1) s += shfl_x(s, m);
            if (lane == 0) { stsf(sb + OFF_ATOT, s); sts128(sb + OFF_BQ + 272, make_uint4(ONE2, ONE2, ONE2, ONE2)); }
            __syncwarp();
            arrive_one(BAR(B_PAR));
        }
        __syncwarp();
        {
            mbar_wait(BAR(B_PAR), 0);
            const uint4 pa = lds128(sb + OFF_PAR + (lane & 15) * 16), ps = lds128(sb + OFF_PAR + 256 + (lane & 15) * 16);
            const uint4 wr = ldg128(p.wr + hg * 128 + (lane & 15) * 8);
            const float atot = ldsf(sb + OFF_ATOT);
            mbar_wait(BAR(B_RED), 0);
            uint4 w;
            #pragma unroll 1
            for (int it = 0; it < POLL_MAX; it++) {
                w = ld_ll(p.s->st2 + rb * 128 + t);
                if (__all_sync(0xffffffffu, __uint_as_float(w.w) == 8.0f)) break;
            }
            uint32_t m2; float rinv;
            ln_final(__uint_as_float(w.x), __uint_as_float(w.y), m2, rinv);
            uint32_t k = (f2key(fmaf(-bf_lo(m2), atot, __uint_as_float(w.z)) * rinv) & ~0xfffu) | ((2047 - rb * 128 - t) << 1);
            const uint32_t best0 = pop_max(k), best1 = pop_max(k) | 1u, grp = rb * 4 + w4;
            if (hg == 0 && lane < 2) st_ll(p.s->cand + grp * 2 + lane, best0, best1, 0, tag);
            const uint32_t row = 127 - (((lane < 16 ? best0 : best1) >> 1) & 127u);
            mbar_wait(BAR(B_X2), 0);
            const uint4 xv = lds128(sb + OFF_OUT + (row >> 3) * 2048u + ((lane >> 3) & 1) * 1024u + (row & 7) * 128u + (((lane ^ row) & 7) << 4));
            sts64(sb + OFF_ST2 + t * 8, m2, __float_as_uint(rinv));
            __syncwarp();
            arrive_one(BAR(B_ST2));
            const uint32_t rm = __shfl_sync(0xffffffffu, m2, row & 31);
            const Recip rr = split_recip(__shfl_sync(0xffffffffu, rinv, row & 31));
            const uint32_t h0 = ln_pair(xv.x, rm, rr, pa.x, ps.x), h1 = ln_pair(xv.y, rm, rr, pa.y, ps.y);
            const uint32_t h2 = ln_pair(xv.z, rm, rr, pa.z, ps.z), h3 = ln_pair(xv.w, rm, rr, pa.w, ps.w);
            uint4* d = p.s->rowh + (grp * 2 + (lane >> 4)) * 128 + hg * 16 + (lane & 15);
            st_ll(d, h0, h1, h2, h3);
            st_ll(d + 16384, xv.x, xv.y, xv.z, xv.w);
            float r = (fmaf(bf_lo(h0), bf_lo(wr.x), bf_hi(h0) * bf_hi(wr.x)) + fmaf(bf_lo(h1), bf_lo(wr.y), bf_hi(h1) * bf_hi(wr.y)))
                    + (fmaf(bf_lo(h2), bf_lo(wr.z), bf_hi(h2) * bf_hi(wr.z)) + fmaf(bf_lo(h3), bf_lo(wr.w), bf_hi(h3) * bf_hi(wr.w)));
            #pragma unroll
            for (int m = 8; m >= 1; m >>= 1) r += shfl_x(r, m);
            if (!(lane & 15)) st_ll(p.s->rsc + (grp * 8 + hg) * 2 + (lane >> 4), __float_as_uint(r), 0, 0, tag);
        }
        if (w4 == 0) {
            uint4 cv[2];
            poll_words<2>(cv, p.s->cand + lane * 2, 64, tag);
            __syncwarp();
            const uint32_t ka = min(cv[0].x, cv[1].x), kb = max(cv[0].y, cv[1].y);
            uint32_t k0 = max(cv[0].x, cv[1].x), k1 = max(ka, kb), k2 = min(ka, kb), k3 = min(cv[0].y, cv[1].y), id[4];
            uint4 hv[4][2], sc;
            const uint4* ha[4];
            #pragma unroll
            for (int i = 0; i < 4; i++) {
                const uint32_t m = __reduce_max_sync(0xffffffffu, k0);
                if (k0 == m) { k0 = k1; k1 = k2; k2 = k3; }
                id[i] = (m & 0xfffu) ^ 0xffeu;
                ha[i] = p.s->rowh + ((id[i] >> 6) * 2 + (id[i] & 1)) * 128 + rank * 64 + lane;
                hv[i][0] = ld_ll(ha[i]); hv[i][1] = ld_ll(ha[i] + 32);
            }
            const uint32_t myid = lane < 16 ? (lane < 8 ? id[0] : id[1]) : (lane < 24 ? id[2] : id[3]), row = myid >> 1;
            const uint4* sa = p.s->rsc + ((myid >> 6) * 8 + (lane & 7)) * 2 + (myid & 1);
            sc = ld_ll(sa);
            sts32(sb + OFF_SEL + 32 + (lane >> 3) * 4, row);
            __syncwarp();
            arrive_one(BAR(B_CAND));
            #pragma unroll 1
            for (int it = 0; it < POLL_MAX; it++) {
                uint32_t m = 0;
                #pragma unroll
                for (int i = 0; i < 4; i++) m = max(m, max(hv[i][0].x, hv[i][1].x));
                if (__all_sync(0xffffffffu, m != EMPTY && sc.w == tag)) break;
                #pragma unroll
                for (int i = 0; i < 4; i++) { hv[i][0] = ld_ll(ha[i]); hv[i][1] = ld_ll(ha[i] + 32); }
                sc = ld_ll(sa);
            }
            #pragma unroll
            for (int i = 0; i < 4; i++) { sts128(sb + OFF_ROWS + i * 1056u + lane * 16u, hv[i][0]); sts128(sb + OFF_ROWS + i * 1056u + 528u + lane * 16u, hv[i][1]); }
            __syncwarp();
            arrive_one(BAR(B_ROWS));
            float r = __uint_as_float(sc.x);
            r += shfl_x(r, 1); r += shfl_x(r, 2); r += shfl_x(r, 4);
            r = rbf(r);
            const uint32_t key = (f2key(r) & 0xffff0000u) | (0xffffu - row);
            uint32_t kq = key;
            const uint32_t best0 = pop_max(kq), best1 = pop_max(kq), tok = key == best0 ? 0 : key == best1 ? 1 : 2;
            sts32(sb + OFF_SEL + 48 + (lane >> 3) * 4, tok);
            if (tok < 2) sts128(sb + OFF_SEL + tok * 16, make_uint4(row, (myid >> 6) * 2 + (myid & 1), __float_as_uint(r), 0));
            __syncwarp();
            arrive_one(BAR(B_SEL));
        } else if (w4 == 1) {
            mbar_wait(BAR(B_SEL), 0);
            const uint4 sel = lds128(sb + OFF_SEL + rank * 16);
            const int col = pr * 16 + c * 2 + (lane >> 4) + (lane & 8);
            uint32_t xs, hs; uint4 gw;
            #pragma unroll 1
            for (int it = 0; it < POLL_MAX; it++) {
                const char* a = (const char*)(p.s->rowh + sel.y * 128) + (col >> 1) * 4;
                hs = ld_rlx(a); xs = ld_rlx(a + 262144); gw = ld_ll(p.s->rest + 768 + (col >> 2));
                if (__all_sync(0xffffffffu, hs != EMPTY && xs != EMPTY && gw.w == tag)) break;
            }
            const uint32_t gq = (col & 2) ? gw.y : gw.x;
            const float fx = (col & 1) ? bf_hi(xs) : bf_lo(xs), fh = (col & 1) ? bf_hi(hs) : bf_lo(hs), fg = (col & 1) ? bf_hi(gq) : bf_lo(gq);
            const float sg = rbf(sigmoidf(__uint_as_float(sel.z)));
            const uint4* src = p.s->yp + g * 512 + rank * 256 + pr * 4 + c;
            bf16* optr = p.out + (size_t)sel.x * 1024 + col;
            asm volatile("" : "+l"(optr));
            uint4 w[7];
            #pragma unroll
            for (int i = 0; i < 7; i++) w[i] = make_uint4(0, EMPTY, 0, EMPTY);
            if (ffn) mbar_wait(BAR(B_YP), 0);
            #pragma unroll 1
            for (int it = 0; it < POLL_MAX; it++) {
                bool ok = true;
                #pragma unroll
                for (int i = 0; i < 7; i++) ld_ll_if(w[i], src + i * 4096, !(tagged2(w[i].y, tag2) && tagged2(w[i].w, tag2)));
                #pragma unroll
                for (int i = 0; i < 7; i++) ok = ok && tagged2(w[i].y, tag2) && tagged2(w[i].w, tag2);
                if (__all_sync(0xffffffffu, ok)) break;
            }
            float y0 = __uint_as_float(w[0].x), y1 = __uint_as_float(w[0].y), y2 = __uint_as_float(w[0].z), y3 = __uint_as_float(w[0].w);
            #pragma unroll
            for (int i = 1; i < 7; i++) { y0 += __uint_as_float(w[i].x); y1 += __uint_as_float(w[i].y); y2 += __uint_as_float(w[i].z); y3 += __uint_as_float(w[i].w); }
            const bool b4 = lane & 16, b3 = lane & 8;
            const float a0 = (b4 ? y2 : y0) + shfl_x(b4 ? y0 : y2, 16), a1 = (b4 ? y3 : y1) + shfl_x(b4 ? y1 : y3, 16);
            float y = (b3 ? a1 : a0) + shfl_x(b3 ? a0 : a1, 8);
            y += shfl_x(y, 4);
            const float upd = rbf(rbf(y) * sg);
            if (!(lane & 4)) *optr = __float2bfloat16(fx + rbf(fg * rbf(fh + upd)));
            if (b == 0 && lane == 0) p.s->done[0] = tag;
        } else if (w4 == 2) {
            mbar_wait(BAR(B_CAND), 0);
            const uint32_t cg = (lds32(sb + OFF_SEL + 32 + c * 4) >> 3) - rb * 16;
            uint32_t late = __reduce_or_sync(0xffffffffu, cg < 16 ? 1u << cg : 0u);
            mbar_wait(BAR(B_OUTW), 0);
            fence_async_smem();
            #pragma unroll 1
            for (uint32_t i = 0; i < 16; i++)
                if (!((late >> i) & 1))
                    asm volatile(EL "cp.async.bulk.tensor.3d.global.shared::cta.bulk_group [%0, {0, %2, %3}], [%1];\n}"
                        :: "l"(&tmO), "r"(sb + OFF_OUT + i * 2048u), "r"(rb * 128 + i * 8), "r"(hg * 2) : "memory");
            bulk_commit();
            mbar_wait(BAR(B_SEL), 0);
            const uint32_t row0 = lds32(sb + OFF_SEL) - rb * 128, row1 = lds32(sb + OFF_SEL + 16) - rb * 128;
            #pragma unroll 1
            for (; late; late &= late - 1) {
                const uint32_t i = __ffs(late) - 1;
                #pragma unroll 1
                for (uint32_t q = 0; q < 4; q++) {
                    const uint32_t r = q * 2 + (lane >> 4), ch = lane & 15;
                    const uint4 v = lds128(sb + OFF_OUT + i * 2048u + (ch >> 3) * 1024u + r * 128u + (((ch ^ r) & 7) << 4));
                    if (i * 8 + r != row0 && i * 8 + r != row1) stg128(p.out + (size_t)(rb * 128 + i * 8 + r) * 1024 + hg * 128 + ch * 8, v);
                }
            }
            bulk_wait();
        }
    } else {
        const int w4 = warp & 3, wgi = warp >> 2;
        uint32_t m2[2], r[4]; Recip ri0, ri1;
        uint32_t tag2;
        {
            const int g = lane >> 2, c = lane & 3, xrow = b * 16 + warp * 2;
            if (b < 32)
                asm volatile("prefetch.global.L2 [%0];" :: "l"(p.wmod + (size_t)((b & 3) * 256 + tid) * 6144 + (((b >> 2) & 1) ? 0 : 1024) + (b >> 3) * 64));
            const uint2 cv = ldg64(p.c + tid * 4);
            const uint32_t tag = ld_rlx(p.s->done) + 1;
            if (lane < 2) stg_fill(p.s->st1 + xrow + lane, 0);
            if (warp == 0 && lane < 16 && b < 64) stg_fill(p.s->mp + b * 16 + lane, EMPTY);
            if (tid < 64) { int s = tid >> 2; sts128(sb + OFF_ONES + tid * 16, make_uint4(((tid & 3) == ((s >> 1) & 3)) ? 0x3F80u : 0u, 0, 0, 0)); }
            cluster_arrive();
            reg_inc<232>();
            {
                const float c0 = bf_lo(cv.x), c1 = bf_hi(cv.x), c2 = bf_lo(cv.y), c3 = bf_hi(cv.y);
                sts64(sb + OFF_SILU + tid * 8, pack2(c0 * sigmoidf(c0), c1 * sigmoidf(c1)), pack2(c2 * sigmoidf(c2), c3 * sigmoidf(c3)));
            }
            tag2 = tag % 3u;
            bar_sync(0, 384);
            bar_arrive(3, 320);
            #pragma unroll 1
            for (int part = 0; part < 2; part++)
            if (part == (b < 32)) {
                mbar_wait(BAR(B_XS + (warp >> 1)), 0);
                float sd[2][4], q1[2][4], q2[2][4];
                #pragma unroll
                for (int e = 0; e < 4; e++) { sd[0][e] = sd[1][e] = q1[0][e] = q1[1][e] = q2[0][e] = q2[1][e] = 0.f; }
                #pragma unroll
                for (int i = 0; i < 8; i++) {
                    uint32_t a0, a1, a2, a3;
                    ldsm4(a0, a1, a2, a3, sb + OFF_XS + warp * 4096u + ((lane >> 3) & 1) * 2048u + i * 256u + (lane >> 4) * 128u + (lane & 7) * 16u);
                    mma16816(sd[i & 1], a0, a1, a2, a3, ONE2, ONE2);
                    mma1688(q1[0], a0, a1, a0); mma1688(q2[0], a0, a1, a1); mma1688(q1[1], a2, a3, a2); mma1688(q2[1], a2, a3, a3);
                }
                const float d0 = __shfl_sync(0xffffffffu, (g & 1) ? q1[0][1] + q1[1][1] : q1[0][0] + q1[1][0], g * 4 + (g >> 1));
                const float d1 = __shfl_sync(0xffffffffu, (g & 1) ? q2[0][3] + q2[1][3] : q2[0][2] + q2[1][2], g * 4 + (g >> 1));
                float sk = (c & 1) ? sd[0][2] + sd[1][2] : sd[0][0] + sd[1][0], qk = (c & 1) ? d1 : d0;
                #pragma unroll
                for (int m = 4; m <= 16; m <<= 1) { sk += shfl_x(sk, m); qk += shfl_x(qk, m); }
                uint32_t mm; float ri;
                ln_final(sk, qk, mm, ri);
                const Recip rr = split_recip(ri);
                if (lane < 2) st_ll(p.s->st1 + xrow + lane, mm, rr.hi, rr.lo, tag);
            } else if (b < 64) {
                float m[4][4];
                uint32_t sv[4];
                ldsm4(sv[0], sv[1], sv[2], sv[3], sb + OFF_SILU + ((b & 3) * 256 + warp * 32) * 2 + (lane >> 3) * 16);
                mbar_wait(BAR(B_WS + (warp >> 1)), 0);
                #pragma unroll
                for (int tt = 0; tt < 4; tt++) {
                    m[tt][0] = m[tt][1] = m[tt][2] = m[tt][3] = 0.f;
                    #pragma unroll
                    for (int e = 0; e < 2; e++) {
                        uint32_t a0, a1, a2, a3;
                        ldsm4t(a0, a1, a2, a3, sb + OFF_WST + warp * 4096u + (e * 16 + (lane & 7) + ((lane >> 4) << 3)) * 128u + (((2 * tt + ((lane >> 3) & 1)) ^ (lane & 7)) << 4));
                        mma16816(m[tt], a0, a1, a2, a3, sv[2 * e], sv[2 * e + 1]);
                    }
                }
                const uint32_t ra = sb + OFF_RED0 + warp * 256 + mod_pos(c, g);
                stsf(ra, (c & 2) ? ((c & 1) ? m[3][0] : m[2][0]) : ((c & 1) ? m[1][0] : m[0][0]));
                stsf(ra + 8, (c & 2) ? ((c & 1) ? m[3][2] : m[2][2]) : ((c & 1) ? m[1][2] : m[0][2]));
                if (warp != 7) bar_arrive(5, 256);
                else {
                    bar_sync(5, 256);
                    float v0 = 0.f, v1 = 0.f, v2 = 0.f, v3 = 0.f;
                    #pragma unroll
                    for (int w = 0; w < 4; w++) {
                        const uint4 u = lds128(sb + OFF_RED0 + w * 512 + lane * 16);
                        v0 += __uint_as_float(u.x); v1 += __uint_as_float(u.y); v2 += __uint_as_float(u.z); v3 += __uint_as_float(u.w);
                    }
                    v0 += shfl_x(v0, 16); v1 += shfl_x(v1, 16); v2 += shfl_x(v2, 16); v3 += shfl_x(v3, 16);
                    if (lane < 16) st_ll(p.s->mp + b * 16 + lane, __float_as_uint(v0), __float_as_uint(v1), __float_as_uint(v2), low_bits(v3, tag2));
                }
            }
            cluster_wait();
            uint4 st[2];
            bool need = warp < 4;
            #pragma unroll 1
            for (int it = 0; it < POLL_MAX; it++) {
                st[0] = ld_ll(p.s->st1 + rb * 128 + warp * 16 + g); st[1] = ld_ll(p.s->st1 + rb * 128 + warp * 16 + g + 8);
                if (need) {
                    const uint4* src = p.s->mp + (warp * 8 + (lane >> 4) * 4) * 16 + (lane & 15);
                    const uint4 w0 = ld_ll(src), w1 = ld_ll(src + 16), w2 = ld_ll(src + 32), w3 = ld_ll(src + 48);
                    if (__all_sync(0xffffffffu, mod_collect(w0, w1, w2, w3, sb, warp, lane, tag2))) {
                        need = false;
                        arrive_many(BAR(B_MOD + warp), bar_count(B_MOD));
                    }
                }
                if (it == 0) {
                    mbar_wait(BAR(B_F1), 0);
                    ldsm4(r[0], r[1], r[2], r[3], sb + OFF_RING + (warp * 16 + (lane & 15)) * 128u + ((((lane >> 4) ^ lane) & 7) << 4));
                }
                if (__all_sync(0xffffffffu, st[0].w == tag && st[1].w == tag) && !need) break;
            }
            m2[0] = st[0].x; ri0.hi = st[0].y; ri0.lo = st[0].z; m2[1] = st[1].x; ri1.hi = st[1].y; ri1.lo = st[1].z;
            arrive_one(BAR(B_STFREE));
        }
        const int lane = lane_id(), g = lane >> 2, c = lane & 3;
        const int srow = warp * 16 + (lane & 15);
        const uint32_t aoff = srow * 128u + ((((lane >> 4) ^ srow) & 7) << 4);
        uint32_t pt[16], qf[32];
        float pp[2][16];
        const uint32_t roff = srow * 128u + ((lane & 7) << 4);
        {
            float accKV[128], accQ[64];
            {
                uint32_t f[2][4];
                mbar_wait(BAR(B_MOD), 0);
                uint4 md = lds128(sb + OFF_MODS + c * 16);
                int s = 0, sp = 1, par = 0;
                #pragma unroll 1
                for (int j = 0; j < 16; j++) {
                    const int sn = s == 0 ? 2 : s - 1;
                    par ^= s == 1;
                    const uint32_t modb = (wgi && j == 15) ? BAR(B_TURN) : BAR(B_MOD + ((j + 1) & 15));
                    const uint64_t db = mk_desc(sb + OFF_RING + s * 65536u + 16384u, 8192, 1024, 1);
                    #pragma unroll
                    for (int ks = 0; ks < 4; ks++) {
                        uint32_t (&ff)[4] = f[ks & 1];
                        ff[0] = ln_pair(r[0], m2[0], ri0, md.x, md.z); ff[1] = ln_pair(r[1], m2[1], ri1, md.x, md.z);
                        ff[2] = ln_pair(r[2], m2[0], ri0, md.y, md.w); ff[3] = ln_pair(r[3], m2[1], ri1, md.y, md.w);
                        const int kn = (ks + 1) & 3;
                        ldsm4(r[0], r[1], r[2], r[3], sb + OFF_RING + (ks == 3 ? sn : s) * 65536u + (aoff ^ (kn << 5)));
                        md = lds128(sb + OFF_MODS + ((ks == 3 ? j + 1 : j) * 4 + kn) * 64 + c * 16);
                        wg_fence();
                        wgmma_n256_rs<1>(accKV, ff[0], ff[1], ff[2], ff[3], desc_add(db, 16384 + ks * 2048), ks ? 1 : j);
                        wgmma_n128_rs<1>(accQ, ff[0], ff[1], ff[2], ff[3], desc_add(db, ks * 2048), ks ? 1 : j);
                        wg_commit();
                        if (ks == 3) arrive_if(BAR(B_TURN), j == 15 && !wgi);
                        if (ks == 1) mbar_wait(modb, 0);
                        if (ks == 2) mbar_wait(BAR(j < 15 ? B_F1 + sn : B_WPHI), j < 15 ? par : 0);
                        wg_wait<1>();
                        if (ks == 0) arrive_if(BAR(B_E1 + sp), j);
                    }
                    sp = s; s = sn;
                }
            }
            mbar_wait(BAR(B_E1 + 2), 0);
            wg_wait<0>();
            acc_fence(accKV); acc_fence(accQ);
            arrive_one(BAR(B_E1));
            uint32_t kf[32];
            #pragma unroll
            for (int h = 0; h < 4; h++) {
                if (h == 1) {
                    #pragma unroll
                    for (int i = 0; i < 16; i++) kf[i] = pack2(accKV[2 * i], accKV[2 * i + 1]);
                    phi_issue(pp, kf, sb, 0);
                }
                #pragma unroll
                for (int q = 0; q < 2; q++) {
                    const int o = 64 + 16 * h + 8 * q;
                    stsm4(sb + OFF_V + h * 8192u + srow * 64u + (((2 * q + (lane >> 4)) ^ ((srow >> 1) & 3)) << 4),
                          pack2(accKV[o], accKV[o + 1]), pack2(accKV[o + 2], accKV[o + 3]), pack2(accKV[o + 4], accKV[o + 5]), pack2(accKV[o + 6], accKV[o + 7]));
                }
            }
            #pragma unroll
            for (int i = 16; i < 32; i++) kf[i] = pack2(accKV[2 * i], accKV[2 * i + 1]);
            phi_transpose(pp, pt, sb + OFF_PHI0 + aoff, sb + OFF_PHI0 + (roff ^ ((lane >> 4) << 6)));
            phi_issue(pp, kf + 16, sb, 1);
            #pragma unroll
            for (int i = 0; i < 32; i++) qf[i] = pack2(accQ[2 * i], accQ[2 * i + 1]);
        }
        reg_dec<CREG>();
        {
            float cp, cn;
            fm_extrema(pt, cp, cn);
            #pragma unroll 1
            for (int u = 0; u < 4; u++) {
                const uint32_t cur = sb + ((u & 1) ? OFF_PHI1 : OFF_PHI0);
                float e[64], s[4];
                uint32_t pn[16];
                #pragma unroll
                for (int k = 0; k < 16; k++) {
                    if (k == KW) {
                        stsf(cur + aoff, e[31 + 2 * k]);
                        phi_transpose(pp, pn, cur + aoff, cur + (roff ^ ((lane >> 4) << 6)));
                    }
                    const float dep = k >= DEP ? e[33 + 2 * (k >= DEP ? k - DEP : 0)] : 0.f, f0 = bf_lo_after(pt[k], dep), f1 = bf_hi_after(pt[k], dep);
                    e[2 * k] = ex2(fmaf(f0, LOG2E, cp)); e[2 * k + 1] = ex2(fmaf(f1, LOG2E, cp));
                    e[32 + 2 * k] = ex2(fmaf(f0, -LOG2E, cn)); e[33 + 2 * k] = ex2(fmaf(f1, -LOG2E, cn));
                    if (k == 0) { s[0] = e[0]; s[1] = e[1]; s[2] = e[32]; s[3] = e[33]; }
                    else { s[0] += e[2 * k]; s[1] += e[2 * k + 1]; s[2] += e[32 + 2 * k]; s[3] += e[33 + 2 * k]; }
                }
                fm_extrema(pn, cp, cn);
                #pragma unroll
                for (int i = 0; i < 16; i++) pt[i] = pn[i];
                const float sp = s[0] + s[1], sn = s[2] + s[3], r = rcp(sp * sn), rp = r * sn, rn = r * sp;
                #pragma unroll
                for (int i = 0; i < 8; i++) {
                    const float q = i < 4 ? rp : rn;
                    sts128((cur + (lane >> 4) * 16384u + roff) ^ (i << 4), make_uint4(pack2(e[8 * i] * q, e[8 * i + 1] * q), pack2(e[8 * i + 2] * q, e[8 * i + 3] * q),
                                                                                   pack2(e[8 * i + 4] * q, e[8 * i + 5] * q), pack2(e[8 * i + 6] * q, e[8 * i + 7] * q)));
                }
                __syncwarp();
                arrive_one(BAR(B_PHI + u));
                if (u == 0) { mbar_wait(BAR(B_E1 + 1), 0); phi_issue(pp, qf, sb, 0); }
                else {
                    mbar_wait(BAR(B_KVD + (u != 1)), 0);
                    if (u == 1) phi_issue(pp, qf + 16, sb, 1);
                }
            }
            wg_wait<0>();
        }
        uint32_t x2[16][2], wf[32][4];
        const uint32_t woff = ((lane >> 3) & 1) * 16384u + ((lane & 7) + ((lane >> 4) << 3)) * 128u + (((warp ^ lane) & 7) << 4);
        mbar_wait(BAR(B_S0), 0);
        #pragma unroll
        for (int q = 0; q < 8; q++) {
            ldsm4(x2[2 * q][0], x2[2 * q][1], x2[2 * q + 1][0], x2[2 * q + 1][1], sb + OFF_XT + (q >> 2) * 16384u + (aoff ^ ((q & 3) << 5)));
            ldsm4t(wf[q][0], wf[q][1], wf[q][2], wf[q][3], sb + OFF_GA + q * 2048u + woff);
        }
        __syncwarp();
        arrive_one(BAR(B_S0FREE));
        float acc[64];
        const uint64_t da0 = mk_desc(sb + OFF_DA + wgi * 8192u, 16, 1024, 1), db0 = mk_desc(sb + OFF_DB, 8192, 1024, 1);
        #pragma unroll 1
        for (int pp = 0; pp < 2; pp++) {
            float o0[20], o1[20];
            const uint64_t dk = mk_desc(sb + OFF_SP + pp * 8192u, OFF_Z - OFF_SP - pp * 8160u, 512, 2);
            const uint64_t dq = mk_desc(sb + (pp ? OFF_PHI1 : OFF_PHI0) + wgi * 8192u, 16, 1024, 1);
            mbar_wait(BAR(B_FB + 4 + pp), 0);
            mbar_wait(BAR(B_PHI + 2 + pp), 0);
            mbar_wait(BAR(B_KVF + pp), 0);
            fence_async_smem();
            wg_fence();
            #pragma unroll
            for (int ks = 0; ks < 4; ks++) {
                wgmma_n40_ss<0, 1>(o0, desc_add(dq, ks * 32), desc_add(dk, ks * 1024), ks);
                wgmma_n40_ss<0, 1>(o1, desc_add(dq, 16384 + ks * 32), desc_raw(dk, 256 + ks * 64 - (255 << 16)), ks);
            }
            wg_commit();
            wg_wait<0>();
            acc_fence(o0); acc_fence(o1);
            arrive_if(BAR(B_ED), pp);
            uint32_t op[16];
            #pragma unroll
            for (int hh = 0; hh < 2; hh++) {
                const float (&o)[20] = hh ? o1 : o0;
                const Recip rd0 = split_recip(rcp(rbf(rbf(o[16]) + 1e-6f)));
                const Recip rd1 = split_recip(rcp(rbf(rbf(o[18]) + 1e-6f)));
                #pragma unroll
                for (int j = 0; j < 4; j++) { op[8 * hh + 2 * j] = hdiv2(pack2(o[4 * j], o[4 * j + 1]), rd0); op[8 * hh + 2 * j + 1] = hdiv2(pack2(o[4 * j + 2], o[4 * j + 3]), rd1); }
                #pragma unroll
                for (int q = 2 * hh; q < 2 * hh + 2; q++) stsm4(sb + OFF_OWN + pp * 16384u + (aoff ^ (q << 5)), op[4 * q], op[4 * q + 1], op[4 * q + 2], op[4 * q + 3]);
            }
            __syncwarp();
            arrive_one(BAR(B_OWN + pp));
            wg_fence();
            #pragma unroll
            for (int ks = 0; ks < 4; ks++) wgmma_n128_rs<1>(acc, op[4 * ks], op[4 * ks + 1], op[4 * ks + 2], op[4 * ks + 3], desc_add(db0, (4 + pp) * 16384u + ks * 2048), ks ? 1 : pp);
            wg_commit();
        }
        const uint32_t ooff = sb + OFF_OUT + (srow >> 3) * 1024u + aoff;
        {
            const uint32_t vchk = lane * 32u + g * 4u;
            #pragma unroll 1
            for (int n = 2; n < 16; n++) {
                const uint32_t s = (SLOT_A >> (4 * n)) & 7, sB = (SLOT_B >> (4 * n)) & 7;
                mbar_wait(BAR(B_FB + sB), (PAR_B >> n) & 1);
                mbar_wait(BAR(B_FA + s), (PAR_A >> n) & 1);
                {
                    const uint32_t ra = sb + OFF_DA + s * 16384u + warp * 2048u;
                    if (__any_sync(0xffffffffu, max(lds32(ra + vchk), lds32(ra + vchk + 1024)) == EMPTY)) {
                        #pragma unroll 1
                        for (int i = 0; i < 4; i++) {
                            uint4 v;
                            #pragma unroll 1
                            for (int it = 0; it < POLL_MAX; it++) {
                                v = ld_ll(p.s->os + (rb * 16 + d_block(hg, n)) * 1024 + warp * 128 + i * 32 + lane);
                                if (umax4(v) != EMPTY) break;
                            }
                            sts128(ra + i * 512 + lane * 16, v);
                        }
                        fence_async_smem();
                        __syncwarp();
                    }
                }
                const uint64_t da = desc_add(da0, s * 16384u), db = desc_add(db0, sB * 16384u);
                wg_fence();
                #pragma unroll
                for (int ks = 0; ks < 4; ks++) wgmma_n128_ss<0, 1>(acc, desc_add(da, ks * 32), desc_add(db, ks * 2048), 1);
                wg_commit();
                wg_wait<1>();
                arrive_one(BAR(B_ED - 1 + n));
            }
            mbar_wait(BAR(B_PAR), 0);
            uint32_t gar[16], bfr[16];
            #pragma unroll
            for (int j = 0; j < 16; j += 4) {
                ldsm4(gar[j], gar[j + 1], gar[j + 2], gar[j + 3], sb + OFF_PAR + 768 + (j + (lane >> 3)) * 16);
                ldsm4(bfr[j], bfr[j + 1], bfr[j + 2], bfr[j + 3], sb + OFF_BQ + ((lane & 1) ? (j + (lane >> 3)) * 16 : 272));
            }
            wg_wait<0>();
            acc_fence(acc);
            bar_arrive(6 + wgi, 256);
            float sd[2][4], q1[2][4], q2[2][4];
            #pragma unroll
            for (int e = 0; e < 4; e++) { sd[0][e] = sd[1][e] = q1[0][e] = q1[1][e] = q2[0][e] = q2[1][e] = 0.f; }
            #pragma unroll
            for (int s = 0; s < 8; s++) {
                #pragma unroll
                for (int e = 0; e < 4; e++) { const int j = 2 * s + (e >> 1), h = e & 1; x2[j][h] = hadd2(x2[j][h], hmul2(gar[j], pack2(acc[4 * j + 2 * h], acc[4 * j + 2 * h + 1]))); }
                mma16816(sd[s & 1], x2[2 * s][0], x2[2 * s][1], x2[2 * s + 1][0], x2[2 * s + 1][1], bfr[2 * s], bfr[2 * s + 1]);
                #pragma unroll
                for (int e = 0; e < 2; e++) { mma1688(q1[e], x2[2 * s + e][0], x2[2 * s + e][1], x2[2 * s + e][0]); mma1688(q2[e], x2[2 * s + e][0], x2[2 * s + e][1], x2[2 * s + e][1]); }
            }
            if (c == (g >> 1)) {
                uint4* d = p.s->st2 + rb * 128 + warp * 16 + g;
                red_add4(d, sd[0][0] + sd[1][0], (g & 1) ? q1[0][1] + q1[1][1] : q1[0][0] + q1[1][0], sd[0][1] + sd[1][1], 1.0f);
                red_add4(d + 8, sd[0][2] + sd[1][2], (g & 1) ? q2[0][3] + q2[1][3] : q2[0][2] + q2[1][2], sd[0][3] + sd[1][3], 1.0f);
            }
            arrive_one(BAR(B_RED));
            bar_sync(7 - wgi, 256);
            #pragma unroll
            for (int q = 0; q < 8; q++) stsm4((ooff + (q >> 2) * 1024u) ^ ((q & 3) << 5), x2[2 * q][0], x2[2 * q][1], x2[2 * q + 1][0], x2[2 * q + 1][1]);
            __syncwarp();
            arrive_one(BAR(B_X2));
        }
        const uint32_t xa = sb + OFF_OUT + warp * 4096u + ((lane >> 3) & 1) * 1024u + (lane >> 4) * 128u + (((lane ^ (lane >> 4)) & 7) << 4);
        const uint4 pa = lds128(sb + OFF_PAR + (lane & 15) * 16), ps = lds128(sb + OFF_PAR + 256 + (lane & 15) * 16), pg = lds128(sb + OFF_PAR + 512 + (lane & 15) * 16);
        if (ffn) mbar_wait(BAR(B_GU), 0);
        #pragma unroll
        for (int q = 8; q < 32; q++) ldsm4t(wf[q][0], wf[q][1], wf[q][2], wf[q][3], sb + (q < 16 ? OFF_GB : q < 24 ? OFF_UP0 : OFF_UP1) + (q & 7) * 2048u + woff);
        {
            mbar_wait(BAR(B_ST2), 0);
            #pragma unroll 1
            for (int q0 = 0; q0 < 2; q0++) {
                uint4 x[4]; uint2 st[4];
                const uint32_t a = xa + q0 * 2048u;
                #pragma unroll
                for (int q = 0; q < 4; q++) { x[q] = lds128((a + q * 256u) ^ (q << 5)); st[q] = lds64(sb + OFF_ST2 + (warp * 16 + q0 * 8 + q * 2 + (lane >> 4)) * 8); }
                #pragma unroll
                for (int q = 0; q < 4; q++) {
                    const Recip r = split_recip(__uint_as_float(st[q].y));
                    sts128((a + q * 256u) ^ (q << 5), make_uint4(
                        hadd2(x[q].x, hmul2(pg.x, ln_pair(x[q].x, st[q].x, r, pa.x, ps.x))), hadd2(x[q].y, hmul2(pg.y, ln_pair(x[q].y, st[q].x, r, pa.y, ps.y))),
                        hadd2(x[q].z, hmul2(pg.z, ln_pair(x[q].z, st[q].x, r, pa.z, ps.z))), hadd2(x[q].w, hmul2(pg.w, ln_pair(x[q].w, st[q].x, r, pa.w, ps.w)))));
                }
            }
            __syncwarp();
            arrive_one(BAR(B_OUTW));
        }
        if (ffn) {
            float acc[4][4];
            uint32_t df[4][4][4];
            {
                #pragma unroll
                for (int i = 0; i < 4; i++) { acc[i][0] = acc[i][1] = acc[i][2] = acc[i][3] = 0.f; }
                const uint32_t da = sb + (wgi ? OFF_DN1 : OFF_DN0) + w4 * 8192u + ((lane & 7) + ((lane >> 4) << 3)) * 128u;
                mbar_wait(BAR(B_WD), 0);
                #pragma unroll
                for (int q = 0; q < DNE; q++)
                    ldsm4t(df[q >> 2][q & 3][0], df[q >> 2][q & 3][1], df[q >> 2][q & 3][2], df[q >> 2][q & 3][3], da + (q & 3) * 2048u + (((2 * (q >> 2) + ((lane >> 3) & 1)) ^ (lane & 7)) << 4));
                mbar_wait(BAR(B_ROWS), 0);
                #pragma unroll
                for (int q = 0; q < 8; q++) {
                    uint32_t b0, b1, b2, b3;
                    ldsm4(b0, b1, b2, b3, sb + OFF_ROWS + (lane & 7) * 528u + (lane >> 3) * 16u + q * 64u);
                    #pragma unroll
                    for (int hf = 0; hf < 2; hf++) {
                        const int k = 16 * hf + 2 * q;
                        mma16816(acc[2 * hf], wf[k][0], wf[k][1], wf[k][2], wf[k][3], b0, b1);
                        mma16816(acc[2 * hf + 1], wf[k + 1][0], wf[k + 1][1], wf[k + 1][2], wf[k + 1][3], b2, b3);
                    }
                }
                const float gs = (acc[0][0] + acc[1][0]) + (acc[2][1] + acc[3][1]), us = (acc[0][2] + acc[1][2]) + (acc[2][3] + acc[3][3]);
                st_partner64(sb + OFF_PX + warp * 256 + lane * 8, BAR(B_PX), rank ^ 1, gs, us);
                #pragma unroll
                for (int q = DNE; q < 16; q++)
                    ldsm4t(df[q >> 2][q & 3][0], df[q >> 2][q & 3][1], df[q >> 2][q & 3][2], df[q >> 2][q & 3][3], da + (q & 3) * 2048u + (((2 * (q >> 2) + ((lane >> 3) & 1)) ^ (lane & 7)) << 4));
                mbar_wait(BAR(B_SEL), 0);
                const uint32_t tok = lds32(sb + OFF_SEL + 48 + c * 4);
                mbar_wait(BAR(B_PX), 0);
                const uint2 q = lds64(sb + OFF_PX + warp * 256 + lane * 8);
                float gt = rbf(gs + __uint_as_float(q.x));
                gt = rbf(gt * sigmoidf(gt));
                if (tok < 2) sts16(sb + OFF_HID + tok * 144 + (warp * 8 + g) * 2, pack2(gt * rbf(us + __uint_as_float(q.y)), 0.f));
            }
            bar_sync(1, 256);
            uint32_t bh[8];
            ldsm4(bh[0], bh[1], bh[2], bh[3], sb + OFF_HID + (lane & 1) * 144u + (lane >> 3) * 16u);
            ldsm4(bh[4], bh[5], bh[6], bh[7], sb + OFF_HID + (lane & 1) * 144u + (lane >> 3) * 16u + 64u);
            float y[4][4];
            #pragma unroll
            for (int tt = 0; tt < 4; tt++) { y[tt][0] = y[tt][1] = y[tt][2] = y[tt][3] = 0.f; }
            #pragma unroll
            for (int ks = 0; ks < 4; ks++)
                #pragma unroll
                for (int tt = 0; tt < 4; tt++) mma16816(y[tt], df[tt][ks][0], df[tt][ks][1], df[tt][ks][2], df[tt][ks][3], bh[2 * ks], bh[2 * ks + 1]);
            float e[4];
            #pragma unroll
            for (int i = 0; i < 4; i++) e[i] = (c & 2) ? ((c & 1) ? y[3][i] : y[2][i]) : ((c & 1) ? y[1][i] : y[0][i]);
            char* d = (char*)(p.s->yp + pr * 512 + rank * 128 + (warp * 4 + c) * 4) + g * 8;
            st_ll8(d, __float_as_uint(e[0]), low_bits(e[2], tag2));
            st_ll8(d + 4096, __float_as_uint(e[1]), low_bits(e[3], tag2));
            arrive_one(BAR(B_YP));
        }
    }
}

typedef CUresult (*EncodeFn)(CUtensorMap*, CUtensorMapDataType, cuuint32_t, void*, const cuuint64_t*, const cuuint64_t*, const cuuint32_t*,
                             const cuuint32_t*, CUtensorMapInterleave, CUtensorMapSwizzle, CUtensorMapL2promotion, CUtensorMapFloatOOBfill);

CUtensorMap make_map(EncodeFn enc, const void* ptr, uint64_t cols, uint64_t rows, uint32_t bc, uint32_t br, CUtensorMapSwizzle swz, CUtensorMapL2promotion promo) {
    CUtensorMap m;
    cuuint64_t dims[2] = {cols, rows}, strides[1] = {cols * 2};
    cuuint32_t box[2] = {bc, br}, es[2] = {1, 1};
    enc(&m, CU_TENSOR_MAP_DATA_TYPE_BFLOAT16, 2, const_cast<void*>(ptr), dims, strides, box, es, CU_TENSOR_MAP_INTERLEAVE_NONE, swz, promo,
        CU_TENSOR_MAP_FLOAT_OOB_FILL_NONE);
    return m;
}
CUtensorMap make_block_map(EncodeFn enc, const void* ptr, uint32_t sections, uint64_t rows, uint32_t br, CUtensorMapL2promotion promo) {
    CUtensorMap m;
    cuuint64_t dims[4] = {64, rows, 16, sections}, strides[3] = {sections * 2048ull, 128, 2048};
    cuuint32_t box[4] = {64, br, 2, sections}, es[4] = {1, 1, 1, 1};
    enc(&m, CU_TENSOR_MAP_DATA_TYPE_BFLOAT16, sections > 1 ? 4 : 3, const_cast<void*>(ptr), dims, strides, box, es, CU_TENSOR_MAP_INTERLEAVE_NONE,
        CU_TENSOR_MAP_SWIZZLE_128B, promo, CU_TENSOR_MAP_FLOAT_OOB_FILL_NONE);
    return m;
}

}

extern "C" void kernel_launch(void* const* d_in, const int* in_sizes, int n_in, void* d_out, int out_size) {
    (void)in_sizes; (void)n_in; (void)out_size;
    void* fn = nullptr; cudaDriverEntryPointQueryResult qr;
    cudaGetDriverEntryPoint("cuTensorMapEncodeTiled", &fn, cudaEnableDefault, &qr);
    EncodeFn enc = (EncodeFn)fn;
    void* hs = nullptr;
    cudaGetSymbolAddress(&hs, g_scratch);
    const CUtensorMapL2promotion P256 = CU_TENSOR_MAP_L2_PROMOTION_L2_256B, P128 = CU_TENSOR_MAP_L2_PROMOTION_L2_128B;
    CUtensorMap tmW = make_block_map(enc, d_in[1], 3, 1024, 64, P256);
    CUtensorMap tmWo = make_block_map(enc, d_in[3], 1, 1024, 64, P256);
    CUtensorMap tmPhi = make_map(enc, d_in[2], 32, 1024, 32, 128, CU_TENSOR_MAP_SWIZZLE_64B, P128);
    CUtensorMap tmG = make_map(enc, d_in[6], 3584, 1024, 64, 128, CU_TENSOR_MAP_SWIZZLE_128B, P128);
    CUtensorMap tmU = make_map(enc, d_in[7], 3584, 1024, 64, 128, CU_TENSOR_MAP_SWIZZLE_128B, P128);
    CUtensorMap tmD = make_block_map(enc, d_in[8], 1, 3584, 64, P128);
    CUtensorMap tmX = make_map(enc, d_in[0], 1024, 2048, 64, 128, CU_TENSOR_MAP_SWIZZLE_128B, P128);
    CUtensorMap tmO = make_block_map(enc, d_out, 1, 2048, 8, P128);
    CUtensorMap tmM = make_map(enc, d_in[10], 6144, 1024, 64, 64, CU_TENSOR_MAP_SWIZZLE_128B, P128);
    CUtensorMap tmR = make_map(enc, d_in[10], 6144, 1024, 32, 64, CU_TENSOR_MAP_SWIZZLE_NONE, P128);
    CUtensorMap tmG8 = make_map(enc, d_in[6], 3584, 1024, 8, PRG, CU_TENSOR_MAP_SWIZZLE_NONE, P128);
    CUtensorMap tmU8 = make_map(enc, d_in[7], 3584, 1024, 8, PRG, CU_TENSOR_MAP_SWIZZLE_NONE, P128);
    CUtensorMap tmD8;
    {
        cuuint64_t dims[3] = {64, 16, 3584}, strides[2] = {128, 2048};
        cuuint32_t box[3] = {8, 8, PRD}, es[3] = {1, 1, 1};
        enc(&tmD8, CU_TENSOR_MAP_DATA_TYPE_BFLOAT16, 3, d_in[8], dims, strides, box, es, CU_TENSOR_MAP_INTERLEAVE_NONE, CU_TENSOR_MAP_SWIZZLE_NONE, P128,
            CU_TENSOR_MAP_FLOAT_OOB_FILL_NONE);
    }
    Ptrs p;
    p.x = (const bf16*)d_in[0]; p.c = (const bf16*)d_in[9]; p.wmod = (const bf16*)d_in[10]; p.wr = (const bf16*)d_in[5];
    p.out = (bf16*)d_out; p.s = (Scratch*)hs;
    p.wqkv = (const bf16*)d_in[1]; p.wo = (const bf16*)d_in[3];
    cudaFuncSetAttribute(fused_kernel, cudaFuncAttributeMaxDynamicSharedMemorySize, SMEM_BYTES);
    fused_kernel<<<128, NTHREADS, SMEM_BYTES, cudaStreamPerThread>>>(p, tmW, tmWo, tmPhi, tmG, tmU, tmD, tmX, tmO, tmM, tmR, tmG8, tmU8, tmD8);
}
```

```cpp
#include <cuda_runtime.h>
#include <cuda.h>
#include <cuda_bf16.h>
#include <stdint.h>

namespace {

typedef __nv_bfloat16 bf16;

constexpr int NTHREADS = 384;
constexpr int POLL_MAX = 400000;
constexpr uint32_t EMPTY = 0xffffffffu;

constexpr int PND = 6;
constexpr int PNG = 5;
constexpr int PRD = (64 + PND - 1) / PND, PRG = (384 + PNG - 1) / PNG;
constexpr uint32_t OFF_RING = 0;
constexpr uint32_t OFF_XS   = 65536;
constexpr uint32_t OFF_WST  = 98304;
constexpr uint32_t OFF_XT   = 0;
constexpr uint32_t OFF_GA   = 32768;
constexpr uint32_t OFF_PHI0 = 163840, OFF_PHI1 = 98304;
constexpr uint32_t OFF_V    = 131072;
constexpr uint32_t OFF_KVS  = 131072;
constexpr uint32_t OFF_DB   = 0;
constexpr uint32_t OFF_DA   = 98304;
constexpr uint64_t SLOT_A   = 0x5432105432105432ull, SLOT_B = 0x1054321054321054ull;
constexpr uint32_t PAR_A    = 0x3f00, PAR_B = 0x0fc0;
constexpr uint32_t OFF_OWN  = OFF_DA + 32768;
constexpr uint32_t OFF_OUT  = OFF_DA + 65536;
constexpr uint32_t OFF_UP0  = OFF_DA, OFF_UP1 = OFF_DB + 32768, OFF_DN0 = OFF_DA + 32768, OFF_DN1 = OFF_DB + 65536;
constexpr uint32_t OFF_WPHI = 196608;
constexpr uint32_t OFF_SP   = 204800;
constexpr uint32_t OFF_Z    = 221184;
constexpr uint32_t OFF_ONES = 225280;
constexpr uint32_t OFF_MODS = 226304;
constexpr uint32_t OFF_GB   = 196608;
constexpr uint32_t OFF_BQ   = 229376;
constexpr uint32_t OFF_ATOT = OFF_BQ + 256;
constexpr uint32_t OFF_BAR  = 230400;
constexpr uint32_t OFF_SEEN = OFF_BAR + 632;
constexpr uint32_t OFF_PAR  = OFF_BAR + 640;
constexpr uint32_t SMEM_BYTES = 232448;
constexpr uint32_t OFF_SILU = OFF_Z;
constexpr uint32_t OFF_RED0 = OFF_Z + 2048;
constexpr uint32_t OFF_DUMMY = OFF_RED0 + 512;
constexpr uint32_t OFF_ST2  = OFF_DB;
constexpr uint32_t OFF_SEL  = OFF_ST2 + 1024;
constexpr uint32_t OFF_ROWS = OFF_ST2 + 2048;
constexpr uint32_t OFF_PX   = OFF_ROWS + 4608;
constexpr uint32_t OFF_HID  = OFF_PX + 2048;

enum {
    B_F1 = 0, B_E1 = 3, B_STFREE = 6, B_WPHI = 7, B_FA = 8, B_FB = 14, B_RF = 20, B_KVD = 24, B_PAR = 26, B_S0 = 27, B_GU = 28, B_WD = 29,
    B_X2 = 30, B_ST2 = 31, B_CAND = 32, B_TURN = 33,
    B_MP = 34, B_MOD = 35, B_PX = 51, B_S0FREE = 52, B_PHI = 53, B_OUTW = 57, B_PUB = 58, B_KVF = 59, B_OWN = 61, B_REL = 63, B_ROWS = 64,
    B_SEL = 65, B_YP = 66, B_RED = 67,
    B_XS = 68,
    B_WS = 72, B_COUNT = 76,
    B_ED = B_MOD, B_PF = B_XS + 3, B_KVS = B_RF
};

struct Scratch {
    uint4 os[256 * 1024];
    uint4 kvp[32 * 256 * 32];
    uint4 kvf[32 * 288];
    uint4 st1[2048];
    uint4 mp[128 * 16];
    uint4 rest[1024];
    uint4 flo[256 * 2];
    uint4 st2[2048];
    uint4 cand[64 * 2];
    uint4 rowh[128 * 128];
    uint4 rowx[128 * 128];
    uint4 rsc[64 * 8 * 2];
    uint4 yp[56 * 512];
    unsigned done[4];
};
__device__ __align__(1024) Scratch g_scratch;

__device__ __forceinline__ uint32_t smem_u32(const void* p) { return (uint32_t)__cvta_generic_to_shared(p); }
__device__ __forceinline__ int lane_id() { int l; asm volatile("mov.u32 %0, %%laneid;" : "=r"(l)); return l; }
__device__ __forceinline__ uint32_t clk32() { uint32_t c; asm volatile("mov.u32 %0, %%clock;" : "=r"(c) :: "memory"); return c; }
__device__ __forceinline__ void arrive_one(uint32_t bar) {
    asm volatile("{\n.reg .pred p;\nelect.sync _|p, 0xffffffff;\n@p mbarrier.arrive.shared::cta.b64 _, [%0];\n}" :: "r"(bar) : "memory");
}
__device__ __forceinline__ void arrive_many(uint32_t bar, uint32_t n) {
    asm volatile("{\n.reg .pred p;\nelect.sync _|p, 0xffffffff;\n@p mbarrier.arrive.shared::cta.b64 _, [%0], %1;\n}" :: "r"(bar), "r"(n) : "memory");
}
__device__ __forceinline__ void arrive_if(uint32_t bar, uint32_t on) {
    asm volatile("{\n.reg .pred q, p;\nelect.sync _|q, 0xffffffff;\nsetp.ne.and.u32 p, %1, 0, q;\n@p mbarrier.arrive.shared::cta.b64 _, [%0];\n}" :: "r"(bar), "r"(on) : "memory");
}
__device__ __forceinline__ void st_partner64(uint32_t a, uint32_t bar, uint32_t cta, float x, float y) {
    asm volatile("{\n.reg .b32 ra, rb;\nmapa.shared::cluster.u32 ra, %0, %2;\nmapa.shared::cluster.u32 rb, %1, %2;\n"
        "st.async.weak.shared::cluster.mbarrier::complete_tx::bytes.v2.f32 [ra], {%3, %4}, [rb];\n}" :: "r"(a), "r"(bar), "r"(cta), "f"(x), "f"(y) : "memory");
}
__device__ __forceinline__ void mbar_wait(uint32_t bar, uint32_t parity) {
    asm volatile("{\n.reg .pred P1;\n.reg .u32 cnt;\nmbarrier.try_wait.parity.shared::cta.b64 P1, [%0], %1;\n@P1 bra DONE;\nmov.u32 cnt, 0;\nLAB_WAIT:\n"
        "mbarrier.try_wait.parity.shared::cta.b64 P1, [%0], %1;\n@P1 bra DONE;\n"
        "add.u32 cnt, cnt, 1;\nsetp.lt.u32 P1, cnt, 1000000;\n@P1 bra LAB_WAIT;\ntrap;\nDONE:\n}" :: "r"(bar), "r"(parity) : "memory");
}
__device__ __forceinline__ uint64_t policy_evict_first() { uint64_t p; asm("createpolicy.fractional.L2::evict_first.b64 %0, 1.0;" : "=l"(p)); return p; }
__device__ __forceinline__ void bulk_commit() { asm volatile("cp.async.bulk.commit_group;" ::: "memory"); }
__device__ __forceinline__ void bulk_wait() { asm volatile("cp.async.bulk.wait_group 0;" ::: "memory"); }
__device__ __forceinline__ void tmap_prefetch(const CUtensorMap* tm) { asm volatile("prefetch.tensormap [%0];" :: "l"(tm) : "memory"); }
#define EL "{\n.reg .pred e;\nelect.sync _|e, 0xffffffff;\n@e "
__device__ __forceinline__ void expect_tx_e(uint32_t bar, uint32_t bytes) { asm volatile(EL "mbarrier.arrive.expect_tx.shared::cta.b64 _, [%0], %1;\n}" :: "r"(bar), "r"(bytes) : "memory"); }
__device__ __forceinline__ void tma2_e(uint32_t dst, const CUtensorMap* tm, int c0, int c1, uint32_t bar) {
    asm volatile(EL "cp.async.bulk.tensor.2d.shared::cluster.global.mbarrier::complete_tx::bytes [%0], [%1, {%3, %4}], [%2];\n}"
        :: "r"(dst), "l"(tm), "r"(bar), "r"(c0), "r"(c1) : "memory");
}
__device__ __forceinline__ void tma2_ef_e(uint32_t dst, const CUtensorMap* tm, int c0, int c1, uint32_t bar) {
    asm volatile(EL "cp.async.bulk.tensor.2d.shared::cluster.global.mbarrier::complete_tx::bytes.L2::cache_hint [%0], [%1, {%3, %4}], [%2], %5;\n}"
        :: "r"(dst), "l"(tm), "r"(bar), "r"(c0), "r"(c1), "l"(policy_evict_first()) : "memory");
}
__device__ __forceinline__ void tma3_e(uint32_t dst, const CUtensorMap* tm, int c1, int c2, uint32_t bar) {
    asm volatile(EL "cp.async.bulk.tensor.3d.shared::cluster.global.mbarrier::complete_tx::bytes [%0], [%1, {0, %3, %4}], [%2];\n}"
        :: "r"(dst), "l"(tm), "r"(bar), "r"(c1), "r"(c2) : "memory");
}
__device__ __forceinline__ void tma3_ef_e(uint32_t dst, const CUtensorMap* tm, int row, int blk, uint32_t bar) {
    asm volatile(EL "cp.async.bulk.tensor.3d.shared::cluster.global.mbarrier::complete_tx::bytes.L2::cache_hint [%0], [%1, {0, %3, %4}], [%2], %5;\n}"
        :: "r"(dst), "l"(tm), "r"(bar), "r"(row), "r"(blk), "l"(policy_evict_first()) : "memory");
}
__device__ __forceinline__ void tma4_ef_e(uint32_t dst, const CUtensorMap* tm, int row, int blk, uint32_t bar) {
    asm volatile(EL "cp.async.bulk.tensor.4d.shared::cluster.global.mbarrier::complete_tx::bytes.L2::cache_hint [%0], [%1, {0, %3, %4, 0}], [%2], %5;\n}"
        :: "r"(dst), "l"(tm), "r"(bar), "r"(row), "r"(blk), "l"(policy_evict_first()) : "memory");
}
__device__ __forceinline__ void bulk_load_e(uint32_t dst, const void* src, uint32_t bytes, uint32_t bar) {
    asm volatile(EL "cp.async.bulk.shared::cluster.global.mbarrier::complete_tx::bytes [%0], [%1], %2, [%3];\n}" :: "r"(dst), "l"(src), "r"(bytes), "r"(bar) : "memory");
}
__device__ __forceinline__ void bulk_store_e(void* dst, uint32_t src, uint32_t bytes) {
    asm volatile(EL "cp.async.bulk.global.shared::cta.bulk_group [%0], [%1], %2;\n}" :: "l"(dst), "r"(src), "r"(bytes) : "memory");
}
__device__ __forceinline__ void st_flag_e(void* p, unsigned v) { asm volatile(EL "st.relaxed.gpu.global.u32 [%0], %1;\n}" :: "l"(p), "r"(v) : "memory"); }
__device__ __forceinline__ void mbar_init(uint32_t bar, uint32_t cnt) { asm volatile("mbarrier.init.shared::cta.b64 [%0], %1;" :: "r"(bar), "r"(cnt) : "memory"); }
__device__ __forceinline__ bool elect_one() {
    uint32_t p;
    asm volatile("{\n.reg .pred P;\nelect.sync _|P, 0xffffffff;\nselp.u32 %0, 1, 0, P;\n}" : "=r"(p));
    return p;
}
__device__ __forceinline__ void wg_fence() { asm volatile("wgmma.fence.sync.aligned;" ::: "memory"); }
__device__ __forceinline__ void wg_commit() { asm volatile("wgmma.commit_group.sync.aligned;" ::: "memory"); }
template<int N> __device__ __forceinline__ void wg_wait() { asm volatile("wgmma.wait_group.sync.aligned %0;" :: "n"(N) : "memory"); }
template<int N> __device__ __forceinline__ void acc_fence(float (&d)[N]) {
    #pragma unroll
    for (int i = 0; i < N; i++) asm volatile("" : "+f"(d[i]) :: "memory");
}
__device__ __forceinline__ uint64_t mk_desc(uint32_t addr, uint32_t lbo, uint32_t sbo, uint32_t swz) {
    uint32_t lo = ((addr & 0x3FFFF) >> 4) | (((lbo & 0x3FFFF) >> 4) << 16);
    uint32_t hi = (sbo >> 4) | (swz << 30);
    return ((uint64_t)hi << 32) | lo;
}
__device__ __forceinline__ uint64_t desc_add(uint64_t d, uint32_t bytes) { return (d & 0xffffffff00000000ull) | (uint32_t)((uint32_t)d + (bytes >> 4)); }
__device__ __forceinline__ uint64_t desc_raw(uint64_t d, uint32_t inc) { return (d & 0xffffffff00000000ull) | (uint32_t)((uint32_t)d + inc); }
__device__ __forceinline__ void fence_async_smem() { asm volatile("fence.proxy.async.shared::cta;" ::: "memory"); }
__device__ __forceinline__ void bar_sync(int id, int n) { asm volatile("bar.sync %0, %1;" :: "r"(id), "r"(n) : "memory"); }
__device__ __forceinline__ void bar_arrive(int id, int n) { asm volatile("bar.arrive %0, %1;" :: "r"(id), "r"(n) : "memory"); }
template<int R> __device__ __forceinline__ void reg_inc() { asm volatile("setmaxnreg.inc.sync.aligned.u32 %0;" :: "n"(R)); }
template<int R> __device__ __forceinline__ void reg_dec() { asm volatile("setmaxnreg.dec.sync.aligned.u32 %0;" :: "n"(R)); }
__device__ __forceinline__ void cluster_arrive() { asm volatile("barrier.cluster.arrive.relaxed.aligned;" ::: "memory"); }
__device__ __forceinline__ void cluster_wait() { asm volatile("barrier.cluster.wait.acquire.aligned;" ::: "memory"); }

__device__ __forceinline__ void stsm4(uint32_t addr, uint32_t r0, uint32_t r1, uint32_t r2, uint32_t r3) {
    asm volatile("stmatrix.sync.aligned.m8n8.x4.shared.b16 [%0], {%1,%2,%3,%4};" :: "r"(addr), "r"(r0), "r"(r1), "r"(r2), "r"(r3) : "memory");
}
__device__ __forceinline__ void ldsm4(uint32_t& r0, uint32_t& r1, uint32_t& r2, uint32_t& r3, uint32_t addr) {
    asm volatile("ldmatrix.sync.aligned.m8n8.x4.shared.b16 {%0,%1,%2,%3}, [%4];" : "=r"(r0), "=r"(r1), "=r"(r2), "=r"(r3) : "r"(addr) : "memory");
}
__device__ __forceinline__ void ldsm4t(uint32_t& r0, uint32_t& r1, uint32_t& r2, uint32_t& r3, uint32_t addr) {
    asm volatile("ldmatrix.sync.aligned.m8n8.x4.trans.shared.b16 {%0,%1,%2,%3}, [%4];" : "=r"(r0), "=r"(r1), "=r"(r2), "=r"(r3) : "r"(addr) : "memory");
}
__device__ __forceinline__ void mma16816(float (&d)[4], uint32_t a0, uint32_t a1, uint32_t a2, uint32_t a3, uint32_t b0, uint32_t b1) {
    asm("mma.sync.aligned.m16n8k16.row.col.f32.bf16.bf16.f32 {%0,%1,%2,%3}, {%4,%5,%6,%7}, {%8,%9}, {%0,%1,%2,%3};"
        : "+f"(d[0]), "+f"(d[1]), "+f"(d[2]), "+f"(d[3]) : "r"(a0), "r"(a1), "r"(a2), "r"(a3), "r"(b0), "r"(b1));
}
__device__ __forceinline__ void mma1688(float (&d)[4], uint32_t a0, uint32_t a1, uint32_t b0) {
    asm("mma.sync.aligned.m16n8k8.row.col.f32.bf16.bf16.f32 {%0,%1,%2,%3}, {%4,%5}, {%6}, {%0,%1,%2,%3};"
        : "+f"(d[0]), "+f"(d[1]), "+f"(d[2]), "+f"(d[3]) : "r"(a0), "r"(a1), "r"(b0));
}
__device__ __forceinline__ uint4 lds128(uint32_t a) { uint4 v; asm volatile("ld.shared.v4.b32 {%0,%1,%2,%3}, [%4];" : "=r"(v.x), "=r"(v.y), "=r"(v.z), "=r"(v.w) : "r"(a) : "memory"); return v; }
__device__ __forceinline__ uint2 lds64(uint32_t a) { uint2 v; asm volatile("ld.shared.v2.b32 {%0,%1}, [%2];" : "=r"(v.x), "=r"(v.y) : "r"(a) : "memory"); return v; }
__device__ __forceinline__ uint32_t lds32(uint32_t a) { uint32_t v; asm volatile("ld.shared.b32 %0, [%1];" : "=r"(v) : "r"(a) : "memory"); return v; }
__device__ __forceinline__ float ldsf(uint32_t a) { float v; asm volatile("ld.shared.f32 %0, [%1];" : "=f"(v) : "r"(a) : "memory"); return v; }
__device__ __forceinline__ uint32_t lds16(uint32_t a) { uint16_t v; asm volatile("ld.shared.b16 %0, [%1];" : "=h"(v) : "r"(a) : "memory"); return v; }
__device__ __forceinline__ void sts128(uint32_t a, uint4 v) { asm volatile("st.shared.v4.b32 [%0], {%1,%2,%3,%4};" :: "r"(a), "r"(v.x), "r"(v.y), "r"(v.z), "r"(v.w) : "memory"); }
__device__ __forceinline__ void sts64(uint32_t a, uint32_t x, uint32_t y) { asm volatile("st.shared.v2.b32 [%0], {%1,%2};" :: "r"(a), "r"(x), "r"(y) : "memory"); }
__device__ __forceinline__ void sts32(uint32_t a, uint32_t x) { asm volatile("st.shared.b32 [%0], %1;" :: "r"(a), "r"(x) : "memory"); }
__device__ __forceinline__ void stsf(uint32_t a, float x) { asm volatile("st.shared.f32 [%0], %1;" :: "r"(a), "f"(x) : "memory"); }
__device__ __forceinline__ void sts16(uint32_t a, uint32_t x) { asm volatile("st.shared.b16 [%0], %1;" :: "r"(a), "h"((uint16_t)x) : "memory"); }

__device__ __forceinline__ uint4 ldg128(const void* p) { uint4 v; asm volatile("ld.global.nc.v4.b32 {%0,%1,%2,%3}, [%4];" : "=r"(v.x), "=r"(v.y), "=r"(v.z), "=r"(v.w) : "l"(p)); return v; }
__device__ __forceinline__ uint2 ldg64(const void* p) { uint2 v; asm volatile("ld.global.nc.v2.b32 {%0,%1}, [%2];" : "=r"(v.x), "=r"(v.y) : "l"(p)); return v; }
__device__ __forceinline__ void stg128(void* p, uint4 v) { asm volatile("st.global.v4.b32 [%0], {%1,%2,%3,%4};" :: "l"(p), "r"(v.x), "r"(v.y), "r"(v.z), "r"(v.w) : "memory"); }
__device__ __forceinline__ void stg_fill(void* p, uint32_t v) { asm volatile("st.global.v4.b32 [%0], {%1,%1,%1,%1};" :: "l"(p), "r"(v) : "memory"); }
__device__ __forceinline__ void st_ll(void* p, uint32_t x, uint32_t y, uint32_t z, uint32_t w) {
    asm volatile("{\n.reg .b128 t;\n.reg .b64 a, b;\nmov.b64 a, {%1, %2};\nmov.b64 b, {%3, %4};\nmov.b128 t, {a, b};\nst.relaxed.gpu.global.b128 [%0], t;\n}"
        :: "l"(p), "r"(x), "r"(y), "r"(z), "r"(w) : "memory");
}
__device__ __forceinline__ uint4 ld_ll(const void* p) {
    uint4 v;
    asm volatile("{\n.reg .b128 t;\n.reg .b64 a, b;\nld.relaxed.gpu.global.b128 t, [%4];\nmov.b128 {a, b}, t;\nmov.b64 {%0, %1}, a;\nmov.b64 {%2, %3}, b;\n}"
        : "=r"(v.x), "=r"(v.y), "=r"(v.z), "=r"(v.w) : "l"(p) : "memory");
    return v;
}
__device__ __forceinline__ void ld_ll_if(uint4& v, const void* p, bool go) {
    asm volatile("{\n.reg .b128 t;\n.reg .b64 a, b;\n.reg .pred q;\nsetp.ne.u32 q, %5, 0;\nmov.b64 a, {%0, %1};\nmov.b64 b, {%2, %3};\nmov.b128 t, {a, b};\n"
        "@q ld.relaxed.gpu.global.b128 t, [%4];\nmov.b128 {a, b}, t;\nmov.b64 {%0, %1}, a;\nmov.b64 {%2, %3}, b;\n}"
        : "+r"(v.x), "+r"(v.y), "+r"(v.z), "+r"(v.w) : "l"(p), "r"((uint32_t)go) : "memory");
}
__device__ __forceinline__ void st_ll8(void* p, uint32_t x, uint32_t y) {
    asm volatile("{\n.reg .b64 a;\nmov.b64 a, {%1, %2};\nst.relaxed.gpu.global.b64 [%0], a;\n}" :: "l"(p), "r"(x), "r"(y) : "memory");
}
__device__ __forceinline__ void st_ll4(void* p, uint32_t x) { asm volatile("st.relaxed.gpu.global.b32 [%0], %1;" :: "l"(p), "r"(x) : "memory"); }
__device__ __forceinline__ unsigned ld_rlx(const void* p) { unsigned v; asm volatile("ld.relaxed.gpu.global.u32 %0, [%1];" : "=r"(v) : "l"(p) : "memory"); return v; }
__device__ __forceinline__ void red_add4(void* p, float x, float y, float z, float w) {
    asm volatile("red.relaxed.gpu.global.add.v4.f32 [%0], {%1, %2, %3, %4};" :: "l"(p), "f"(x), "f"(y), "f"(z), "f"(w) : "memory");
}
__device__ __forceinline__ void fence_rel_gpu() { asm volatile("fence.proxy.async.global;\nfence.release.gpu;" ::: "memory"); }
__device__ __forceinline__ void fence_acq_gpu() { asm volatile("fence.acquire.gpu;" ::: "memory"); }
template<int N> __device__ __forceinline__ void poll_words(uint4 (&v)[N], const uint4* p, int stride, uint32_t tag) {
    #pragma unroll 1
    for (int it = 0; it < POLL_MAX; it++) {
        bool ok = true;
        #pragma unroll
        for (int i = 0; i < N; i++) v[i] = ld_ll(p + i * stride);
        #pragma unroll
        for (int i = 0; i < N; i++) ok = ok && v[i].z == tag && v[i].w == tag;
        if (__all_sync(0xffffffffu, ok)) break;
    }
}
__device__ __forceinline__ void pause(uint32_t n) { const uint32_t c0 = clk32(); while (clk32() - c0 < n) {} }
template<int B> __device__ __forceinline__ uint32_t low_byte(float v, uint32_t src) { return __byte_perm(__float_as_uint(v), src, 0x3214 + B); }
__device__ __forceinline__ uint32_t low_bits(float v, uint32_t tag2) { return (__float_as_uint(v) & ~3u) | tag2; }
__device__ __forceinline__ float untag2(uint32_t w, uint32_t tag2) { return __uint_as_float(w ^ tag2); }
__device__ __forceinline__ bool tagged2(uint32_t w, uint32_t tag2) { return (w & 3u) == tag2; }
__device__ __forceinline__ uint32_t umax4(uint4 v) { return max(max(v.x, v.y), max(v.z, v.w)); }
constexpr uint32_t ONE2 = 0x3F803F80u;
__device__ __forceinline__ uint32_t pack2(float lo, float hi) { uint32_t d; asm("cvt.rn.bf16x2.f32 %0, %1, %2;" : "=r"(d) : "f"(hi), "f"(lo)); return d; }
__device__ __forceinline__ float bf_lo(uint32_t v) { return __uint_as_float(v << 16); }
__device__ __forceinline__ float bf_lo_after(uint32_t v, float nonneg) { float d; asm("prmt.b32 %0, %1, %2, 0x10ff;" : "=f"(d) : "r"(v), "f"(nonneg)); return d; }
__device__ __forceinline__ float bf_hi_after(uint32_t v, float nonneg) { float d; asm("prmt.b32 %0, %1, %2, 0x32ff;" : "=f"(d) : "r"(v), "f"(nonneg)); return d; }
__device__ __forceinline__ float bf_hi(uint32_t v) { return __uint_as_float(v & 0xffff0000u); }
__device__ __forceinline__ float rbf(float x) { return bf_lo(pack2(x, 0.f)); }
__device__ __forceinline__ uint32_t hsub2(uint32_t a, uint32_t b) { uint32_t d; asm("sub.rn.bf16x2 %0, %1, %2;" : "=r"(d) : "r"(a), "r"(b)); return d; }
__device__ __forceinline__ uint32_t hadd2(uint32_t a, uint32_t b) { uint32_t d; asm("add.rn.bf16x2 %0, %1, %2;" : "=r"(d) : "r"(a), "r"(b)); return d; }
__device__ __forceinline__ uint32_t hmul2(uint32_t a, uint32_t b) { uint32_t d; asm("mul.rn.bf16x2 %0, %1, %2;" : "=r"(d) : "r"(a), "r"(b)); return d; }
__device__ __forceinline__ uint32_t hmax2(uint32_t a, uint32_t b) { uint32_t d; asm("max.bf16x2 %0, %1, %2;" : "=r"(d) : "r"(a), "r"(b)); return d; }
__device__ __forceinline__ uint32_t hmin2(uint32_t a, uint32_t b) { uint32_t d; asm("min.bf16x2 %0, %1, %2;" : "=r"(d) : "r"(a), "r"(b)); return d; }
__device__ __forceinline__ float ex2(float x) { float y; asm("ex2.approx.ftz.f32 %0, %1;" : "=f"(y) : "f"(x)); return y; }
__device__ __forceinline__ float rcp(float x) { float y; asm("rcp.approx.ftz.f32 %0, %1;" : "=f"(y) : "f"(x)); return y; }
__device__ __forceinline__ float shfl_x(float v, int m) { return __shfl_xor_sync(0xffffffffu, v, m); }
constexpr float LOG2E = 1.4426950408889634f;
__device__ __forceinline__ float sigmoidf(float x) { return rcp(1.0f + ex2(-LOG2E * x)); }
struct Recip { uint32_t hi, lo; };
__device__ __forceinline__ Recip split_recip(float r) { Recip q; q.hi = pack2(r, r); const float l = r - bf_hi(q.hi); q.lo = pack2(l, l); return q; }
__device__ __forceinline__ uint32_t hdiv2(uint32_t n, Recip r) { uint32_t d; asm("fma.rn.bf16x2 %0, %1, %2, %3;" : "=r"(d) : "r"(n), "r"(r.hi), "r"(hmul2(n, r.lo))); return d; }
__device__ __forceinline__ uint32_t ln_pair(uint32_t x, uint32_t m2, Recip r, uint32_t a, uint32_t s) { return hadd2(hmul2(hdiv2(hsub2(x, m2), r), a), s); }
__device__ __forceinline__ void ln_final(float s1, float s2, uint32_t& m2, float& rinv) {
    const float mean = s1 * (1.0f / 1024.0f), var = fmaf(-mean, mean, s2 * (1.0f / 1024.0f));
    m2 = pack2(mean, mean);
    float sd;
    asm("sqrt.approx.ftz.f32 %0, %1;" : "=f"(sd) : "f"(rbf(rbf(fmaxf(var, 0.f)) + 1e-5f)));
    rinv = rcp(rbf(sd));
}
__device__ __forceinline__ uint32_t f2key(float f) { uint32_t u = __float_as_uint(f); return (u & 0x80000000u) ? ~u : (u | 0x80000000u); }

__device__ __forceinline__ void fm_extrema(const uint32_t (&p)[16], float& cp, float& cn) {
    uint32_t mx = p[0], mn = p[0];
    #pragma unroll
    for (int k = 1; k < 15; k += 2) { mx = hmax2(hmax2(mx, p[k]), p[k + 1]); mn = hmin2(hmin2(mn, p[k]), p[k + 1]); }
    mx = hmax2(mx, p[15]); mn = hmin2(mn, p[15]);
    cp = -fmaxf(bf_lo(mx), bf_hi(mx)) * LOG2E; cn = fminf(bf_lo(mn), bf_hi(mn)) * LOG2E;
}
template<int TB> __device__ __forceinline__ void wgmma_n32_rs(float (&d)[16], uint32_t a0, uint32_t a1, uint32_t a2, uint32_t a3, uint64_t db, int sc) {
  asm volatile("{\n.reg .pred p;\nsetp.ne.b32 p, %21, 0;\n"
    "wgmma.mma_async.sync.aligned.m64n32k16.f32.bf16.bf16 {%0, %1, %2, %3, %4, %5, %6, %7, %8, %9, %10, %11, %12, %13, %14, %15}, {%16,%17,%18,%19}, %20, p, 1, 1, %22;\n}\n"
    : "+f"(d[0]), "+f"(d[1]), "+f"(d[2]), "+f"(d[3]), "+f"(d[4]), "+f"(d[5]), "+f"(d[6]), "+f"(d[7]), "+f"(d[8]), "+f"(d[9]), "+f"(d[10]), "+f"(d[11]), "+f"(d[12]), "+f"(d[13]), "+f"(d[14]), "+f"(d[15])
    : "r"(a0), "r"(a1), "r"(a2), "r"(a3), "l"(db), "r"(sc), "n"(TB));
}
template<int TA, int TB> __device__ __forceinline__ void wgmma_n40_ss(float (&d)[20], uint64_t da, uint64_t db, int sc) {
  asm volatile("{\n.reg .pred p;\nsetp.ne.b32 p, %22, 0;\n"
    "wgmma.mma_async.sync.aligned.m64n40k16.f32.bf16.bf16 {%0, %1, %2, %3, %4, %5, %6, %7, %8, %9, %10, %11, %12, %13, %14, %15, %16, %17, %18, %19}, %20, %21, p, 1, 1, %23, %24;\n}\n"
    : "+f"(d[0]), "+f"(d[1]), "+f"(d[2]), "+f"(d[3]), "+f"(d[4]), "+f"(d[5]), "+f"(d[6]), "+f"(d[7]), "+f"(d[8]), "+f"(d[9]), "+f"(d[10]), "+f"(d[11]), "+f"(d[12]), "+f"(d[13]), "+f"(d[14]), "+f"(d[15]), "+f"(d[16]), "+f"(d[17]), "+f"(d[18]), "+f"(d[19])
    : "l"(da), "l"(db), "r"(sc), "n"(TA), "n"(TB));
}
template<int TA, int TB> __device__ __forceinline__ void wgmma_n128_ss(float (&d)[64], uint64_t da, uint64_t db, int sc) {
  asm volatile("{\n.reg .pred p;\nsetp.ne.b32 p, %66, 0;\n"
    "wgmma.mma_async.sync.aligned.m64n128k16.f32.bf16.bf16 {%0, %1, %2, %3, %4, %5, %6, %7, %8, %9, %10, %11, %12, %13, %14, %15, %16, %17, %18, %19, %20, %21, %22, %23, %24, %25, %26, %27, %28, %29, %30, %31, %32, %33, %34, %35, %36, %37, %38, %39, %40, %41, %42, %43, %44, %45, %46, %47, %48, %49, %50, %51, %52, %53, %54, %55, %56, %57, %58, %59, %60, %61, %62, %63}, %64, %65, p, 1, 1, %67, %68;\n}\n"
    : "+f"(d[0]), "+f"(d[1]), "+f"(d[2]), "+f"(d[3]), "+f"(d[4]), "+f"(d[5]), "+f"(d[6]), "+f"(d[7]), "+f"(d[8]), "+f"(d[9]), "+f"(d[10]), "+f"(d[11]), "+f"(d[12]), "+f"(d[13]), "+f"(d[14]), "+f"(d[15]), "+f"(d[16]), "+f"(d[17]), "+f"(d[18]), "+f"(d[19]), "+f"(d[20]), "+f"(d[21]), "+f"(d[22]), "+f"(d[23]), "+f"(d[24]), "+f"(d[25]), "+f"(d[26]), "+f"(d[27]), "+f"(d[28]), "+f"(d[29]), "+f"(d[30]), "+f"(d[31]), "+f"(d[32]), "+f"(d[33]), "+f"(d[34]), "+f"(d[35]), "+f"(d[36]), "+f"(d[37]), "+f"(d[38]), "+f"(d[39]), "+f"(d[40]), "+f"(d[41]), "+f"(d[42]), "+f"(d[43]), "+f"(d[44]), "+f"(d[45]), "+f"(d[46]), "+f"(d[47]), "+f"(d[48]), "+f"(d[49]), "+f"(d[50]), "+f"(d[51]), "+f"(d[52]), "+f"(d[53]), "+f"(d[54]), "+f"(d[55]), "+f"(d[56]), "+f"(d[57]), "+f"(d[58]), "+f"(d[59]), "+f"(d[60]), "+f"(d[61]), "+f"(d[62]), "+f"(d[63])
    : "l"(da), "l"(db), "r"(sc), "n"(TA), "n"(TB));
}
template<int TB> __device__ __forceinline__ void wgmma_n128_rs(float (&d)[64], uint32_t a0, uint32_t a1, uint32_t a2, uint32_t a3, uint64_t db, int sc) {
  asm volatile("{\n.reg .pred p;\nsetp.ne.b32 p, %69, 0;\n"
    "wgmma.mma_async.sync.aligned.m64n128k16.f32.bf16.bf16 {%0, %1, %2, %3, %4, %5, %6, %7, %8, %9, %10, %11, %12, %13, %14, %15, %16, %17, %18, %19, %20, %21, %22, %23, %24, %25, %26, %27, %28, %29, %30, %31, %32, %33, %34, %35, %36, %37, %38, %39, %40, %41, %42, %43, %44, %45, %46, %47, %48, %49, %50, %51, %52, %53, %54, %55, %56, %57, %58, %59, %60, %61, %62, %63}, {%64,%65,%66,%67}, %68, p, 1, 1, %70;\n}\n"
    : "+f"(d[0]), "+f"(d[1]), "+f"(d[2]), "+f"(d[3]), "+f"(d[4]), "+f"(d[5]), "+f"(d[6]), "+f"(d[7]), "+f"(d[8]), "+f"(d[9]), "+f"(d[10]), "+f"(d[11]), "+f"(d[12]), "+f"(d[13]), "+f"(d[14]), "+f"(d[15]), "+f"(d[16]), "+f"(d[17]), "+f"(d[18]), "+f"(d[19]), "+f"(d[20]), "+f"(d[21]), "+f"(d[22]), "+f"(d[23]), "+f"(d[24]), "+f"(d[25]), "+f"(d[26]), "+f"(d[27]), "+f"(d[28]), "+f"(d[29]), "+f"(d[30]), "+f"(d[31]), "+f"(d[32]), "+f"(d[33]), "+f"(d[34]), "+f"(d[35]), "+f"(d[36]), "+f"(d[37]), "+f"(d[38]), "+f"(d[39]), "+f"(d[40]), "+f"(d[41]), "+f"(d[42]), "+f"(d[43]), "+f"(d[44]), "+f"(d[45]), "+f"(d[46]), "+f"(d[47]), "+f"(d[48]), "+f"(d[49]), "+f"(d[50]), "+f"(d[51]), "+f"(d[52]), "+f"(d[53]), "+f"(d[54]), "+f"(d[55]), "+f"(d[56]), "+f"(d[57]), "+f"(d[58]), "+f"(d[59]), "+f"(d[60]), "+f"(d[61]), "+f"(d[62]), "+f"(d[63])
    : "r"(a0), "r"(a1), "r"(a2), "r"(a3), "l"(db), "r"(sc), "n"(TB));
}
template<int TB> __device__ __forceinline__ void wgmma_n256_rs(float (&d)[128], uint32_t a0, uint32_t a1, uint32_t a2, uint32_t a3, uint64_t db, int sc) {
  asm volatile("{\n.reg .pred p;\nsetp.ne.b32 p, %133, 0;\n"
    "wgmma.mma_async.sync.aligned.m64n256k16.f32.bf16.bf16 {%0, %1, %2, %3, %4, %5, %6, %7, %8, %9, %10, %11, %12, %13, %14, %15, %16, %17, %18, %19, %20, %21, %22, %23, %24, %25, %26, %27, %28, %29, %30, %31, %32, %33, %34, %35, %36, %37, %38, %39, %40, %41, %42, %43, %44, %45, %46, %47, %48, %49, %50, %51, %52, %53, %54, %55, %56, %57, %58, %59, %60, %61, %62, %63, %64, %65, %66, %67, %68, %69, %70, %71, %72, %73, %74, %75, %76, %77, %78, %79, %80, %81, %82, %83, %84, %85, %86, %87, %88, %89, %90, %91, %92, %93, %94, %95, %96, %97, %98, %99, %100, %101, %102, %103, %104, %105, %106, %107, %108, %109, %110, %111, %112, %113, %114, %115, %116, %117, %118, %119, %120, %121, %122, %123, %124, %125, %126, %127}, {%128,%129,%130,%131}, %132, p, 1, 1, %134;\n}\n"
    : "+f"(d[0]), "+f"(d[1]), "+f"(d[2]), "+f"(d[3]), "+f"(d[4]), "+f"(d[5]), "+f"(d[6]), "+f"(d[7]), "+f"(d[8]), "+f"(d[9]), "+f"(d[10]), "+f"(d[11]), "+f"(d[12]), "+f"(d[13]), "+f"(d[14]), "+f"(d[15]), "+f"(d[16]), "+f"(d[17]), "+f"(d[18]), "+f"(d[19]), "+f"(d[20]), "+f"(d[21]), "+f"(d[22]), "+f"(d[23]), "+f"(d[24]), "+f"(d[25]), "+f"(d[26]), "+f"(d[27]), "+f"(d[28]), "+f"(d[29]), "+f"(d[30]), "+f"(d[31]), "+f"(d[32]), "+f"(d[33]), "+f"(d[34]), "+f"(d[35]), "+f"(d[36]), "+f"(d[37]), "+f"(d[38]), "+f"(d[39]), "+f"(d[40]), "+f"(d[41]), "+f"(d[42]), "+f"(d[43]), "+f"(d[44]), "+f"(d[45]), "+f"(d[46]), "+f"(d[47]), "+f"(d[48]), "+f"(d[49]), "+f"(d[50]), "+f"(d[51]), "+f"(d[52]), "+f"(d[53]), "+f"(d[54]), "+f"(d[55]), "+f"(d[56]), "+f"(d[57]), "+f"(d[58]), "+f"(d[59]), "+f"(d[60]), "+f"(d[61]), "+f"(d[62]), "+f"(d[63]), "+f"(d[64]), "+f"(d[65]), "+f"(d[66]), "+f"(d[67]), "+f"(d[68]), "+f"(d[69]), "+f"(d[70]), "+f"(d[71]), "+f"(d[72]), "+f"(d[73]), "+f"(d[74]), "+f"(d[75]), "+f"(d[76]), "+f"(d[77]), "+f"(d[78]), "+f"(d[79]), "+f"(d[80]), "+f"(d[81]), "+f"(d[82]), "+f"(d[83]), "+f"(d[84]), "+f"(d[85]), "+f"(d[86]), "+f"(d[87]), "+f"(d[88]), "+f"(d[89]), "+f"(d[90]), "+f"(d[91]), "+f"(d[92]), "+f"(d[93]), "+f"(d[94]), "+f"(d[95]), "+f"(d[96]), "+f"(d[97]), "+f"(d[98]), "+f"(d[99]), "+f"(d[100]), "+f"(d[101]), "+f"(d[102]), "+f"(d[103]), "+f"(d[104]), "+f"(d[105]), "+f"(d[106]), "+f"(d[107]), "+f"(d[108]), "+f"(d[109]), "+f"(d[110]), "+f"(d[111]), "+f"(d[112]), "+f"(d[113]), "+f"(d[114]), "+f"(d[115]), "+f"(d[116]), "+f"(d[117]), "+f"(d[118]), "+f"(d[119]), "+f"(d[120]), "+f"(d[121]), "+f"(d[122]), "+f"(d[123]), "+f"(d[124]), "+f"(d[125]), "+f"(d[126]), "+f"(d[127])
    : "r"(a0), "r"(a1), "r"(a2), "r"(a3), "l"(db), "r"(sc), "n"(TB));
}

constexpr uint32_t T_INI = 500;
constexpr uint32_t T_X0 = 450;
constexpr uint32_t T_XD = 600;
constexpr uint32_t T_P0 = 1500;
constexpr uint32_t T_P1 = 3000;
constexpr uint32_t T_W1 = 2800;
constexpr uint32_t T_S0 = 3300;
constexpr uint32_t T_S1 = 5800;
constexpr uint32_t T_WLATE = 4000;
constexpr uint32_t T_REST = 6000;
constexpr uint32_t T_COL = 7000;
constexpr uint32_t T_COL2 = 14000;
constexpr uint32_t T_OSC = 24000;
constexpr uint32_t T_OSD = 800;
constexpr uint32_t KVDLY = 700;
constexpr uint32_t OP0 = 500;
constexpr uint32_t OPS = 400;
constexpr int PFJ = 3;
constexpr int WOJ = 10;
constexpr int CREG = 208;
constexpr int KW = 8;
constexpr int DEP = 2;
constexpr int DNE = 12;
struct Ptrs { const bf16 *x, *c, *wmod, *wr, *wqkv, *wo; bf16* out; Scratch* s; };

#define BAR(i) (sb + OFF_BAR + 8u * (i))

__device__ __forceinline__ int d_block(int hg, int n) {
    const int m = n - (n >= 9 ? 9 : 2);
    return n < 2 ? 2 * hg + n : 2 * (m + (m >= hg)) + (n >= 9);
}
__host__ __device__ constexpr uint32_t bar_count(int i) {
    return ((i >= B_E1 && i < B_E1 + 3) || (i >= B_S0FREE && i < B_PHI + 4) || i == B_OWN || i == B_OWN + 1 || (i >= B_ED && i < B_ED + 16)
            || i == B_STFREE || i == B_X2 || i == B_OUTW || i == B_YP || i == B_RED) ? 8
         : ((i >= B_KVD && i < B_KVD + 2) || i == B_ST2 || i == B_TURN) ? 4 : (i == B_KVF || i == B_KVF + 1) ? 2 : 1;
}
template<int I0, int I1> __device__ __forceinline__ void init_barriers(uint32_t sb) {
    #pragma unroll
    for (int i = I0; i < I1; i++) mbar_init(BAR(i), bar_count(i));
}
__device__ __forceinline__ uint32_t pop_max(uint32_t& k) {
    const uint32_t m = __reduce_max_sync(0xffffffffu, k);
    k = k == m ? 0u : k;
    return m;
}
__device__ __forceinline__ uint32_t cand_row(uint32_t key) { return (key & 126u) * 16 + 31 - ((key >> 7) & 31u); }
__device__ __forceinline__ uint32_t mod_pos(int step, int g) { return step * 64 + (g >> 1) * 16 + (g & 1) * 4; }
__device__ __forceinline__ void fma8(float (&a)[8], uint4 w, float s) {
    a[0] = fmaf(bf_lo(w.x), s, a[0]); a[1] = fmaf(bf_hi(w.x), s, a[1]); a[2] = fmaf(bf_lo(w.y), s, a[2]); a[3] = fmaf(bf_hi(w.y), s, a[3]);
    a[4] = fmaf(bf_lo(w.z), s, a[4]); a[5] = fmaf(bf_hi(w.z), s, a[5]); a[6] = fmaf(bf_lo(w.w), s, a[6]); a[7] = fmaf(bf_hi(w.w), s, a[7]);
}
__device__ __forceinline__ float reduce8(const float (&v)[8], int lane) {
    const bool b3 = lane & 16, b2 = lane & 8, b1 = lane & 4;
    float a[4], b[2];
    #pragma unroll
    for (int i = 0; i < 4; i++) { float keep = b3 ? v[4 + i] : v[i], send = b3 ? v[i] : v[4 + i]; a[i] = keep + shfl_x(send, 16); }
    #pragma unroll
    for (int i = 0; i < 2; i++) { float keep = b2 ? a[2 + i] : a[i], send = b2 ? a[i] : a[2 + i]; b[i] = keep + shfl_x(send, 8); }
    float keep = b1 ? b[1] : b[0], send = b1 ? b[0] : b[1];
    return keep + shfl_x(send, 4);
}
__device__ __forceinline__ bool mod_collect(uint4 w0, uint4 w1, uint4 w2, uint4 w3, uint32_t sb, int jb, int lane, uint32_t tag2) {
    const uint32_t add = lane < 16 ? ONE2 : 0u;
    const uint32_t lo = pack2((__uint_as_float(w0.x) + __uint_as_float(w1.x)) + (__uint_as_float(w2.x) + __uint_as_float(w3.x)),
                              (__uint_as_float(w0.y) + __uint_as_float(w1.y)) + (__uint_as_float(w2.y) + __uint_as_float(w3.y)));
    const uint32_t hi = pack2((__uint_as_float(w0.z) + __uint_as_float(w1.z)) + (__uint_as_float(w2.z) + __uint_as_float(w3.z)),
                              (untag2(w0.w, tag2) + untag2(w1.w, tag2)) + (untag2(w2.w, tag2) + untag2(w3.w, tag2)));
    sts64(sb + OFF_MODS + jb * 256 + (lane & 15) * 16 + (lane >> 4) * 8, hadd2(lo, add), hadd2(hi, add));
    return tagged2(w0.w, tag2) && tagged2(w1.w, tag2) && tagged2(w2.w, tag2) && tagged2(w3.w, tag2);
}
__device__ __forceinline__ void phi_issue(float (&pp)[2][16], const uint32_t* a, uint32_t sb, int pair) {
    const uint64_t dw = mk_desc(sb + OFF_WPHI + pair * 4096, 16, 512, 2);
    wg_fence();
    #pragma unroll
    for (int ks = 0; ks < 2; ks++)
        #pragma unroll
        for (int h = 0; h < 2; h++) wgmma_n32_rs<1>(pp[h], a[8 * h + 4 * ks], a[8 * h + 4 * ks + 1], a[8 * h + 4 * ks + 2], a[8 * h + 4 * ks + 3], desc_add(dw, h * 2048 + ks * 1024), ks);
    wg_commit();
}
__device__ __forceinline__ void phi_transpose(float (&pp)[2][16], uint32_t (&pt)[16], uint32_t wr, uint32_t rd) {
    wg_wait<0>();
    acc_fence(pp[0]); acc_fence(pp[1]);
    #pragma unroll
    for (int q = 0; q < 4; q++) {
        const float (&a)[16] = pp[q >> 1]; const int o = 8 * (q & 1);
        stsm4(wr ^ (q << 5), pack2(a[o], a[o + 1]), pack2(a[o + 2], a[o + 3]), pack2(a[o + 4], a[o + 5]), pack2(a[o + 6], a[o + 7]));
    }
    __syncwarp();
    #pragma unroll
    for (int i = 0; i < 4; i++) { const uint4 v = lds128(rd ^ (i << 4)); pt[4 * i] = v.x; pt[4 * i + 1] = v.y; pt[4 * i + 2] = v.z; pt[4 * i + 3] = v.w; }
    __syncwarp();
}

__global__ void __cluster_dims__(2, 1, 1) __launch_bounds__(NTHREADS, 1)
fused_kernel(const Ptrs p, const __grid_constant__ CUtensorMap tmW, const __grid_constant__ CUtensorMap tmWo, const __grid_constant__ CUtensorMap tmPhi,
             const __grid_constant__ CUtensorMap tmG, const __grid_constant__ CUtensorMap tmU, const __grid_constant__ CUtensorMap tmD,
             const __grid_constant__ CUtensorMap tmX, const __grid_constant__ CUtensorMap tmO, const __grid_constant__ CUtensorMap tmM,
             const __grid_constant__ CUtensorMap tmR, const __grid_constant__ CUtensorMap tmG8, const __grid_constant__ CUtensorMap tmU8,
             const __grid_constant__ CUtensorMap tmD8)
{
    extern __shared__ __align__(1024) uint8_t smem_raw[];
    const uint32_t sb = smem_u32(smem_raw);
    const int tid = threadIdx.x, lane = tid & 31, warp = __shfl_sync(0xffffffffu, tid >> 5, 0);
    const int b = blockIdx.x;
    const int pr = b >> 1, rank = b & 1;
    const int cls = pr < 4 ? 15 : pr < 36 ? 2 * ((pr - 4) & 7) : 2 * ((pr - 36) % 7) + 1, mem = pr < 4 ? pr : pr < 36 ? (pr - 4) >> 3 : (pr - 36) / 7;
    const int hg = (((cls + 1) >> 1) & 1) * 4 + mem, rb = (cls >> 1) * 2 + rank;
    const bool ffn = b < 112;
    const uint32_t cstart = clk32();

    if (warp >= 8) {
        const int t = tid & 127, w4 = warp & 3, g = lane >> 2, c = lane & 3;
        reg_dec<40>();
        if (w4 == 0) { tmap_prefetch(&tmX); tmap_prefetch(&tmW); }
        if (w4 == 3) tmap_prefetch(&tmM);
        if (w4 < 2) while (clk32() - cstart < T_INI) {}
        if (elect_one()) {
            if (w4 & 2) { if (w4 & 1) init_barriers<B_WS, B_COUNT>(sb); else init_barriers<B_XS, B_WS>(sb); }
            else { if (w4 & 1) init_barriers<B_MP, B_XS>(sb); else init_barriers<0, B_MP>(sb); }
        }
        __syncwarp();
        if (w4 == 1) {
            asm volatile("fence.mbarrier_init.release.cluster;" ::: "memory");
            expect_tx_e(BAR(B_PX), 2048); sts32(sb + OFF_SEEN, 0);
        }
        bar_arrive(0, 384);
        if (w4 == 2) {
            #pragma unroll 1
            for (int i = 0; i < 4; i++) {
                while (clk32() - cstart < T_X0 + i * T_XD) {}
                bulk_load_e(sb + OFF_XS + i * 8192u, p.x + (size_t)(b * 16 + i * 4) * 1024, 8192, BAR(B_XS + i));
                expect_tx_e(BAR(B_XS + i), 8192);
            }
        }
        if (w4 == 3 && b < 64) {
            while (b >= 32 && clk32() - cstart < T_W1) {}
            #pragma unroll 1
            for (int i = 0; i < 4; i++) {
                tma2_ef_e(sb + OFF_WST + i * 8192u, &tmM, (((b >> 2) & 1) ? 0 : 1024) + (b >> 3) * 64, (b & 3) * 256 + i * 64, BAR(B_WS + i));
                expect_tx_e(BAR(B_WS + i), 8192);
            }
        }
        cluster_arrive();
        const uint32_t tag = ld_rlx(p.s->done) + 1, tag2 = tag % 3u;
        if (w4 == 0) {
            uint4* clr = p.s->kvp + (hg * 1024 + rb) * 32 + lane;
            #pragma unroll 1
            for (int j = 0; j < 3; j++) {
                while (clk32() - cstart < (j ? T_P1 : T_P0)) {}
                if (lane < 24) asm volatile("prefetch.global.L2 [%0];" :: "l"((const char*)p.wqkv + ((j * 128 + b) * 24 + lane) * 128));
            }
            int s = 0, par = 1;
            #pragma unroll 1
            for (int j = 0; j < 19; j++) {
                if (j >= 2) mbar_wait(BAR(j == 2 ? B_STFREE : B_E1 + s), j == 2 ? 0 : par);
                else while (clk32() - cstart < (j ? T_S1 : T_S0)) {}
                const uint32_t st = sb + OFF_RING + s * 65536u;
                if (j < 16) {
                    tma4_ef_e(st + 16384u, &tmW, j * 64, hg * 2, BAR(B_F1 + s));
                    tma2_e(st, &tmX, j * 64, rb * 128, BAR(B_F1 + s));
                    expect_tx_e(BAR(B_F1 + s), 65536);
                    if (j >= WOJ && j < WOJ + 4) asm volatile("prefetch.global.L2 [%0];" :: "l"((const char*)p.wo + (j - WOJ) * 524288 + (b * 32 + lane) * 128));
                } else if (j == 17) {
                    #pragma unroll 1
                    for (int n = 0; n < 2; n++) {
                        expect_tx_e(BAR(B_FB + 4 + n), 16384);
                        tma3_ef_e(st + n * 16384u, &tmWo, (2 * hg + n) * 64, hg * 2, BAR(B_FB + 4 + n));
                    }
                } else if (j == 18) {
                    expect_tx_e(BAR(B_S0), ffn ? 65536 : 32768);
                    #pragma unroll 1
                    for (int i = 0; i < (ffn ? 4 : 2); i++)
                        tma2_ef_e(st + i * 16384u, i < 2 ? &tmX : i == 2 ? &tmG : &tmU, i < 2 ? hg * 128 + i * 64 : pr * 64, i < 2 ? rb * 128 : rank * 512, BAR(B_S0));
                }
                par ^= s == 1;
                s = s == 0 ? 2 : s - 1;
                if (j >= 2 && j < 18) {
                    #pragma unroll
                    for (int i = 0; i < 4; i++) stg_fill(clr + i * 512, EMPTY);
                    clr += 2048;
                }
                const int piece = j - PFJ;
                if (ffn && piece >= 0 && piece < PND + 2 * PNG) {
                    if (piece < PND) tma3_e(sb + OFF_DUMMY, &tmD8, rank * 8, pr * 64 + piece * PRD, BAR(B_PF));
                    else tma2_e(sb + OFF_DUMMY, (piece & 1) ? &tmU8 : &tmG8, pr * 64, rank * 512 + 512 - PRG - ((piece - PND) >> 1) * PRG, BAR(B_PF));
                }
            }
            expect_tx_e(BAR(B_PF), ffn ? PND * PRD * 128 + 2 * PNG * PRG * 16 : 0);
        } else if (w4 == 1) {
            #pragma unroll 1
            for (int it = 0, jb = 4; it < POLL_MAX && jb < 16; it++) {
                while (clk32() - cstart < (jb < 8 ? T_COL : T_COL2)) {}
                const int n = min(4, (jb < 8 ? 8 : 16) - jb);
                bulk_load_e(sb + OFF_WPHI, p.s->mp + jb * 128, n * 2048, BAR(B_MP));
                expect_tx_e(BAR(B_MP), n * 2048);
                mbar_wait(BAR(B_MP), it & 1);
                #pragma unroll 1
                for (int q = 0; q < n; q++) {
                    const uint32_t a = sb + OFF_WPHI + q * 2048 + (lane >> 4) * 1024 + (lane & 15) * 16;
                    if (!__all_sync(0xffffffffu, mod_collect(lds128(a), lds128(a + 256), lds128(a + 512), lds128(a + 768), sb, jb, lane, tag2))) break;
                    arrive_many(BAR(B_MOD + jb), bar_count(B_MOD));
                    jb++;
                }
            }
            fence_async_smem();
            __syncwarp();
            expect_tx_e(BAR(B_WPHI), 8192);
            tma2_e(sb + OFF_WPHI, &tmPhi, 0, hg * 128, BAR(B_WPHI));
            #pragma unroll 1
            for (int i = 0; i < 4; i++) {
                uint4* rw = p.s->rowh + (rb * 8 + i * 2 + (lane >> 4)) * 128 + hg * 16 + (lane & 15);
                stg_fill(rw, EMPTY); stg_fill(rw + 16384, EMPTY);
                if (lane < 18) stg_fill(p.s->kvf + (hg * 4 + i) * 288 + (lane < 16 ? (rb >> 2) * 64 + (rb & 3) * 8 + (lane >> 3) * 32 + (lane & 7) : 240 + rb * 2 + lane), EMPTY);
            }
            if (hg == 0 && lane < 8) stg_fill(p.s->cand + rb * 8 + lane, 0);
            if (lane < 28) stg_fill(lane < 16 ? p.s->st2 + rb * 128 + hg * 16 + lane : lane < 20 ? p.s->flo + (rb * 16 + hg * 2) * 2 + lane - 16
                                    : p.s->rsc + ((rb * 4 + ((lane - 20) >> 1)) * 8 + hg) * 2 + (lane & 1), 0);
            fence_rel_gpu();
            #pragma unroll 1
            for (int i = 0; i < (ffn ? 9 : 8); i++) {
                while (clk32() - cstart < T_OSC + i * T_OSD) {}
                uint4* d = (i < 8 ? p.s->os + (rb * 16 + 2 * hg) * 1024 + i * 256 : p.s->yp + pr * 512 + rank * 128) + lane;
                #pragma unroll
                for (int q = 0; q < 4; q++) { stg_fill(d + q * 32, EMPTY); stg_fill(d + (i < 8 ? 128 : 256) + q * 32, EMPTY); }
            }
        } else {
            const int hw = w4 & 1;
            const uint32_t fb = BAR(B_RF + 2 * hw);
            if (w4 == 2) {
                if (lane < 8) stg_fill(p.s->rest + b * 8 + lane, 0);
                else if (lane < 24 && b >= 64) stg_fill(p.s->mp + b * 16 + lane - 8, EMPTY);
            }
            bar_sync(3, 320);
            const uint32_t buf = sb + OFF_SP + hw * 8192u;
            #pragma unroll 1
            for (int job = b < 64; job < 2; job++) {
                const int nr = job ? 8 : 4;
                const int c0 = job ? 2048 + b * 32 : (((b >> 2) & 1) ? 0 : 1024) + (b >> 3) * 64 + hw * 32;
                const int row0 = job ? hw * 512 : (b & 3) * 256;
                while (clk32() - cstart < (job ? T_REST : T_WLATE)) __nanosleep(100);
                float macc[8] = {0.f, 0.f, 0.f, 0.f, 0.f, 0.f, 0.f, 0.f};
                #pragma unroll 1
                for (int q = -2; q < nr; q++) {
                    if (q >= 0) {
                        mbar_wait(fb + (q & 1) * 8, (q >> 1) & 1);
                        const uint32_t sv0 = sb + OFF_SILU + (row0 + q * 64 + g) * 2, wa = buf + (q & 1) * 4096u + lane * 16u;
                        #pragma unroll
                        for (int i = 0; i < 8; i += 2) {
                            const uint32_t s0 = lds16(sv0 + i * 16), s1 = lds16(sv0 + i * 16 + 16);
                            const uint4 w0 = lds128(wa + i * 512u), w1 = lds128(wa + i * 512u + 512u);
                            fma8(macc, w0, bf_lo(s0)); fma8(macc, w1, bf_lo(s1));
                        }
                    }
                    __syncwarp();
                    if (q + 2 < nr) {
                        expect_tx_e(fb + (q & 1) * 8, 4096);
                        tma2_ef_e(buf + (q & 1) * 4096u, &tmR, c0, row0 + (q + 2) * 64, fb + (q & 1) * 8);
                    }
                }
                stsf(sb + OFF_RED0 + (job ? hw * 256 + (c * 8 + g) * 4 : mod_pos(hw * 2 + (c >> 1), g) + (c & 1) * 8), reduce8(macc, lane));
                bar_sync(4, 64);
                if (w4 == 2) {
                    const uint4 u0 = lds128(sb + OFF_RED0 + (lane & 15) * 16), u1 = lds128(sb + OFF_RED0 + 256 + (lane & 15) * 16);
                    const float v0 = __uint_as_float(u0.x) + __uint_as_float(u1.x), v1 = __uint_as_float(u0.y) + __uint_as_float(u1.y);
                    const float v2 = __uint_as_float(u0.z) + __uint_as_float(u1.z), v3 = __uint_as_float(u0.w) + __uint_as_float(u1.w);
                    const uint32_t add = (b >> 5) == 2 ? ONE2 : 0u;
                    if (job == 0) { if (lane < 16) st_ll(p.s->mp + b * 16 + lane, u0.x, u0.y, u0.z, low_bits(__uint_as_float(u0.w), tag2)); }
                    else { if (lane < 8) st_ll(p.s->rest + b * 8 + lane, hadd2(pack2(v0, v1), add), hadd2(pack2(v2, v3), add), tag, tag); }
                }
                bar_sync(4, 64);
            }
            tmap_prefetch(hw ? &tmWo : &tmG); tmap_prefetch(hw ? &tmU : &tmD); tmap_prefetch(hw ? &tmPhi : &tmO);
        }
        __syncwarp();
        cluster_wait();
        bar_sync(2, 128);
        reg_inc<504 - 2 * CREG>();
        #pragma unroll 1
        for (int pp = 0; pp < 2; pp++) {
            mbar_wait(BAR(B_PHI + pp), 0);
            fence_async_smem();
            float o[2][20];
            const uint32_t vb = OFF_V + pp * 16384u;
            const uint64_t dp = mk_desc(sb + (pp ? OFF_PHI1 : OFF_PHI0), 16, 1024, 1), dv = mk_desc(sb + vb, OFF_ONES - vb, 512, 2);
            wg_fence();
            #pragma unroll
            for (int hh = 0; hh < 2; hh++) {
                #pragma unroll
                for (int ks = 0; ks < 8; ks++)
                    wgmma_n40_ss<1, 1>(o[hh], desc_add(dp, hh * 16384 + ks * 2048), desc_raw(dv, (hh * 8 + ks) * (64 - (64 << 16))), ks);
                wg_commit();
            }
            #pragma unroll
            for (int hh = 0; hh < 2; hh++) {
                if (hh) wg_wait<0>(); else wg_wait<1>();
                acc_fence(o[hh]);
                if (hh) arrive_one(BAR(B_KVD + pp));
                if (hh == 0 && pp && w4 < 2) {
                    mbar_wait(BAR(B_KVD), 0);
                    bulk_load_e(sb + OFF_KVS + w4 * 8192u, p.s->kvp + ((hg * 4 + w4) * 16 + rb) * 512, 8192, BAR(B_KVS + w4));
                    expect_tx_e(BAR(B_KVS + w4), 8192);
                }
                uint4* dst = p.s->kvp + (((hg * 4 + 2 * pp + hh) * 16 + (t >> 3)) * 16 + rb) * 32 + (t & 7);
                const float (&a)[20] = o[hh];
                #pragma unroll
                for (int k = 0; k < 2; k++) {
                    const uint32_t z = __float_as_uint(a[16 + 2 * k]);
                    st_ll(dst + k * 8, low_byte<1>(a[4 * k], z), low_byte<2>(a[4 * k + 1], z), low_byte<3>(a[4 * k + 2], z), low_bits(a[4 * k + 3], tag2));
                    st_ll(dst + 16 + k * 8, __float_as_uint(a[8 + 4 * k]), __float_as_uint(a[9 + 4 * k]), __float_as_uint(a[10 + 4 * k]), low_bits(a[11 + 4 * k], tag2));
                }
            }
        }
        {
            uint4* const fin = p.s->kvf + (hg * 4 + w4) * 288;
            {
                const uint4* src = p.s->kvp + ((hg * 4 + w4) * 16 + rb) * 512 + lane;
                uint4 w[16];
                if (w4 < 2) {
                    mbar_wait(BAR(B_KVS + w4), 0);
                    #pragma unroll
                    for (int i = 0; i < 16; i++) w[i] = lds128(sb + OFF_KVS + w4 * 8192u + i * 512u + lane * 16u);
                } else {
                    pause(KVDLY);
                    #pragma unroll
                    for (int i = 0; i < 16; i++) w[i].w = EMPTY;
                }
                #pragma unroll 1
                for (int it = 0; it < POLL_MAX; it++) {
                    uint32_t bad = 0;
                    #pragma unroll
                    for (int i = 0; i < 16; i++) bad |= w[i].w ^ tag2;
                    if (__all_sync(0xffffffffu, !(bad & 3))) break;
                    #pragma unroll
                    for (int i = 0; i < 16; i++) ld_ll_if(w[i], src + i * 32, !tagged2(w[i].w, tag2));
                }
                float s[5], s2[5];
                #pragma unroll
                for (int i = 0; i < 16; i++) {
                    const float z = __uint_as_float(__byte_perm(__byte_perm(w[i].x, w[i].y, 0x0400), w[i].z, 0x4210));
                    float (&a)[5] = (i & 1) ? s2 : s;
                    if (i < 2) { a[0] = __uint_as_float(w[i].x); a[1] = __uint_as_float(w[i].y); a[2] = __uint_as_float(w[i].z); a[3] = untag2(w[i].w, tag2); a[4] = z; }
                    else { a[0] += __uint_as_float(w[i].x); a[1] += __uint_as_float(w[i].y); a[2] += __uint_as_float(w[i].z); a[3] += untag2(w[i].w, tag2); a[4] += z; }
                }
                #pragma unroll
                for (int i = 0; i < 5; i++) s[i] += s2[i];
                char* d = (char*)fin + ((rb >> 2) * 16 + (rb & 3) * 2 + (g & 1)) * 64 + (((lane >> 3) ^ (rb & 3)) << 4) + c * 4;
                st_ll4(d, pack2(s[0], s[1]));
                st_ll4(d + 512, pack2(s[2], s[3]));
                if (lane < 16 && c < 2) st_ll4((char*)fin + 4096 + rb * 32 + (g * 2 + c) * 4, pack2(s[4], s[4]));
            }
            mbar_wait(BAR(B_PF), 1);
            fence_acq_gpu();
            uint4 v[9];
            #pragma unroll 1
            for (int it = 0; it < POLL_MAX; it++) {
                uint32_t m = 0;
                #pragma unroll
                for (int k = 0; k < 9; k++) v[k] = ld_ll(fin + k * 32 + lane);
                #pragma unroll
                for (int k = 0; k < 9; k++) m = max(m, umax4(v[k]));
                if (__all_sync(0xffffffffu, m != EMPTY)) break;
            }
            #pragma unroll
            for (int k = 0; k < 8; k++) sts128(sb + OFF_SP + w4 * 4096u + k * 512u + lane * 16u, v[k]);
            const uint32_t za = sb + OFF_Z + ((lane >> 3) * 16 + ((lane >> 1) & 3) * 2 + (lane & 1) * 8) * 64u + ((w4 ^ ((lane >> 1) & 3)) << 4);
            sts128(za, make_uint4(v[8].x, v[8].x, v[8].x, v[8].x)); sts128(za + 64, make_uint4(v[8].z, v[8].z, v[8].z, v[8].z));
            __syncwarp();
            arrive_one(BAR(B_KVF + (w4 >> 1)));
        }
        if (w4 == 0) {
            const unsigned* f = (const unsigned*)(p.s->flo + (rb * 16 + d_block(hg, lane & 15)) * 2);
            const uint4* const a0 = p.s->os + rb * 16384;
            uint32_t seen = 0;
            uint32_t kb = hg ? 0 : 2, s = 4, freeb = BAR(B_OWN), par = 0;
            mbar_wait(BAR(B_OWN), 0);
            fence_async_smem();
            bulk_store_e(p.s->os + (rb * 16 + 2 * hg) * 1024, sb + OFF_OWN, 16384);
            bulk_commit();
            mbar_wait(BAR(B_REL), 0);
            bulk_wait();
            st_flag_e(p.s->flo + (rb * 16 + 2 * hg) * 2, tag);
            #pragma unroll 1
            for (int n = 2; n < 16; n++) {
                if (!((seen >> n) & 1)) {
                    if (n >= 8) asm volatile("ld.acquire.cta.shared.u32 %0, [%1];" : "=r"(seen) : "r"(sb + OFF_SEEN) : "memory");
                    #pragma unroll 1
                    for (int it = 0; it < POLL_MAX && !((seen >> n) & 1); it++) { seen = __ballot_sync(0xffffffffu, ld_rlx(f) == tag); fence_acq_gpu(); }
                }
                mbar_wait(freeb, par);
                bulk_load_e(sb + OFF_DA + s * 16384u, a0 + kb * 1024, 16384, BAR(B_FA + s));
                expect_tx_e(BAR(B_FA + s), 16384);
                if (n == 6) mbar_wait(BAR(B_PUB), 0);
                kb = n == 8 ? 1 : kb + 2;
                if ((kb >> 1) == hg) kb += 2;
                s = (SLOT_A >> (4 * n + 4)) & 7;
                if (n >= 5) { freeb = BAR(B_ED + n - 5); par = 1; } else if (n == 3) freeb = BAR(B_OWN + 1);
            }
        } else if (w4 == 1) {
            if (ffn) { expect_tx_e(BAR(B_GU), 98304); expect_tx_e(BAR(B_WD), 65536); }
            fence_rel_gpu();
            arrive_one(BAR(B_REL));
            mbar_wait(BAR(B_S0FREE), 0);
            #pragma unroll 1
            for (int n = 2; n < (ffn ? 20 : 16); n++) {
                if (n >= 6) mbar_wait(BAR(B_ED + n - 6), 1);
                if (n < 16) {
                    const uint32_t s = (SLOT_B >> (4 * n)) & 7, bar = BAR(B_FB + s), dst = sb + OFF_DB + s * 16384u;
                    expect_tx_e(bar, 16384);
                    tma3_ef_e(dst, &tmWo, d_block(hg, n) * 64, hg * 2, bar);
                    if (ffn && (n == 6 || n == 7)) tma2_ef_e(sb + OFF_GB + (n & 1) * 16384u, (n & 1) ? &tmU : &tmG, pr * 64, rank * 512 + 128, BAR(B_GU));
                } else if (n < 18) {
                    tma2_ef_e(sb + OFF_UP0 + (n & 1) * 16384u, (n & 1) ? &tmU : &tmG, pr * 64, rank * 512 + 256, BAR(B_GU));
                    tma2_ef_e(sb + OFF_UP1 + (n & 1) * 16384u, (n & 1) ? &tmU : &tmG, pr * 64, rank * 512 + 384, BAR(B_GU));
                } else {
                    tma3_ef_e(sb + OFF_DN0 + (n & 1) * 16384u, &tmD, pr * 64, rank * 8 + (n & 1) * 2, BAR(B_WD));
                    tma3_ef_e(sb + OFF_DN1 + (n & 1) * 16384u, &tmD, pr * 64, rank * 8 + 4 + (n & 1) * 2, BAR(B_WD));
                }
            }
        } else if (w4 == 3) {
            const unsigned* f = (const unsigned*)(p.s->flo + (rb * 16 + d_block(hg, lane & 15)) * 2);
            uint32_t seen = 0xffff0003u;
            mbar_wait(BAR(B_PUB), 0);
            #pragma unroll 1
            for (int it = 0; it < POLL_MAX && seen != 0xffffffffu; it++) {
                const uint32_t m = seen | __ballot_sync(0xffffffffu, !((seen >> lane) & 1) && ld_rlx(f) == tag);
                if (m != seen) {
                    seen = m;
                    fence_acq_gpu();
                    __syncwarp();
                    asm volatile(EL "st.release.cta.shared.u32 [%0], %1;\n}" :: "r"(sb + OFF_SEEN), "r"(seen) : "memory");
                }
            }
        } else {
            mbar_wait(BAR(B_OWN + 1), 0);
            fence_async_smem();
            #pragma unroll 1
            for (uint32_t i = 0, due = clk32() + OP0; i < 4; i++, due += OPS) {
                while ((int)(clk32() - due) < 0) {}
                bulk_store_e(p.s->os + (rb * 16 + 2 * hg + 1) * 1024 + i * 256, sb + OFF_OWN + 16384u + i * 4096u, 4096);
            }
            bulk_commit();
            mbar_wait(BAR(B_REL), 0);
            bulk_wait();
            st_flag_e(p.s->flo + (rb * 16 + 2 * hg + 1) * 2, tag);
            arrive_one(BAR(B_PUB));
            {
                uint4 w[4];
                poll_words<4>(w, p.s->rest + hg * 32 + lane, 256, tag);
                sts64(sb + OFF_PAR + lane * 8, w[2].x, w[2].y); sts64(sb + OFF_PAR + 256 + lane * 8, w[1].x, w[1].y);
                sts64(sb + OFF_PAR + 512 + lane * 8, w[3].x, w[3].y); sts64(sb + OFF_PAR + 768 + lane * 8, w[0].x, w[0].y);
                const uint2 wr = ldg64(p.wr + hg * 128 + lane * 4);
                sts64(sb + OFF_BQ + lane * 8, hmul2(w[2].x, wr.x), hmul2(w[2].y, wr.y));
            }
            float s = 0.f;
            #pragma unroll 1
            for (int i = 0; i < 2; i++) {
                uint4 w[4]; uint2 wr[4];
                #pragma unroll
                for (int q = 0; q < 4; q++) wr[q] = ldg64(p.wr + (lane + 32 * q + 128 * i) * 4);
                poll_words<4>(w, p.s->rest + 512 + i * 128 + lane, 32, tag);
                #pragma unroll
                for (int q = 0; q < 4; q++) { const uint32_t r0 = hmul2(w[q].x, wr[q].x), r1 = hmul2(w[q].y, wr[q].y); s += (bf_lo(r0) + bf_hi(r0)) + (bf_lo(r1) + bf_hi(r1)); }
            }
            __syncwarp();
            #pragma unroll
            for (int m = 16; m >= 1; m >>= 1) s += shfl_x(s, m);
            if (lane == 0) { stsf(sb + OFF_ATOT, s); sts128(sb + OFF_BQ + 272, make_uint4(ONE2, ONE2, ONE2, ONE2)); }
            __syncwarp();
            arrive_one(BAR(B_PAR));
        }
        __syncwarp();
        {
            mbar_wait(BAR(B_PAR), 0);
            const uint4 pa = lds128(sb + OFF_PAR + (lane & 15) * 16), ps = lds128(sb + OFF_PAR + 256 + (lane & 15) * 16);
            const uint4 wr = ldg128(p.wr + hg * 128 + (lane & 15) * 8);
            const float atot = ldsf(sb + OFF_ATOT);
            mbar_wait(BAR(B_RED), 0);
            uint4 w;
            #pragma unroll 1
            for (int it = 0; it < POLL_MAX; it++) {
                w = ld_ll(p.s->st2 + rb * 128 + t);
                if (__all_sync(0xffffffffu, __uint_as_float(w.w) == 8.0f)) break;
            }
            uint32_t m2; float rinv;
            ln_final(__uint_as_float(w.x), __uint_as_float(w.y), m2, rinv);
            const uint32_t grp = rb * 4 + w4;
            uint32_t k = (f2key(fmaf(-bf_lo(m2), atot, __uint_as_float(w.z)) * rinv) & ~0xfffu) | ((31 - lane) << 7) | (grp * 2);
            const uint32_t best0 = pop_max(k), best1 = pop_max(k) | 1u;
            if (hg == 0 && lane < 2) st_ll(p.s->cand + grp * 2 + lane, best0, best1, tag, tag);
            const uint32_t row = w4 * 32 + 31 - (((lane < 16 ? best0 : best1) >> 7) & 31u);
            mbar_wait(BAR(B_X2), 0);
            const uint4 xv = lds128(sb + OFF_OUT + (row >> 3) * 2048u + ((lane >> 3) & 1) * 1024u + (row & 7) * 128u + (((lane ^ row) & 7) << 4));
            sts64(sb + OFF_ST2 + t * 8, m2, __float_as_uint(rinv));
            __syncwarp();
            arrive_one(BAR(B_ST2));
            const uint32_t rm = __shfl_sync(0xffffffffu, m2, row & 31);
            const Recip rr = split_recip(__shfl_sync(0xffffffffu, rinv, row & 31));
            const uint32_t h0 = ln_pair(xv.x, rm, rr, pa.x, ps.x), h1 = ln_pair(xv.y, rm, rr, pa.y, ps.y);
            const uint32_t h2 = ln_pair(xv.z, rm, rr, pa.z, ps.z), h3 = ln_pair(xv.w, rm, rr, pa.w, ps.w);
            uint4* d = p.s->rowh + (grp * 2 + (lane >> 4)) * 128 + hg * 16 + (lane & 15);
            st_ll(d, h0, h1, h2, h3);
            st_ll(d + 16384, xv.x, xv.y, xv.z, xv.w);
            float r = (fmaf(bf_lo(h0), bf_lo(wr.x), bf_hi(h0) * bf_hi(wr.x)) + fmaf(bf_lo(h1), bf_lo(wr.y), bf_hi(h1) * bf_hi(wr.y)))
                    + (fmaf(bf_lo(h2), bf_lo(wr.z), bf_hi(h2) * bf_hi(wr.z)) + fmaf(bf_lo(h3), bf_lo(wr.w), bf_hi(h3) * bf_hi(wr.w)));
            #pragma unroll
            for (int m = 8; m >= 1; m >>= 1) r += shfl_x(r, m);
            if (!(lane & 15)) st_ll(p.s->rsc + (grp * 8 + hg) * 2 + (lane >> 4), __float_as_uint(r), __float_as_uint(r), tag, tag);
        }
        if (w4 == 0) {
            uint4 cv[2];
            poll_words<2>(cv, p.s->cand + lane * 2, 64, tag);
            const uint32_t ka = min(cv[0].x, cv[1].x), kb = max(cv[0].y, cv[1].y);
            uint32_t k0 = max(cv[0].x, cv[1].x), k1 = max(ka, kb), k2 = min(ka, kb), k3 = min(cv[0].y, cv[1].y), m[4];
            uint4 hv[4][2];
            const uint4* const h0 = p.s->rowh + rank * 64 + lane;
            #pragma unroll
            for (int i = 0; i < 4; i++) {
                m[i] = __reduce_max_sync(0xffffffffu, k0);
                if (k0 == m[i]) { k0 = k1; k1 = k2; k2 = k3; }
                hv[i][0] = ld_ll(h0 + (m[i] & 127u) * 128); hv[i][1] = ld_ll(h0 + (m[i] & 127u) * 128 + 32);
            }
            sts128(sb + OFF_SEL + 32, make_uint4(m[0], m[1], m[2], m[3]));
            __syncwarp();
            arrive_one(BAR(B_CAND));
            #pragma unroll 1
            for (int it = 0; it < POLL_MAX; it++) {
                uint32_t mx = 0;
                #pragma unroll
                for (int i = 0; i < 4; i++) mx = max(mx, max(hv[i][0].x, hv[i][1].x));
                if (__all_sync(0xffffffffu, mx != EMPTY)) break;
                #pragma unroll
                for (int i = 0; i < 4; i++) { hv[i][0] = ld_ll(h0 + (m[i] & 127u) * 128); hv[i][1] = ld_ll(h0 + (m[i] & 127u) * 128 + 32); }
            }
            #pragma unroll
            for (int i = 0; i < 4; i++) { sts128(sb + OFF_ROWS + i * 1056u + lane * 16u, hv[i][0]); sts128(sb + OFF_ROWS + i * 1056u + 528u + lane * 16u, hv[i][1]); }
            __syncwarp();
            arrive_one(BAR(B_ROWS));
        } else if (w4 == 3) {
            mbar_wait(BAR(B_CAND), 0);
            const uint32_t m = lds32(sb + OFF_SEL + 32 + (lane >> 3) * 4), slot = m & 127u, row = cand_row(m);
            uint4 sc[1];
            poll_words<1>(sc, p.s->rsc + ((slot >> 1) * 8 + (lane & 7)) * 2 + (slot & 1), 0, tag);
            float r = __uint_as_float(sc[0].x & sc[0].y);
            r += shfl_x(r, 1); r += shfl_x(r, 2); r += shfl_x(r, 4);
            r = rbf(r);
            const uint32_t key = (f2key(r) & 0xffff0000u) | (0xffffu - row);
            uint32_t kq = key;
            const uint32_t best0 = pop_max(kq), best1 = pop_max(kq), tok = key == best0 ? 0 : key == best1 ? 1 : 2;
            sts32(sb + OFF_SEL + 48 + (lane >> 3) * 4, tok);
            if (tok < 2) sts128(sb + OFF_SEL + tok * 16, make_uint4(row, slot, __float_as_uint(r), 0));
            __syncwarp();
            arrive_one(BAR(B_SEL));
        } else if (w4 == 1) {
            mbar_wait(BAR(B_SEL), 0);
            const uint4 sel = lds128(sb + OFF_SEL + rank * 16);
            const int col = pr * 16 + c * 2 + (lane >> 4) + (lane & 8);
            uint32_t xs, hs; uint4 gw;
            #pragma unroll 1
            for (int it = 0; it < POLL_MAX; it++) {
                const char* a = (const char*)(p.s->rowh + sel.y * 128) + (col >> 1) * 4;
                hs = ld_rlx(a); xs = ld_rlx(a + 262144); gw = ld_ll(p.s->rest + 768 + (col >> 2));
                if (__all_sync(0xffffffffu, hs != EMPTY && xs != EMPTY && gw.z == tag && gw.w == tag)) break;
            }
            const uint32_t gq = (col & 2) ? gw.y : gw.x;
            const float fx = (col & 1) ? bf_hi(xs) : bf_lo(xs), fh = (col & 1) ? bf_hi(hs) : bf_lo(hs), fg = (col & 1) ? bf_hi(gq) : bf_lo(gq);
            const float sg = rbf(sigmoidf(__uint_as_float(sel.z)));
            const uint4* src = p.s->yp + g * 512 + rank * 256 + pr * 4 + c;
            bf16* optr = p.out + (size_t)sel.x * 1024 + col;
            asm volatile("" : "+l"(optr));
            uint4 w[7];
            #pragma unroll
            for (int i = 0; i < 7; i++) w[i] = make_uint4(0, EMPTY, 0, EMPTY);
            if (ffn) mbar_wait(BAR(B_YP), 0);
            #pragma unroll 1
            for (int it = 0; it < POLL_MAX; it++) {
                bool ok = true;
                #pragma unroll
                for (int i = 0; i < 7; i++) ld_ll_if(w[i], src + i * 4096, !(tagged2(w[i].y, tag2) && tagged2(w[i].w, tag2)));
                #pragma unroll
                for (int i = 0; i < 7; i++) ok = ok && tagged2(w[i].y, tag2) && tagged2(w[i].w, tag2);
                if (__all_sync(0xffffffffu, ok)) break;
            }
            float y0 = __uint_as_float(w[0].x), y1 = untag2(w[0].y, tag2), y2 = __uint_as_float(w[0].z), y3 = untag2(w[0].w, tag2);
            #pragma unroll
            for (int i = 1; i < 7; i++) { y0 += __uint_as_float(w[i].x); y1 += untag2(w[i].y, tag2); y2 += __uint_as_float(w[i].z); y3 += untag2(w[i].w, tag2); }
            const bool b4 = lane & 16, b3 = lane & 8;
            const float a0 = (b4 ? y2 : y0) + shfl_x(b4 ? y0 : y2, 16), a1 = (b4 ? y3 : y1) + shfl_x(b4 ? y1 : y3, 16);
            float y = (b3 ? a1 : a0) + shfl_x(b3 ? a0 : a1, 8);
            y += shfl_x(y, 4);
            const float upd = rbf(rbf(y) * sg);
            if (!(lane & 4)) *optr = __float2bfloat16(fx + rbf(fg * rbf(fh + upd)));
            if (b == 0 && lane == 0) p.s->done[0] = tag;
        } else {
            mbar_wait(BAR(B_CAND), 0);
            const uint32_t cg = (cand_row(lds32(sb + OFF_SEL + 32 + c * 4)) >> 3) - rb * 16;
            uint32_t late = __reduce_or_sync(0xffffffffu, cg < 16 ? 1u << cg : 0u);
            mbar_wait(BAR(B_OUTW), 0);
            fence_async_smem();
            #pragma unroll 1
            for (uint32_t i = 0; i < 16; i++)
                if (!((late >> i) & 1))
                    asm volatile(EL "cp.async.bulk.tensor.3d.global.shared::cta.bulk_group [%0, {0, %2, %3}], [%1];\n}"
                        :: "l"(&tmO), "r"(sb + OFF_OUT + i * 2048u), "r"(rb * 128 + i * 8), "r"(hg * 2) : "memory");
            bulk_commit();
            mbar_wait(BAR(B_SEL), 0);
            const uint32_t row0 = lds32(sb + OFF_SEL) - rb * 128, row1 = lds32(sb + OFF_SEL + 16) - rb * 128;
            #pragma unroll 1
            for (; late; late &= late - 1) {
                const uint32_t i = __ffs(late) - 1;
                #pragma unroll 1
                for (uint32_t q = 0; q < 4; q++) {
                    const uint32_t r = q * 2 + (lane >> 4), ch = lane & 15;
                    const uint4 v = lds128(sb + OFF_OUT + i * 2048u + (ch >> 3) * 1024u + r * 128u + (((ch ^ r) & 7) << 4));
                    if (i * 8 + r != row0 && i * 8 + r != row1) stg128(p.out + (size_t)(rb * 128 + i * 8 + r) * 1024 + hg * 128 + ch * 8, v);
                }
            }
            bulk_wait();
        }
    } else {
        const int w4 = warp & 3, wgi = warp >> 2;
        uint32_t m2[2], r[4]; Recip ri0, ri1;
        uint32_t tag2;
        {
            const int g = lane >> 2, c = lane & 3, xrow = b * 16 + warp * 2;
            if (b < 32)
                asm volatile("prefetch.global.L2 [%0];" :: "l"(p.wmod + (size_t)((b & 3) * 256 + tid) * 6144 + (((b >> 2) & 1) ? 0 : 1024) + (b >> 3) * 64));
            const uint2 cv = ldg64(p.c + tid * 4);
            const uint32_t tag = ld_rlx(p.s->done) + 1;
            if (lane < 2) stg_fill(p.s->st1 + xrow + lane, 0);
            if (warp == 0 && lane < 16 && b < 64) stg_fill(p.s->mp + b * 16 + lane, EMPTY);
            if (tid < 64) { int s = tid >> 2; sts128(sb + OFF_ONES + tid * 16, make_uint4(((tid & 3) == ((s >> 1) & 3)) ? 0x3F80u : 0u, 0, 0, 0)); }
            cluster_arrive();
            reg_inc<232>();
            {
                const float c0 = bf_lo(cv.x), c1 = bf_hi(cv.x), c2 = bf_lo(cv.y), c3 = bf_hi(cv.y);
                sts64(sb + OFF_SILU + tid * 8, pack2(c0 * sigmoidf(c0), c1 * sigmoidf(c1)), pack2(c2 * sigmoidf(c2), c3 * sigmoidf(c3)));
            }
            tag2 = tag % 3u;
            bar_sync(0, 384);
            bar_arrive(3, 320);
            #pragma unroll 1
            for (int part = 0; part < 2; part++)
            if (part == (b < 32)) {
                mbar_wait(BAR(B_XS + (warp >> 1)), 0);
                float sd[2][4], q1[2][4], q2[2][4];
                #pragma unroll
                for (int e = 0; e < 4; e++) { sd[0][e] = sd[1][e] = q1[0][e] = q1[1][e] = q2[0][e] = q2[1][e] = 0.f; }
                #pragma unroll
                for (int i = 0; i < 8; i++) {
                    uint32_t a0, a1, a2, a3;
                    ldsm4(a0, a1, a2, a3, sb + OFF_XS + warp * 4096u + ((lane >> 3) & 1) * 2048u + i * 256u + (lane >> 4) * 128u + (lane & 7) * 16u);
                    mma16816(sd[i & 1], a0, a1, a2, a3, ONE2, ONE2);
                    mma1688(q1[0], a0, a1, a0); mma1688(q2[0], a0, a1, a1); mma1688(q1[1], a2, a3, a2); mma1688(q2[1], a2, a3, a3);
                }
                const float d0 = __shfl_sync(0xffffffffu, (g & 1) ? q1[0][1] + q1[1][1] : q1[0][0] + q1[1][0], g * 4 + (g >> 1));
                const float d1 = __shfl_sync(0xffffffffu, (g & 1) ? q2[0][3] + q2[1][3] : q2[0][2] + q2[1][2], g * 4 + (g >> 1));
                float sk = (c & 1) ? sd[0][2] + sd[1][2] : sd[0][0] + sd[1][0], qk = (c & 1) ? d1 : d0;
                #pragma unroll
                for (int m = 4; m <= 16; m <<= 1) { sk += shfl_x(sk, m); qk += shfl_x(qk, m); }
                uint32_t mm; float ri;
                ln_final(sk, qk, mm, ri);
                const Recip rr = split_recip(ri);
                if (lane < 2) st_ll(p.s->st1 + xrow + lane, mm, rr.hi, rr.lo, tag);
            } else if (b < 64) {
                float m[4][4];
                uint32_t sv[4];
                ldsm4(sv[0], sv[1], sv[2], sv[3], sb + OFF_SILU + ((b & 3) * 256 + warp * 32) * 2 + (lane >> 3) * 16);
                mbar_wait(BAR(B_WS + (warp >> 1)), 0);
                #pragma unroll
                for (int tt = 0; tt < 4; tt++) {
                    m[tt][0] = m[tt][1] = m[tt][2] = m[tt][3] = 0.f;
                    #pragma unroll
                    for (int e = 0; e < 2; e++) {
                        uint32_t a0, a1, a2, a3;
                        ldsm4t(a0, a1, a2, a3, sb + OFF_WST + warp * 4096u + (e * 16 + (lane & 7) + ((lane >> 4) << 3)) * 128u + (((2 * tt + ((lane >> 3) & 1)) ^ (lane & 7)) << 4));
                        mma16816(m[tt], a0, a1, a2, a3, sv[2 * e], sv[2 * e + 1]);
                    }
                }
                const uint32_t ra = sb + OFF_RED0 + warp * 256 + mod_pos(c, g);
                stsf(ra, (c & 2) ? ((c & 1) ? m[3][0] : m[2][0]) : ((c & 1) ? m[1][0] : m[0][0]));
                stsf(ra + 8, (c & 2) ? ((c & 1) ? m[3][2] : m[2][2]) : ((c & 1) ? m[1][2] : m[0][2]));
                if (warp != 7) bar_arrive(5, 256);
                else {
                    bar_sync(5, 256);
                    float v0 = 0.f, v1 = 0.f, v2 = 0.f, v3 = 0.f;
                    #pragma unroll
                    for (int w = 0; w < 4; w++) {
                        const uint4 u = lds128(sb + OFF_RED0 + w * 512 + lane * 16);
                        v0 += __uint_as_float(u.x); v1 += __uint_as_float(u.y); v2 += __uint_as_float(u.z); v3 += __uint_as_float(u.w);
                    }
                    v0 += shfl_x(v0, 16); v1 += shfl_x(v1, 16); v2 += shfl_x(v2, 16); v3 += shfl_x(v3, 16);
                    if (lane < 16) st_ll(p.s->mp + b * 16 + lane, __float_as_uint(v0), __float_as_uint(v1), __float_as_uint(v2), low_bits(v3, tag2));
                }
            }
            cluster_wait();
            uint4 st[2];
            bool need = warp < 4;
            #pragma unroll 1
            for (int it = 0; it < POLL_MAX; it++) {
                st[0] = ld_ll(p.s->st1 + rb * 128 + warp * 16 + g); st[1] = ld_ll(p.s->st1 + rb * 128 + warp * 16 + g + 8);
                if (need) {
                    const uint4* src = p.s->mp + (warp * 8 + (lane >> 4) * 4) * 16 + (lane & 15);
                    const uint4 w0 = ld_ll(src), w1 = ld_ll(src + 16), w2 = ld_ll(src + 32), w3 = ld_ll(src + 48);
                    if (__all_sync(0xffffffffu, mod_collect(w0, w1, w2, w3, sb, warp, lane, tag2))) {
                        need = false;
                        arrive_many(BAR(B_MOD + warp), bar_count(B_MOD));
                    }
                }
                if (it == 0) {
                    mbar_wait(BAR(B_F1), 0);
                    ldsm4(r[0], r[1], r[2], r[3], sb + OFF_RING + (warp * 16 + (lane & 15)) * 128u + ((((lane >> 4) ^ lane) & 7) << 4));
                }
                if (__all_sync(0xffffffffu, st[0].w == tag && st[1].w == tag) && !need) break;
            }
            m2[0] = st[0].x; ri0.hi = st[0].y; ri0.lo = st[0].z; m2[1] = st[1].x; ri1.hi = st[1].y; ri1.lo = st[1].z;
            arrive_one(BAR(B_STFREE));
        }
        const int lane = lane_id(), g = lane >> 2, c = lane & 3;
        const int srow = warp * 16 + (lane & 15);
        const uint32_t aoff = srow * 128u + ((((lane >> 4) ^ srow) & 7) << 4);
        uint32_t pt[16], qf[32];
        float pp[2][16];
        const uint32_t roff = srow * 128u + ((lane & 7) << 4);
        {
            float accKV[128], accQ[64];
            {
                uint32_t f[2][4];
                mbar_wait(BAR(B_MOD), 0);
                uint4 md = lds128(sb + OFF_MODS + c * 16);
                int s = 0, sp = 1, par = 0;
                #pragma unroll 1
                for (int j = 0; j < 16; j++) {
                    const int sn = s == 0 ? 2 : s - 1;
                    par ^= s == 1;
                    const uint32_t modb = (wgi && j == 15) ? BAR(B_TURN) : BAR(B_MOD + ((j + 1) & 15));
                    const uint64_t db = mk_desc(sb + OFF_RING + s * 65536u + 16384u, 8192, 1024, 1);
                    #pragma unroll
                    for (int ks = 0; ks < 4; ks++) {
                        uint32_t (&ff)[4] = f[ks & 1];
                        ff[0] = ln_pair(r[0], m2[0], ri0, md.x, md.z); ff[1] = ln_pair(r[1], m2[1], ri1, md.x, md.z);
                        ff[2] = ln_pair(r[2], m2[0], ri0, md.y, md.w); ff[3] = ln_pair(r[3], m2[1], ri1, md.y, md.w);
                        const int kn = (ks + 1) & 3;
                        ldsm4(r[0], r[1], r[2], r[3], sb + OFF_RING + (ks == 3 ? sn : s) * 65536u + (aoff ^ (kn << 5)));
                        md = lds128(sb + OFF_MODS + ((ks == 3 ? j + 1 : j) * 4 + kn) * 64 + c * 16);
                        wg_fence();
                        wgmma_n256_rs<1>(accKV, ff[0], ff[1], ff[2], ff[3], desc_add(db, 16384 + ks * 2048), ks ? 1 : j);
                        wgmma_n128_rs<1>(accQ, ff[0], ff[1], ff[2], ff[3], desc_add(db, ks * 2048), ks ? 1 : j);
                        wg_commit();
                        if (ks == 3) arrive_if(BAR(B_TURN), j == 15 && !wgi);
                        if (ks == 1) mbar_wait(modb, 0);
                        if (ks == 2) mbar_wait(BAR(j < 15 ? B_F1 + sn : B_WPHI), j < 15 ? par : 0);
                        wg_wait<1>();
                        if (ks == 0) arrive_if(BAR(B_E1 + sp), j);
                    }
                    sp = s; s = sn;
                }
            }
            mbar_wait(BAR(B_E1 + 2), 0);
            wg_wait<0>();
            acc_fence(accKV); acc_fence(accQ);
            arrive_one(BAR(B_E1));
            uint32_t kf[32];
            #pragma unroll
            for (int h = 0; h < 4; h++) {
                if (h == 1) {
                    #pragma unroll
                    for (int i = 0; i < 16; i++) kf[i] = pack2(accKV[2 * i], accKV[2 * i + 1]);
                    phi_issue(pp, kf, sb, 0);
                }
                #pragma unroll
                for (int q = 0; q < 2; q++) {
                    const int o = 64 + 16 * h + 8 * q;
                    stsm4(sb + OFF_V + h * 8192u + srow * 64u + (((2 * q + (lane >> 4)) ^ ((srow >> 1) & 3)) << 4),
                          pack2(accKV[o], accKV[o + 1]), pack2(accKV[o + 2], accKV[o + 3]), pack2(accKV[o + 4], accKV[o + 5]), pack2(accKV[o + 6], accKV[o + 7]));
                }
            }
            #pragma unroll
            for (int i = 16; i < 32; i++) kf[i] = pack2(accKV[2 * i], accKV[2 * i + 1]);
            phi_transpose(pp, pt, sb + OFF_PHI0 + aoff, sb + OFF_PHI0 + (roff ^ ((lane >> 4) << 6)));
            phi_issue(pp, kf + 16, sb, 1);
            #pragma unroll
            for (int i = 0; i < 32; i++) qf[i] = pack2(accQ[2 * i], accQ[2 * i + 1]);
        }
        reg_dec<CREG>();
        {
            float cp, cn;
            fm_extrema(pt, cp, cn);
            #pragma unroll 1
            for (int u = 0; u < 4; u++) {
                const uint32_t cur = sb + ((u & 1) ? OFF_PHI1 : OFF_PHI0);
                float e[64], s[4];
                uint32_t pn[16];
                #pragma unroll
                for (int k = 0; k < 16; k++) {
                    if (k == KW) {
                        stsf(cur + aoff, e[31 + 2 * k]);
                        phi_transpose(pp, pn, cur + aoff, cur + (roff ^ ((lane >> 4) << 6)));
                    }
                    const float dep = k >= DEP ? e[33 + 2 * (k >= DEP ? k - DEP : 0)] : 0.f, f0 = bf_lo_after(pt[k], dep), f1 = bf_hi_after(pt[k], dep);
                    e[2 * k] = ex2(fmaf(f0, LOG2E, cp)); e[2 * k + 1] = ex2(fmaf(f1, LOG2E, cp));
                    e[32 + 2 * k] = ex2(fmaf(f0, -LOG2E, cn)); e[33 + 2 * k] = ex2(fmaf(f1, -LOG2E, cn));
                    if (k == 0) { s[0] = e[0]; s[1] = e[1]; s[2] = e[32]; s[3] = e[33]; }
                    else { s[0] += e[2 * k]; s[1] += e[2 * k + 1]; s[2] += e[32 + 2 * k]; s[3] += e[33 + 2 * k]; }
                }
                fm_extrema(pn, cp, cn);
                #pragma unroll
                for (int i = 0; i < 16; i++) pt[i] = pn[i];
                const float sp = s[0] + s[1], sn = s[2] + s[3], r = rcp(sp * sn), rp = r * sn, rn = r * sp;
                #pragma unroll
                for (int i = 0; i < 8; i++) {
                    const float q = i < 4 ? rp : rn;
                    sts128((cur + (lane >> 4) * 16384u + roff) ^ (i << 4), make_uint4(pack2(e[8 * i] * q, e[8 * i + 1] * q), pack2(e[8 * i + 2] * q, e[8 * i + 3] * q),
                                                                                   pack2(e[8 * i + 4] * q, e[8 * i + 5] * q), pack2(e[8 * i + 6] * q, e[8 * i + 7] * q)));
                }
                __syncwarp();
                arrive_one(BAR(B_PHI + u));
                if (u == 0) { mbar_wait(BAR(B_E1 + 1), 0); phi_issue(pp, qf, sb, 0); }
                else {
                    mbar_wait(BAR(B_KVD + (u != 1)), 0);
                    if (u == 1) phi_issue(pp, qf + 16, sb, 1);
                }
            }
            wg_wait<0>();
        }
        uint32_t x2[16][2], wf[32][4];
        const uint32_t woff = ((lane >> 3) & 1) * 16384u + ((lane & 7) + ((lane >> 4) << 3)) * 128u + (((warp ^ lane) & 7) << 4);
        mbar_wait(BAR(B_S0), 0);
        #pragma unroll
        for (int q = 0; q < 8; q++) {
            ldsm4(x2[2 * q][0], x2[2 * q][1], x2[2 * q + 1][0], x2[2 * q + 1][1], sb + OFF_XT + (q >> 2) * 16384u + (aoff ^ ((q & 3) << 5)));
            ldsm4t(wf[q][0], wf[q][1], wf[q][2], wf[q][3], sb + OFF_GA + q * 2048u + woff);
        }
        __syncwarp();
        arrive_one(BAR(B_S0FREE));
        float acc[64];
        const uint64_t da0 = mk_desc(sb + OFF_DA + wgi * 8192u, 16, 1024, 1), db0 = mk_desc(sb + OFF_DB, 8192, 1024, 1);
        #pragma unroll 1
        for (int pp = 0; pp < 2; pp++) {
            float o0[20], o1[20];
            const uint64_t dk = mk_desc(sb + OFF_SP + pp * 8192u, OFF_Z - OFF_SP - pp * 8160u, 512, 2);
            const uint64_t dq = mk_desc(sb + (pp ? OFF_PHI1 : OFF_PHI0) + wgi * 8192u, 16, 1024, 1);
            mbar_wait(BAR(B_FB + 4 + pp), 0);
            mbar_wait(BAR(B_PHI + 2 + pp), 0);
            mbar_wait(BAR(B_KVF + pp), 0);
            fence_async_smem();
            wg_fence();
            #pragma unroll
            for (int ks = 0; ks < 4; ks++) {
                wgmma_n40_ss<0, 1>(o0, desc_add(dq, ks * 32), desc_add(dk, ks * 1024), ks);
                wgmma_n40_ss<0, 1>(o1, desc_add(dq, 16384 + ks * 32), desc_raw(dk, 256 + ks * 64 - (255 << 16)), ks);
            }
            wg_commit();
            wg_wait<0>();
            acc_fence(o0); acc_fence(o1);
            arrive_if(BAR(B_ED), pp);
            uint32_t op[16];
            #pragma unroll
            for (int hh = 0; hh < 2; hh++) {
                const float (&o)[20] = hh ? o1 : o0;
                const Recip rd0 = split_recip(rcp(rbf(rbf(o[16]) + 1e-6f)));
                const Recip rd1 = split_recip(rcp(rbf(rbf(o[18]) + 1e-6f)));
                #pragma unroll
                for (int j = 0; j < 4; j++) { op[8 * hh + 2 * j] = hdiv2(pack2(o[4 * j], o[4 * j + 1]), rd0); op[8 * hh + 2 * j + 1] = hdiv2(pack2(o[4 * j + 2], o[4 * j + 3]), rd1); }
                #pragma unroll
                for (int q = 2 * hh; q < 2 * hh + 2; q++) stsm4(sb + OFF_OWN + pp * 16384u + (aoff ^ (q << 5)), op[4 * q], op[4 * q + 1], op[4 * q + 2], op[4 * q + 3]);
            }
            __syncwarp();
            arrive_one(BAR(B_OWN + pp));
            wg_fence();
            #pragma unroll
            for (int ks = 0; ks < 4; ks++) wgmma_n128_rs<1>(acc, op[4 * ks], op[4 * ks + 1], op[4 * ks + 2], op[4 * ks + 3], desc_add(db0, (4 + pp) * 16384u + ks * 2048), ks ? 1 : pp);
            wg_commit();
        }
        const uint32_t ooff = sb + OFF_OUT + (srow >> 3) * 1024u + aoff;
        {
            const uint32_t vchk = lane * 32u + g * 4u;
            #pragma unroll 1
            for (int n = 2; n < 16; n++) {
                const uint32_t s = (SLOT_A >> (4 * n)) & 7, sB = (SLOT_B >> (4 * n)) & 7;
                mbar_wait(BAR(B_FB + sB), (PAR_B >> n) & 1);
                mbar_wait(BAR(B_FA + s), (PAR_A >> n) & 1);
                {
                    const uint32_t ra = sb + OFF_DA + s * 16384u + warp * 2048u;
                    if (__any_sync(0xffffffffu, max(lds32(ra + vchk), lds32(ra + vchk + 1024)) == EMPTY)) {
                        #pragma unroll 1
                        for (int i = 0; i < 4; i++) {
                            uint4 v;
                            #pragma unroll 1
                            for (int it = 0; it < POLL_MAX; it++) {
                                v = ld_ll(p.s->os + (rb * 16 + d_block(hg, n)) * 1024 + warp * 128 + i * 32 + lane);
                                if (umax4(v) != EMPTY) break;
                            }
                            sts128(ra + i * 512 + lane * 16, v);
                        }
                        fence_async_smem();
                        __syncwarp();
                    }
                }
                const uint64_t da = desc_add(da0, s * 16384u), db = desc_add(db0, sB * 16384u);
                wg_fence();
                #pragma unroll
                for (int ks = 0; ks < 4; ks++) wgmma_n128_ss<0, 1>(acc, desc_add(da, ks * 32), desc_add(db, ks * 2048), 1);
                wg_commit();
                wg_wait<1>();
                arrive_one(BAR(B_ED - 1 + n));
            }
            mbar_wait(BAR(B_PAR), 0);
            uint32_t gar[16], bfr[16];
            #pragma unroll
            for (int j = 0; j < 16; j += 4) {
                ldsm4(gar[j], gar[j + 1], gar[j + 2], gar[j + 3], sb + OFF_PAR + 768 + (j + (lane >> 3)) * 16);
                ldsm4(bfr[j], bfr[j + 1], bfr[j + 2], bfr[j + 3], sb + OFF_BQ + ((lane & 1) ? (j + (lane >> 3)) * 16 : 272));
            }
            wg_wait<0>();
            acc_fence(acc);
            bar_arrive(6 + wgi, 256);
            float sd[2][4], q1[2][4], q2[2][4];
            #pragma unroll
            for (int e = 0; e < 4; e++) { sd[0][e] = sd[1][e] = q1[0][e] = q1[1][e] = q2[0][e] = q2[1][e] = 0.f; }
            #pragma unroll
            for (int s = 0; s < 8; s++) {
                #pragma unroll
                for (int e = 0; e < 4; e++) { const int j = 2 * s + (e >> 1), h = e & 1; x2[j][h] = hadd2(x2[j][h], hmul2(gar[j], pack2(acc[4 * j + 2 * h], acc[4 * j + 2 * h + 1]))); }
                mma16816(sd[s & 1], x2[2 * s][0], x2[2 * s][1], x2[2 * s + 1][0], x2[2 * s + 1][1], bfr[2 * s], bfr[2 * s + 1]);
                #pragma unroll
                for (int e = 0; e < 2; e++) { mma1688(q1[e], x2[2 * s + e][0], x2[2 * s + e][1], x2[2 * s + e][0]); mma1688(q2[e], x2[2 * s + e][0], x2[2 * s + e][1], x2[2 * s + e][1]); }
            }
            if (c == (g >> 1)) {
                uint4* d = p.s->st2 + rb * 128 + warp * 16 + g;
                red_add4(d, sd[0][0] + sd[1][0], (g & 1) ? q1[0][1] + q1[1][1] : q1[0][0] + q1[1][0], sd[0][1] + sd[1][1], 1.0f);
                red_add4(d + 8, sd[0][2] + sd[1][2], (g & 1) ? q2[0][3] + q2[1][3] : q2[0][2] + q2[1][2], sd[0][3] + sd[1][3], 1.0f);
            }
            arrive_one(BAR(B_RED));
            bar_sync(7 - wgi, 256);
            #pragma unroll
            for (int q = 0; q < 8; q++) stsm4((ooff + (q >> 2) * 1024u) ^ ((q & 3) << 5), x2[2 * q][0], x2[2 * q][1], x2[2 * q + 1][0], x2[2 * q + 1][1]);
            __syncwarp();
            arrive_one(BAR(B_X2));
        }
        const uint32_t xa = sb + OFF_OUT + warp * 4096u + ((lane >> 3) & 1) * 1024u + (lane >> 4) * 128u + (((lane ^ (lane >> 4)) & 7) << 4);
        const uint4 pa = lds128(sb + OFF_PAR + (lane & 15) * 16), ps = lds128(sb + OFF_PAR + 256 + (lane & 15) * 16), pg = lds128(sb + OFF_PAR + 512 + (lane & 15) * 16);
        if (ffn) mbar_wait(BAR(B_GU), 0);
        #pragma unroll
        for (int q = 8; q < 32; q++) ldsm4t(wf[q][0], wf[q][1], wf[q][2], wf[q][3], sb + (q < 16 ? OFF_GB : q < 24 ? OFF_UP0 : OFF_UP1) + (q & 7) * 2048u + woff);
        {
            mbar_wait(BAR(B_ST2), 0);
            #pragma unroll 1
            for (int q0 = 0; q0 < 2; q0++) {
                uint4 x[4]; uint2 st[4];
                const uint32_t a = xa + q0 * 2048u;
                #pragma unroll
                for (int q = 0; q < 4; q++) { x[q] = lds128((a + q * 256u) ^ (q << 5)); st[q] = lds64(sb + OFF_ST2 + (warp * 16 + q0 * 8 + q * 2 + (lane >> 4)) * 8); }
                #pragma unroll
                for (int q = 0; q < 4; q++) {
                    const Recip r = split_recip(__uint_as_float(st[q].y));
                    sts128((a + q * 256u) ^ (q << 5), make_uint4(
                        hadd2(x[q].x, hmul2(pg.x, ln_pair(x[q].x, st[q].x, r, pa.x, ps.x))), hadd2(x[q].y, hmul2(pg.y, ln_pair(x[q].y, st[q].x, r, pa.y, ps.y))),
                        hadd2(x[q].z, hmul2(pg.z, ln_pair(x[q].z, st[q].x, r, pa.z, ps.z))), hadd2(x[q].w, hmul2(pg.w, ln_pair(x[q].w, st[q].x, r, pa.w, ps.w)))));
                }
            }
            __syncwarp();
            arrive_one(BAR(B_OUTW));
        }
        if (ffn) {
            float acc[4][4];
            uint32_t df[4][4][4];
            {
                #pragma unroll
                for (int i = 0; i < 4; i++) { acc[i][0] = acc[i][1] = acc[i][2] = acc[i][3] = 0.f; }
                const uint32_t da = sb + (wgi ? OFF_DN1 : OFF_DN0) + w4 * 8192u + ((lane & 7) + ((lane >> 4) << 3)) * 128u;
                mbar_wait(BAR(B_WD), 0);
                #pragma unroll
                for (int q = 0; q < DNE; q++)
                    ldsm4t(df[q >> 2][q & 3][0], df[q >> 2][q & 3][1], df[q >> 2][q & 3][2], df[q >> 2][q & 3][3], da + (q & 3) * 2048u + (((2 * (q >> 2) + ((lane >> 3) & 1)) ^ (lane & 7)) << 4));
                mbar_wait(BAR(B_ROWS), 0);
                #pragma unroll
                for (int q = 0; q < 8; q++) {
                    uint32_t b0, b1, b2, b3;
                    ldsm4(b0, b1, b2, b3, sb + OFF_ROWS + (lane & 7) * 528u + (lane >> 3) * 16u + q * 64u);
                    #pragma unroll
                    for (int hf = 0; hf < 2; hf++) {
                        const int k = 16 * hf + 2 * q;
                        mma16816(acc[2 * hf], wf[k][0], wf[k][1], wf[k][2], wf[k][3], b0, b1);
                        mma16816(acc[2 * hf + 1], wf[k + 1][0], wf[k + 1][1], wf[k + 1][2], wf[k + 1][3], b2, b3);
                    }
                }
                const float gs = (acc[0][0] + acc[1][0]) + (acc[2][1] + acc[3][1]), us = (acc[0][2] + acc[1][2]) + (acc[2][3] + acc[3][3]);
                st_partner64(sb + OFF_PX + warp * 256 + lane * 8, BAR(B_PX), rank ^ 1, gs, us);
                #pragma unroll
                for (int q = DNE; q < 16; q++)
                    ldsm4t(df[q >> 2][q & 3][0], df[q >> 2][q & 3][1], df[q >> 2][q & 3][2], df[q >> 2][q & 3][3], da + (q & 3) * 2048u + (((2 * (q >> 2) + ((lane >> 3) & 1)) ^ (lane & 7)) << 4));
                mbar_wait(BAR(B_SEL), 0);
                const uint32_t tok = lds32(sb + OFF_SEL + 48 + c * 4);
                mbar_wait(BAR(B_PX), 0);
                const uint2 q = lds64(sb + OFF_PX + warp * 256 + lane * 8);
                float gt = rbf(gs + __uint_as_float(q.x));
                gt = rbf(gt * sigmoidf(gt));
                if (tok < 2) sts16(sb + OFF_HID + tok * 144 + (warp * 8 + g) * 2, pack2(gt * rbf(us + __uint_as_float(q.y)), 0.f));
            }
            bar_sync(1, 256);
            uint32_t bh[8];
            ldsm4(bh[0], bh[1], bh[2], bh[3], sb + OFF_HID + (lane & 1) * 144u + (lane >> 3) * 16u);
            ldsm4(bh[4], bh[5], bh[6], bh[7], sb + OFF_HID + (lane & 1) * 144u + (lane >> 3) * 16u + 64u);
            float y[4][4];
            #pragma unroll
            for (int tt = 0; tt < 4; tt++) { y[tt][0] = y[tt][1] = y[tt][2] = y[tt][3] = 0.f; }
            #pragma unroll
            for (int ks = 0; ks < 4; ks++)
                #pragma unroll
                for (int tt = 0; tt < 4; tt++) mma16816(y[tt], df[tt][ks][0], df[tt][ks][1], df[tt][ks][2], df[tt][ks][3], bh[2 * ks], bh[2 * ks + 1]);
            float e[4];
            #pragma unroll
            for (int i = 0; i < 4; i++) e[i] = (c & 2) ? ((c & 1) ? y[3][i] : y[2][i]) : ((c & 1) ? y[1][i] : y[0][i]);
            char* d = (char*)(p.s->yp + pr * 512 + rank * 128 + (warp * 4 + c) * 4) + g * 8;
            st_ll8(d, __float_as_uint(e[0]), low_bits(e[2], tag2));
            st_ll8(d + 4096, __float_as_uint(e[1]), low_bits(e[3], tag2));
            arrive_one(BAR(B_YP));
        }
    }
}

typedef CUresult (*EncodeFn)(CUtensorMap*, CUtensorMapDataType, cuuint32_t, void*, const cuuint64_t*, const cuuint64_t*, const cuuint32_t*,
                             const cuuint32_t*, CUtensorMapInterleave, CUtensorMapSwizzle, CUtensorMapL2promotion, CUtensorMapFloatOOBfill);

CUtensorMap make_map(EncodeFn enc, const void* ptr, uint64_t cols, uint64_t rows, uint32_t bc, uint32_t br, CUtensorMapSwizzle swz, CUtensorMapL2promotion promo) {
    CUtensorMap m;
    cuuint64_t dims[2] = {cols, rows}, strides[1] = {cols * 2};
    cuuint32_t box[2] = {bc, br}, es[2] = {1, 1};
    enc(&m, CU_TENSOR_MAP_DATA_TYPE_BFLOAT16, 2, const_cast<void*>(ptr), dims, strides, box, es, CU_TENSOR_MAP_INTERLEAVE_NONE, swz, promo,
        CU_TENSOR_MAP_FLOAT_OOB_FILL_NONE);
    return m;
}
CUtensorMap make_block_map(EncodeFn enc, const void* ptr, uint32_t sections, uint64_t rows, uint32_t br, CUtensorMapL2promotion promo) {
    CUtensorMap m;
    cuuint64_t dims[4] = {64, rows, 16, sections}, strides[3] = {sections * 2048ull, 128, 2048};
    cuuint32_t box[4] = {64, br, 2, sections}, es[4] = {1, 1, 1, 1};
    enc(&m, CU_TENSOR_MAP_DATA_TYPE_BFLOAT16, sections > 1 ? 4 : 3, const_cast<void*>(ptr), dims, strides, box, es, CU_TENSOR_MAP_INTERLEAVE_NONE,
        CU_TENSOR_MAP_SWIZZLE_128B, promo, CU_TENSOR_MAP_FLOAT_OOB_FILL_NONE);
    return m;
}

}

extern "C" void kernel_launch(void* const* d_in, const int* in_sizes, int n_in, void* d_out, int out_size) {
    (void)in_sizes; (void)n_in; (void)out_size;
    void* fn = nullptr; cudaDriverEntryPointQueryResult qr;
    cudaGetDriverEntryPoint("cuTensorMapEncodeTiled", &fn, cudaEnableDefault, &qr);
    EncodeFn enc = (EncodeFn)fn;
    void* hs = nullptr;
    cudaGetSymbolAddress(&hs, g_scratch);
    const CUtensorMapL2promotion P256 = CU_TENSOR_MAP_L2_PROMOTION_L2_256B, P128 = CU_TENSOR_MAP_L2_PROMOTION_L2_128B;
    CUtensorMap tmW = make_block_map(enc, d_in[1], 3, 1024, 64, P256);
    CUtensorMap tmWo = make_block_map(enc, d_in[3], 1, 1024, 64, P256);
    CUtensorMap tmPhi = make_map(enc, d_in[2], 32, 1024, 32, 128, CU_TENSOR_MAP_SWIZZLE_64B, P128);
    CUtensorMap tmG = make_map(enc, d_in[6], 3584, 1024, 64, 128, CU_TENSOR_MAP_SWIZZLE_128B, P128);
    CUtensorMap tmU = make_map(enc, d_in[7], 3584, 1024, 64, 128, CU_TENSOR_MAP_SWIZZLE_128B, P128);
    CUtensorMap tmD = make_block_map(enc, d_in[8], 1, 3584, 64, P128);
    CUtensorMap tmX = make_map(enc, d_in[0], 1024, 2048, 64, 128, CU_TENSOR_MAP_SWIZZLE_128B, P128);
    CUtensorMap tmO = make_block_map(enc, d_out, 1, 2048, 8, P128);
    CUtensorMap tmM = make_map(enc, d_in[10], 6144, 1024, 64, 64, CU_TENSOR_MAP_SWIZZLE_128B, P128);
    CUtensorMap tmR = make_map(enc, d_in[10], 6144, 1024, 32, 64, CU_TENSOR_MAP_SWIZZLE_NONE, P128);
    CUtensorMap tmG8 = make_map(enc, d_in[6], 3584, 1024, 8, PRG, CU_TENSOR_MAP_SWIZZLE_NONE, P128);
    CUtensorMap tmU8 = make_map(enc, d_in[7], 3584, 1024, 8, PRG, CU_TENSOR_MAP_SWIZZLE_NONE, P128);
    CUtensorMap tmD8;
    {
        cuuint64_t dims[3] = {64, 16, 3584}, strides[2] = {128, 2048};
        cuuint32_t box[3] = {8, 8, PRD}, es[3] = {1, 1, 1};
        enc(&tmD8, CU_TENSOR_MAP_DATA_TYPE_BFLOAT16, 3, d_in[8], dims, strides, box, es, CU_TENSOR_MAP_INTERLEAVE_NONE, CU_TENSOR_MAP_SWIZZLE_NONE, P128,
            CU_TENSOR_MAP_FLOAT_OOB_FILL_NONE);
    }
    Ptrs p;
    p.x = (const bf16*)d_in[0]; p.c = (const bf16*)d_in[9]; p.wmod = (const bf16*)d_in[10]; p.wr = (const bf16*)d_in[5];
    p.out = (bf16*)d_out; p.s = (Scratch*)hs;
    p.wqkv = (const bf16*)d_in[1]; p.wo = (const bf16*)d_in[3];
    cudaFuncSetAttribute(fused_kernel, cudaFuncAttributeMaxDynamicSharedMemorySize, SMEM_BYTES);
    fused_kernel<<<128, NTHREADS, SMEM_BYTES, cudaStreamPerThread>>>(p, tmW, tmWo, tmPhi, tmG, tmU, tmD, tmX, tmO, tmM, tmR, tmG8, tmU8, tmD8);
}
```

```cpp
#include <cuda_runtime.h>
#include <cuda.h>
#include <cuda_bf16.h>
#include <stdint.h>

namespace {

typedef __nv_bfloat16 bf16;

constexpr int NTHREADS = 384;
constexpr int POLL_MAX = 400000;
constexpr uint32_t EMPTY = 0xffffffffu;

constexpr int PND = 6;
constexpr int PNG = 5;
constexpr int PRD = (64 + PND - 1) / PND, PRG = (384 + PNG - 1) / PNG;
constexpr uint32_t OFF_RING = 0;
constexpr uint32_t OFF_XS   = 65536;
constexpr uint32_t OFF_WST  = 98304;
constexpr uint32_t OFF_XT   = 0;
constexpr uint32_t OFF_GA   = 32768;
constexpr uint32_t OFF_PHI0 = 163840, OFF_PHI1 = 98304;
constexpr uint32_t OFF_V    = 131072;
constexpr uint32_t OFF_KVS  = 131072;
constexpr uint32_t OFF_DB   = 0;
constexpr uint32_t OFF_DA   = 98304;
constexpr uint64_t SLOT_A   = 0x5432105432105432ull, SLOT_B = 0x1054321054321054ull;
constexpr uint32_t PAR_A    = 0x3f00, PAR_B = 0x0fc0;
constexpr uint32_t OFF_OWN  = OFF_DA + 32768;
constexpr uint32_t OFF_OUT  = OFF_DA + 65536;
constexpr uint32_t OFF_UP0  = OFF_DA, OFF_UP1 = OFF_DB + 32768, OFF_DN0 = OFF_DA + 32768, OFF_DN1 = OFF_DB + 65536;
constexpr uint32_t OFF_WPHI = 196608;
constexpr uint32_t OFF_SP   = 204800;
constexpr uint32_t OFF_Z    = 221184;
constexpr uint32_t OFF_ONES = 225280;
constexpr uint32_t OFF_MODS = 226304;
constexpr uint32_t OFF_GB   = 196608;
constexpr uint32_t OFF_BQ   = 229376;
constexpr uint32_t OFF_ATOT = OFF_BQ + 256;
constexpr uint32_t OFF_BAR  = 230400;
constexpr uint32_t OFF_SEEN = OFF_BAR + 632;
constexpr uint32_t OFF_PAR  = OFF_BAR + 640;
constexpr uint32_t SMEM_BYTES = 232448;
constexpr uint32_t OFF_SILU = OFF_Z;
constexpr uint32_t OFF_RED0 = OFF_Z + 2048;
constexpr uint32_t OFF_DUMMY = OFF_RED0 + 512;
constexpr uint32_t OFF_ST2  = OFF_DB;
constexpr uint32_t OFF_SEL  = OFF_ST2 + 1024;
constexpr uint32_t OFF_ROWS = OFF_ST2 + 2048;
constexpr uint32_t OFF_PX   = OFF_ROWS + 4608;
constexpr uint32_t OFF_HID  = OFF_PX + 2048;

enum {
    B_F1 = 0, B_E1 = 3, B_STFREE = 6, B_WPHI = 7, B_FA = 8, B_FB = 14, B_RF = 20, B_KVD = 24, B_PAR = 26, B_S0 = 27, B_GU = 28, B_WD = 29,
    B_X2 = 30, B_ST2 = 31, B_CAND = 32, B_TURN = 33,
    B_MP = 34, B_MOD = 35, B_PX = 51, B_S0FREE = 52, B_PHI = 53, B_OUTW = 57, B_PUB = 58, B_KVF = 59, B_OWN = 61, B_REL = 63, B_ROWS = 64,
    B_SEL = 65, B_YP = 66, B_RED = 67,
    B_XS = 68,
    B_WS = 72, B_COUNT = 76,
    B_ED = B_MOD, B_PF = B_XS + 3, B_KVS = B_RF
};

struct Scratch {
    uint4 kvf[32 * 288];
    uint4 st1[2048];
    uint4 mp[128 * 16];
    uint4 rest[1024];
    uint4 flo[256 * 2];
    uint4 st2[2048];
    uint4 cand[64 * 2];
    uint4 rowh[128 * 128];
    uint4 rowx[128 * 128];
    uint4 rsc[64 * 8 * 2];
    uint4 yp[56 * 512];
    unsigned done[256];
    uint4 kvp[32 * 256 * 32];
    uint4 os[256 * 1024];
};
__device__ __align__(1024) Scratch g_scratch;

__device__ __forceinline__ uint32_t smem_u32(const void* p) { return (uint32_t)__cvta_generic_to_shared(p); }
__device__ __forceinline__ int lane_id() { int l; asm volatile("mov.u32 %0, %%laneid;" : "=r"(l)); return l; }
__device__ __forceinline__ uint32_t clk32() { uint32_t c; asm volatile("mov.u32 %0, %%clock;" : "=r"(c) :: "memory"); return c; }
__device__ __forceinline__ void arrive_one(uint32_t bar) {
    asm volatile("{\n.reg .pred p;\nelect.sync _|p, 0xffffffff;\n@p mbarrier.arrive.shared::cta.b64 _, [%0];\n}" :: "r"(bar) : "memory");
}
__device__ __forceinline__ void arrive_many(uint32_t bar, uint32_t n) {
    asm volatile("{\n.reg .pred p;\nelect.sync _|p, 0xffffffff;\n@p mbarrier.arrive.shared::cta.b64 _, [%0], %1;\n}" :: "r"(bar), "r"(n) : "memory");
}
__device__ __forceinline__ void arrive_if(uint32_t bar, uint32_t on) {
    asm volatile("{\n.reg .pred q, p;\nelect.sync _|q, 0xffffffff;\nsetp.ne.and.u32 p, %1, 0, q;\n@p mbarrier.arrive.shared::cta.b64 _, [%0];\n}" :: "r"(bar), "r"(on) : "memory");
}
__device__ __forceinline__ void st_partner64(uint32_t a, uint32_t bar, uint32_t cta, float x, float y) {
    asm volatile("{\n.reg .b32 ra, rb;\nmapa.shared::cluster.u32 ra, %0, %2;\nmapa.shared::cluster.u32 rb, %1, %2;\n"
        "st.async.weak.shared::cluster.mbarrier::complete_tx::bytes.v2.f32 [ra], {%3, %4}, [rb];\n}" :: "r"(a), "r"(bar), "r"(cta), "f"(x), "f"(y) : "memory");
}
__device__ __forceinline__ void mbar_wait(uint32_t bar, uint32_t parity) {
    asm volatile("{\n.reg .pred P1;\n.reg .u32 cnt;\nmbarrier.try_wait.parity.shared::cta.b64 P1, [%0], %1;\n@P1 bra DONE;\nmov.u32 cnt, 0;\nLAB_WAIT:\n"
        "mbarrier.try_wait.parity.shared::cta.b64 P1, [%0], %1;\n@P1 bra DONE;\n"
        "add.u32 cnt, cnt, 1;\nsetp.lt.u32 P1, cnt, 1000000;\n@P1 bra LAB_WAIT;\ntrap;\nDONE:\n}" :: "r"(bar), "r"(parity) : "memory");
}
__device__ __forceinline__ uint64_t policy_evict_first() { uint64_t p; asm("createpolicy.fractional.L2::evict_first.b64 %0, 1.0;" : "=l"(p)); return p; }
__device__ __forceinline__ void bulk_commit() { asm volatile("cp.async.bulk.commit_group;" ::: "memory"); }
__device__ __forceinline__ void bulk_wait() { asm volatile("cp.async.bulk.wait_group 0;" ::: "memory"); }
__device__ __forceinline__ void tmap_prefetch(const CUtensorMap* tm) { asm volatile("prefetch.tensormap [%0];" :: "l"(tm) : "memory"); }
#define EL "{\n.reg .pred e;\nelect.sync _|e, 0xffffffff;\n@e "
__device__ __forceinline__ void expect_tx_e(uint32_t bar, uint32_t bytes) { asm volatile(EL "mbarrier.arrive.expect_tx.shared::cta.b64 _, [%0], %1;\n}" :: "r"(bar), "r"(bytes) : "memory"); }
__device__ __forceinline__ void tma2_e(uint32_t dst, const CUtensorMap* tm, int c0, int c1, uint32_t bar) {
    asm volatile(EL "cp.async.bulk.tensor.2d.shared::cluster.global.mbarrier::complete_tx::bytes [%0], [%1, {%3, %4}], [%2];\n}"
        :: "r"(dst), "l"(tm), "r"(bar), "r"(c0), "r"(c1) : "memory");
}
__device__ __forceinline__ void tma2_ef_e(uint32_t dst, const CUtensorMap* tm, int c0, int c1, uint32_t bar) {
    asm volatile(EL "cp.async.bulk.tensor.2d.shared::cluster.global.mbarrier::complete_tx::bytes.L2::cache_hint [%0], [%1, {%3, %4}], [%2], %5;\n}"
        :: "r"(dst), "l"(tm), "r"(bar), "r"(c0), "r"(c1), "l"(policy_evict_first()) : "memory");
}
__device__ __forceinline__ void tma3_e(uint32_t dst, const CUtensorMap* tm, int c1, int c2, uint32_t bar) {
    asm volatile(EL "cp.async.bulk.tensor.3d.shared::cluster.global.mbarrier::complete_tx::bytes [%0], [%1, {0, %3, %4}], [%2];\n}"
        :: "r"(dst), "l"(tm), "r"(bar), "r"(c1), "r"(c2) : "memory");
}
__device__ __forceinline__ void tma3_ef_e(uint32_t dst, const CUtensorMap* tm, int row, int blk, uint32_t bar) {
    asm volatile(EL "cp.async.bulk.tensor.3d.shared::cluster.global.mbarrier::complete_tx::bytes.L2::cache_hint [%0], [%1, {0, %3, %4}], [%2], %5;\n}"
        :: "r"(dst), "l"(tm), "r"(bar), "r"(row), "r"(blk), "l"(policy_evict_first()) : "memory");
}
__device__ __forceinline__ void tma4_ef_e(uint32_t dst, const CUtensorMap* tm, int row, int blk, uint32_t bar) {
    asm volatile(EL "cp.async.bulk.tensor.4d.shared::cluster.global.mbarrier::complete_tx::bytes.L2::cache_hint [%0], [%1, {0, %3, %4, 0}], [%2], %5;\n}"
        :: "r"(dst), "l"(tm), "r"(bar), "r"(row), "r"(blk), "l"(policy_evict_first()) : "memory");
}
__device__ __forceinline__ void bulk_load_e(uint32_t dst, const void* src, uint32_t bytes, uint32_t bar) {
    asm volatile(EL "cp.async.bulk.shared::cluster.global.mbarrier::complete_tx::bytes [%0], [%1], %2, [%3];\n}" :: "r"(dst), "l"(src), "r"(bytes), "r"(bar) : "memory");
}
__device__ __forceinline__ void bulk_store_e(void* dst, uint32_t src, uint32_t bytes) {
    asm volatile(EL "cp.async.bulk.global.shared::cta.bulk_group [%0], [%1], %2;\n}" :: "l"(dst), "r"(src), "r"(bytes) : "memory");
}
__device__ __forceinline__ void st_flag_e(void* p, unsigned v) { asm volatile(EL "st.relaxed.gpu.global.u32 [%0], %1;\n}" :: "l"(p), "r"(v) : "memory"); }
__device__ __forceinline__ void mbar_init(uint32_t bar, uint32_t cnt) { asm volatile("mbarrier.init.shared::cta.b64 [%0], %1;" :: "r"(bar), "r"(cnt) : "memory"); }
__device__ __forceinline__ bool elect_one() {
    uint32_t p;
    asm volatile("{\n.reg .pred P;\nelect.sync _|P, 0xffffffff;\nselp.u32 %0, 1, 0, P;\n}" : "=r"(p));
    return p;
}
__device__ __forceinline__ void wg_fence() { asm volatile("wgmma.fence.sync.aligned;" ::: "memory"); }
__device__ __forceinline__ void wg_commit() { asm volatile("wgmma.commit_group.sync.aligned;" ::: "memory"); }
template<int N> __device__ __forceinline__ void wg_wait() { asm volatile("wgmma.wait_group.sync.aligned %0;" :: "n"(N) : "memory"); }
template<int N> __device__ __forceinline__ void acc_fence(float (&d)[N]) {
    #pragma unroll
    for (int i = 0; i < N; i++) asm volatile("" : "+f"(d[i]) :: "memory");
}
__device__ __forceinline__ uint64_t mk_desc(uint32_t addr, uint32_t lbo, uint32_t sbo, uint32_t swz) {
    uint32_t lo = ((addr & 0x3FFFF) >> 4) | (((lbo & 0x3FFFF) >> 4) << 16);
    uint32_t hi = (sbo >> 4) | (swz << 30);
    return ((uint64_t)hi << 32) | lo;
}
__device__ __forceinline__ uint64_t desc_add(uint64_t d, uint32_t bytes) { return (d & 0xffffffff00000000ull) | (uint32_t)((uint32_t)d + (bytes >> 4)); }
__device__ __forceinline__ uint64_t desc_raw(uint64_t d, uint32_t inc) { return (d & 0xffffffff00000000ull) | (uint32_t)((uint32_t)d + inc); }
__device__ __forceinline__ void fence_async_smem() { asm volatile("fence.proxy.async.shared::cta;" ::: "memory"); }
__device__ __forceinline__ void bar_sync(int id, int n) { asm volatile("bar.sync %0, %1;" :: "r"(id), "r"(n) : "memory"); }
__device__ __forceinline__ void bar_arrive(int id, int n) { asm volatile("bar.arrive %0, %1;" :: "r"(id), "r"(n) : "memory"); }
template<int R> __device__ __forceinline__ void reg_inc() { asm volatile("setmaxnreg.inc.sync.aligned.u32 %0;" :: "n"(R)); }
template<int R> __device__ __forceinline__ void reg_dec() { asm volatile("setmaxnreg.dec.sync.aligned.u32 %0;" :: "n"(R)); }
__device__ __forceinline__ void cluster_arrive() { asm volatile("barrier.cluster.arrive.relaxed.aligned;" ::: "memory"); }
__device__ __forceinline__ void cluster_wait() { asm volatile("barrier.cluster.wait.acquire.aligned;" ::: "memory"); }

__device__ __forceinline__ void stsm4(uint32_t addr, uint32_t r0, uint32_t r1, uint32_t r2, uint32_t r3) {
    asm volatile("stmatrix.sync.aligned.m8n8.x4.shared.b16 [%0], {%1,%2,%3,%4};" :: "r"(addr), "r"(r0), "r"(r1), "r"(r2), "r"(r3) : "memory");
}
__device__ __forceinline__ void ldsm4(uint32_t& r0, uint32_t& r1, uint32_t& r2, uint32_t& r3, uint32_t addr) {
    asm volatile("ldmatrix.sync.aligned.m8n8.x4.shared.b16 {%0,%1,%2,%3}, [%4];" : "=r"(r0), "=r"(r1), "=r"(r2), "=r"(r3) : "r"(addr) : "memory");
}
__device__ __forceinline__ void ldsm4t(uint32_t& r0, uint32_t& r1, uint32_t& r2, uint32_t& r3, uint32_t addr) {
    asm volatile("ldmatrix.sync.aligned.m8n8.x4.trans.shared.b16 {%0,%1,%2,%3}, [%4];" : "=r"(r0), "=r"(r1), "=r"(r2), "=r"(r3) : "r"(addr) : "memory");
}
__device__ __forceinline__ void mma16816(float (&d)[4], uint32_t a0, uint32_t a1, uint32_t a2, uint32_t a3, uint32_t b0, uint32_t b1) {
    asm("mma.sync.aligned.m16n8k16.row.col.f32.bf16.bf16.f32 {%0,%1,%2,%3}, {%4,%5,%6,%7}, {%8,%9}, {%0,%1,%2,%3};"
        : "+f"(d[0]), "+f"(d[1]), "+f"(d[2]), "+f"(d[3]) : "r"(a0), "r"(a1), "r"(a2), "r"(a3), "r"(b0), "r"(b1));
}
__device__ __forceinline__ void mma1688(float (&d)[4], uint32_t a0, uint32_t a1, uint32_t b0) {
    asm("mma.sync.aligned.m16n8k8.row.col.f32.bf16.bf16.f32 {%0,%1,%2,%3}, {%4,%5}, {%6}, {%0,%1,%2,%3};"
        : "+f"(d[0]), "+f"(d[1]), "+f"(d[2]), "+f"(d[3]) : "r"(a0), "r"(a1), "r"(b0));
}
__device__ __forceinline__ uint4 lds128(uint32_t a) { uint4 v; asm volatile("ld.shared.v4.b32 {%0,%1,%2,%3}, [%4];" : "=r"(v.x), "=r"(v.y), "=r"(v.z), "=r"(v.w) : "r"(a) : "memory"); return v; }
__device__ __forceinline__ uint2 lds64(uint32_t a) { uint2 v; asm volatile("ld.shared.v2.b32 {%0,%1}, [%2];" : "=r"(v.x), "=r"(v.y) : "r"(a) : "memory"); return v; }
__device__ __forceinline__ uint32_t lds32(uint32_t a) { uint32_t v; asm volatile("ld.shared.b32 %0, [%1];" : "=r"(v) : "r"(a) : "memory"); return v; }
__device__ __forceinline__ float ldsf(uint32_t a) { float v; asm volatile("ld.shared.f32 %0, [%1];" : "=f"(v) : "r"(a) : "memory"); return v; }
__device__ __forceinline__ uint32_t lds16(uint32_t a) { uint16_t v; asm volatile("ld.shared.b16 %0, [%1];" : "=h"(v) : "r"(a) : "memory"); return v; }
__device__ __forceinline__ void sts128(uint32_t a, uint4 v) { asm volatile("st.shared.v4.b32 [%0], {%1,%2,%3,%4};" :: "r"(a), "r"(v.x), "r"(v.y), "r"(v.z), "r"(v.w) : "memory"); }
__device__ __forceinline__ void sts64(uint32_t a, uint32_t x, uint32_t y) { asm volatile("st.shared.v2.b32 [%0], {%1,%2};" :: "r"(a), "r"(x), "r"(y) : "memory"); }
__device__ __forceinline__ void sts32(uint32_t a, uint32_t x) { asm volatile("st.shared.b32 [%0], %1;" :: "r"(a), "r"(x) : "memory"); }
__device__ __forceinline__ void stsf(uint32_t a, float x) { asm volatile("st.shared.f32 [%0], %1;" :: "r"(a), "f"(x) : "memory"); }
__device__ __forceinline__ void sts16(uint32_t a, uint32_t x) { asm volatile("st.shared.b16 [%0], %1;" :: "r"(a), "h"((uint16_t)x) : "memory"); }

__device__ __forceinline__ uint4 ldg128(const void* p) { uint4 v; asm volatile("ld.global.nc.v4.b32 {%0,%1,%2,%3}, [%4];" : "=r"(v.x), "=r"(v.y), "=r"(v.z), "=r"(v.w) : "l"(p)); return v; }
__device__ __forceinline__ uint2 ldg64(const void* p) { uint2 v; asm volatile("ld.global.nc.v2.b32 {%0,%1}, [%2];" : "=r"(v.x), "=r"(v.y) : "l"(p)); return v; }
__device__ __forceinline__ void stg128(void* p, uint4 v) { asm volatile("st.global.v4.b32 [%0], {%1,%2,%3,%4};" :: "l"(p), "r"(v.x), "r"(v.y), "r"(v.z), "r"(v.w) : "memory"); }
__device__ __forceinline__ void stg_fill(void* p, uint32_t v) { asm volatile("st.global.v4.b32 [%0], {%1,%1,%1,%1};" :: "l"(p), "r"(v) : "memory"); }
__device__ __forceinline__ void st_ll(void* p, uint32_t x, uint32_t y, uint32_t z, uint32_t w) {
    asm volatile("{\n.reg .b128 t;\n.reg .b64 a, b;\nmov.b64 a, {%1, %2};\nmov.b64 b, {%3, %4};\nmov.b128 t, {a, b};\nst.relaxed.gpu.global.b128 [%0], t;\n}"
        :: "l"(p), "r"(x), "r"(y), "r"(z), "r"(w) : "memory");
}
__device__ __forceinline__ void st_ll_if(void* p, uint32_t x, uint32_t y, uint32_t z, uint32_t w, bool on) {
    asm volatile("{\n.reg .b128 t;\n.reg .b64 a, b;\n.reg .pred q;\nsetp.ne.u32 q, %5, 0;\nmov.b64 a, {%1, %2};\nmov.b64 b, {%3, %4};\nmov.b128 t, {a, b};\n@q st.relaxed.gpu.global.b128 [%0], t;\n}"
        :: "l"(p), "r"(x), "r"(y), "r"(z), "r"(w), "r"((uint32_t)on) : "memory");
}
__device__ __forceinline__ uint4 ld_ll(const void* p) {
    uint4 v;
    asm volatile("{\n.reg .b128 t;\n.reg .b64 a, b;\nld.relaxed.gpu.global.b128 t, [%4];\nmov.b128 {a, b}, t;\nmov.b64 {%0, %1}, a;\nmov.b64 {%2, %3}, b;\n}"
        : "=r"(v.x), "=r"(v.y), "=r"(v.z), "=r"(v.w) : "l"(p) : "memory");
    return v;
}
__device__ __forceinline__ void ld_ll_if(uint4& v, const void* p, bool go) {
    asm volatile("{\n.reg .b128 t;\n.reg .b64 a, b;\n.reg .pred q;\nsetp.ne.u32 q, %5, 0;\nmov.b64 a, {%0, %1};\nmov.b64 b, {%2, %3};\nmov.b128 t, {a, b};\n"
        "@q ld.relaxed.gpu.global.b128 t, [%4];\nmov.b128 {a, b}, t;\nmov.b64 {%0, %1}, a;\nmov.b64 {%2, %3}, b;\n}"
        : "+r"(v.x), "+r"(v.y), "+r"(v.z), "+r"(v.w) : "l"(p), "r"((uint32_t)go) : "memory");
}
__device__ __forceinline__ void st_ll8(void* p, uint32_t x, uint32_t y) {
    asm volatile("{\n.reg .b64 a;\nmov.b64 a, {%1, %2};\nst.relaxed.gpu.global.b64 [%0], a;\n}" :: "l"(p), "r"(x), "r"(y) : "memory");
}
__device__ __forceinline__ void st_ll4(void* p, uint32_t x) { asm volatile("st.relaxed.gpu.global.b32 [%0], %1;" :: "l"(p), "r"(x) : "memory"); }
__device__ __forceinline__ void st_ll4_if(void* p, uint32_t x, bool on) {
    asm volatile("{\n.reg .pred q;\nsetp.ne.u32 q, %2, 0;\n@q st.relaxed.gpu.global.b32 [%0], %1;\n}" :: "l"(p), "r"(x), "r"((uint32_t)on) : "memory");
}
__device__ __forceinline__ unsigned ld_rlx(const void* p) { unsigned v; asm volatile("ld.relaxed.gpu.global.u32 %0, [%1];" : "=r"(v) : "l"(p) : "memory"); return v; }
__device__ __forceinline__ void red_add4_if(void* p, float x, float y, float z, float w, bool on) {
    asm volatile("{\n.reg .pred q;\nsetp.ne.u32 q, %5, 0;\n@q red.relaxed.gpu.global.add.v4.f32 [%0], {%1, %2, %3, %4};\n}"
        :: "l"(p), "f"(x), "f"(y), "f"(z), "f"(w), "r"((uint32_t)on) : "memory");
}
__device__ __forceinline__ void fence_rel_gpu() { asm volatile("fence.proxy.async.global;\nfence.release.gpu;" ::: "memory"); }
__device__ __forceinline__ void fence_acq_gpu() { asm volatile("fence.acquire.gpu;" ::: "memory"); }
template<int N> __device__ __forceinline__ void poll_words(uint4 (&v)[N], const uint4* p, int stride, uint32_t tag) {
    #pragma unroll 1
    for (int it = 0; it < POLL_MAX; it++) {
        uint32_t bad = 0;
        #pragma unroll
        for (int i = 0; i < N; i++) v[i] = ld_ll(p + i * stride);
        #pragma unroll
        for (int i = 0; i < N; i++) bad |= (v[i].z ^ tag) | (v[i].w ^ tag);
        if (__all_sync(0xffffffffu, !bad)) break;
    }
}
__device__ __forceinline__ void pause(uint32_t n) { const uint32_t c0 = clk32(); while (clk32() - c0 < n) {} }
template<int B> __device__ __forceinline__ uint32_t low_byte(float v, uint32_t src) { return __byte_perm(__float_as_uint(v), src, 0x3214 + B); }
__device__ __forceinline__ uint32_t low_bits(float v, uint32_t tag2) { return (__float_as_uint(v) & ~3u) | tag2; }
__device__ __forceinline__ float untag2(uint32_t w, uint32_t tag2) { return __uint_as_float(w ^ tag2); }
__device__ __forceinline__ bool tagged2(uint32_t w, uint32_t tag2) { return (w & 3u) == tag2; }
__device__ __forceinline__ uint32_t umax4(uint4 v) { return max(max(v.x, v.y), max(v.z, v.w)); }
constexpr uint32_t ONE2 = 0x3F803F80u;
__device__ __forceinline__ uint32_t pack2(float lo, float hi) { uint32_t d; asm("cvt.rn.bf16x2.f32 %0, %1, %2;" : "=r"(d) : "f"(hi), "f"(lo)); return d; }
__device__ __forceinline__ float bf_lo(uint32_t v) { return __uint_as_float(v << 16); }
__device__ __forceinline__ float bf_lo_after(uint32_t v, float nonneg) { float d; asm("prmt.b32 %0, %1, %2, 0x10ff;" : "=f"(d) : "r"(v), "f"(nonneg)); return d; }
__device__ __forceinline__ float bf_hi_after(uint32_t v, float nonneg) { float d; asm("prmt.b32 %0, %1, %2, 0x32ff;" : "=f"(d) : "r"(v), "f"(nonneg)); return d; }
__device__ __forceinline__ float bf_hi(uint32_t v) { return __uint_as_float(v & 0xffff0000u); }
__device__ __forceinline__ float rbf(float x) { return bf_lo(pack2(x, 0.f)); }
__device__ __forceinline__ uint32_t hsub2(uint32_t a, uint32_t b) { uint32_t d; asm("sub.rn.bf16x2 %0, %1, %2;" : "=r"(d) : "r"(a), "r"(b)); return d; }
__device__ __forceinline__ uint32_t hadd2(uint32_t a, uint32_t b) { uint32_t d; asm("add.rn.bf16x2 %0, %1, %2;" : "=r"(d) : "r"(a), "r"(b)); return d; }
__device__ __forceinline__ uint32_t hmul2(uint32_t a, uint32_t b) { uint32_t d; asm("mul.rn.bf16x2 %0, %1, %2;" : "=r"(d) : "r"(a), "r"(b)); return d; }
__device__ __forceinline__ uint32_t hmax2(uint32_t a, uint32_t b) { uint32_t d; asm("max.bf16x2 %0, %1, %2;" : "=r"(d) : "r"(a), "r"(b)); return d; }
__device__ __forceinline__ uint32_t hmin2(uint32_t a, uint32_t b) { uint32_t d; asm("min.bf16x2 %0, %1, %2;" : "=r"(d) : "r"(a), "r"(b)); return d; }
__device__ __forceinline__ float ex2(float x) { float y; asm("ex2.approx.ftz.f32 %0, %1;" : "=f"(y) : "f"(x)); return y; }
__device__ __forceinline__ float rcp(float x) { float y; asm("rcp.approx.ftz.f32 %0, %1;" : "=f"(y) : "f"(x)); return y; }
__device__ __forceinline__ float shfl_x(float v, int m) { return __shfl_xor_sync(0xffffffffu, v, m); }
constexpr float LOG2E = 1.4426950408889634f;
__device__ __forceinline__ float sigmoidf(float x) { return rcp(1.0f + ex2(-LOG2E * x)); }
struct Recip { uint32_t hi, lo; };
__device__ __forceinline__ Recip split_recip(float r) { Recip q; q.hi = pack2(r, r); const float l = r - bf_hi(q.hi); q.lo = pack2(l, l); return q; }
__device__ __forceinline__ uint32_t hdiv2(uint32_t n, Recip r) { uint32_t d; asm("fma.rn.bf16x2 %0, %1, %2, %3;" : "=r"(d) : "r"(n), "r"(r.hi), "r"(hmul2(n, r.lo))); return d; }
__device__ __forceinline__ uint32_t ln_pair(uint32_t x, uint32_t m2, Recip r, uint32_t a, uint32_t s) { return hadd2(hmul2(hdiv2(hsub2(x, m2), r), a), s); }
__device__ __forceinline__ void ln_final(float s1, float s2, uint32_t& m2, float& rinv) {
    const float mean = s1 * (1.0f / 1024.0f), var = fmaf(-mean, mean, s2 * (1.0f / 1024.0f));
    m2 = pack2(mean, mean);
    float sd;
    asm("sqrt.approx.ftz.f32 %0, %1;" : "=f"(sd) : "f"(rbf(rbf(fmaxf(var, 0.f)) + 1e-5f)));
    rinv = rcp(rbf(sd));
}
__device__ __forceinline__ uint32_t f2key(float f) { uint32_t u = __float_as_uint(f); return (u & 0x80000000u) ? ~u : (u | 0x80000000u); }

__device__ __forceinline__ void fm_extrema(const uint32_t (&p)[16], float& cp, float& cn) {
    uint32_t mx = p[0], mn = p[0];
    #pragma unroll
    for (int k = 1; k < 15; k += 2) { mx = hmax2(hmax2(mx, p[k]), p[k + 1]); mn = hmin2(hmin2(mn, p[k]), p[k + 1]); }
    mx = hmax2(mx, p[15]); mn = hmin2(mn, p[15]);
    cp = -fmaxf(bf_lo(mx), bf_hi(mx)) * LOG2E; cn = fminf(bf_lo(mn), bf_hi(mn)) * LOG2E;
}
template<int TB> __device__ __forceinline__ void wgmma_n32_rs(float (&d)[16], uint32_t a0, uint32_t a1, uint32_t a2, uint32_t a3, uint64_t db, int sc) {
  asm volatile("{\n.reg .pred p;\nsetp.ne.b32 p, %21, 0;\n"
    "wgmma.mma_async.sync.aligned.m64n32k16.f32.bf16.bf16 {%0, %1, %2, %3, %4, %5, %6, %7, %8, %9, %10, %11, %12, %13, %14, %15}, {%16,%17,%18,%19}, %20, p, 1, 1, %22;\n}\n"
    : "+f"(d[0]), "+f"(d[1]), "+f"(d[2]), "+f"(d[3]), "+f"(d[4]), "+f"(d[5]), "+f"(d[6]), "+f"(d[7]), "+f"(d[8]), "+f"(d[9]), "+f"(d[10]), "+f"(d[11]), "+f"(d[12]), "+f"(d[13]), "+f"(d[14]), "+f"(d[15])
    : "r"(a0), "r"(a1), "r"(a2), "r"(a3), "l"(db), "r"(sc), "n"(TB));
}
template<int TA, int TB> __device__ __forceinline__ void wgmma_n40_ss(float (&d)[20], uint64_t da, uint64_t db, int sc) {
  asm volatile("{\n.reg .pred p;\nsetp.ne.b32 p, %22, 0;\n"
    "wgmma.mma_async.sync.aligned.m64n40k16.f32.bf16.bf16 {%0, %1, %2, %3, %4, %5, %6, %7, %8, %9, %10, %11, %12, %13, %14, %15, %16, %17, %18, %19}, %20, %21, p, 1, 1, %23, %24;\n}\n"
    : "+f"(d[0]), "+f"(d[1]), "+f"(d[2]), "+f"(d[3]), "+f"(d[4]), "+f"(d[5]), "+f"(d[6]), "+f"(d[7]), "+f"(d[8]), "+f"(d[9]), "+f"(d[10]), "+f"(d[11]), "+f"(d[12]), "+f"(d[13]), "+f"(d[14]), "+f"(d[15]), "+f"(d[16]), "+f"(d[17]), "+f"(d[18]), "+f"(d[19])
    : "l"(da), "l"(db), "r"(sc), "n"(TA), "n"(TB));
}
template<int TA, int TB> __device__ __forceinline__ void wgmma_n128_ss(float (&d)[64], uint64_t da, uint64_t db, int sc) {
  asm volatile("{\n.reg .pred p;\nsetp.ne.b32 p, %66, 0;\n"
    "wgmma.mma_async.sync.aligned.m64n128k16.f32.bf16.bf16 {%0, %1, %2, %3, %4, %5, %6, %7, %8, %9, %10, %11, %12, %13, %14, %15, %16, %17, %18, %19, %20, %21, %22, %23, %24, %25, %26, %27, %28, %29, %30, %31, %32, %33, %34, %35, %36, %37, %38, %39, %40, %41, %42, %43, %44, %45, %46, %47, %48, %49, %50, %51, %52, %53, %54, %55, %56, %57, %58, %59, %60, %61, %62, %63}, %64, %65, p, 1, 1, %67, %68;\n}\n"
    : "+f"(d[0]), "+f"(d[1]), "+f"(d[2]), "+f"(d[3]), "+f"(d[4]), "+f"(d[5]), "+f"(d[6]), "+f"(d[7]), "+f"(d[8]), "+f"(d[9]), "+f"(d[10]), "+f"(d[11]), "+f"(d[12]), "+f"(d[13]), "+f"(d[14]), "+f"(d[15]), "+f"(d[16]), "+f"(d[17]), "+f"(d[18]), "+f"(d[19]), "+f"(d[20]), "+f"(d[21]), "+f"(d[22]), "+f"(d[23]), "+f"(d[24]), "+f"(d[25]), "+f"(d[26]), "+f"(d[27]), "+f"(d[28]), "+f"(d[29]), "+f"(d[30]), "+f"(d[31]), "+f"(d[32]), "+f"(d[33]), "+f"(d[34]), "+f"(d[35]), "+f"(d[36]), "+f"(d[37]), "+f"(d[38]), "+f"(d[39]), "+f"(d[40]), "+f"(d[41]), "+f"(d[42]), "+f"(d[43]), "+f"(d[44]), "+f"(d[45]), "+f"(d[46]), "+f"(d[47]), "+f"(d[48]), "+f"(d[49]), "+f"(d[50]), "+f"(d[51]), "+f"(d[52]), "+f"(d[53]), "+f"(d[54]), "+f"(d[55]), "+f"(d[56]), "+f"(d[57]), "+f"(d[58]), "+f"(d[59]), "+f"(d[60]), "+f"(d[61]), "+f"(d[62]), "+f"(d[63])
    : "l"(da), "l"(db), "r"(sc), "n"(TA), "n"(TB));
}
template<int TB> __device__ __forceinline__ void wgmma_n128_rs(float (&d)[64], uint32_t a0, uint32_t a1, uint32_t a2, uint32_t a3, uint64_t db, int sc) {
  asm volatile("{\n.reg .pred p;\nsetp.ne.b32 p, %69, 0;\n"
    "wgmma.mma_async.sync.aligned.m64n128k16.f32.bf16.bf16 {%0, %1, %2, %3, %4, %5, %6, %7, %8, %9, %10, %11, %12, %13, %14, %15, %16, %17, %18, %19, %20, %21, %22, %23, %24, %25, %26, %27, %28, %29, %30, %31, %32, %33, %34, %35, %36, %37, %38, %39, %40, %41, %42, %43, %44, %45, %46, %47, %48, %49, %50, %51, %52, %53, %54, %55, %56, %57, %58, %59, %60, %61, %62, %63}, {%64,%65,%66,%67}, %68, p, 1, 1, %70;\n}\n"
    : "+f"(d[0]), "+f"(d[1]), "+f"(d[2]), "+f"(d[3]), "+f"(d[4]), "+f"(d[5]), "+f"(d[6]), "+f"(d[7]), "+f"(d[8]), "+f"(d[9]), "+f"(d[10]), "+f"(d[11]), "+f"(d[12]), "+f"(d[13]), "+f"(d[14]), "+f"(d[15]), "+f"(d[16]), "+f"(d[17]), "+f"(d[18]), "+f"(d[19]), "+f"(d[20]), "+f"(d[21]), "+f"(d[22]), "+f"(d[23]), "+f"(d[24]), "+f"(d[25]), "+f"(d[26]), "+f"(d[27]), "+f"(d[28]), "+f"(d[29]), "+f"(d[30]), "+f"(d[31]), "+f"(d[32]), "+f"(d[33]), "+f"(d[34]), "+f"(d[35]), "+f"(d[36]), "+f"(d[37]), "+f"(d[38]), "+f"(d[39]), "+f"(d[40]), "+f"(d[41]), "+f"(d[42]), "+f"(d[43]), "+f"(d[44]), "+f"(d[45]), "+f"(d[46]), "+f"(d[47]), "+f"(d[48]), "+f"(d[49]), "+f"(d[50]), "+f"(d[51]), "+f"(d[52]), "+f"(d[53]), "+f"(d[54]), "+f"(d[55]), "+f"(d[56]), "+f"(d[57]), "+f"(d[58]), "+f"(d[59]), "+f"(d[60]), "+f"(d[61]), "+f"(d[62]), "+f"(d[63])
    : "r"(a0), "r"(a1), "r"(a2), "r"(a3), "l"(db), "r"(sc), "n"(TB));
}
template<int TB> __device__ __forceinline__ void wgmma_n256_rs(float (&d)[128], uint32_t a0, uint32_t a1, uint32_t a2, uint32_t a3, uint64_t db, int sc) {
  asm volatile("{\n.reg .pred p;\nsetp.ne.b32 p, %133, 0;\n"
    "wgmma.mma_async.sync.aligned.m64n256k16.f32.bf16.bf16 {%0, %1, %2, %3, %4, %5, %6, %7, %8, %9, %10, %11, %12, %13, %14, %15, %16, %17, %18, %19, %20, %21, %22, %23, %24, %25, %26, %27, %28, %29, %30, %31, %32, %33, %34, %35, %36, %37, %38, %39, %40, %41, %42, %43, %44, %45, %46, %47, %48, %49, %50, %51, %52, %53, %54, %55, %56, %57, %58, %59, %60, %61, %62, %63, %64, %65, %66, %67, %68, %69, %70, %71, %72, %73, %74, %75, %76, %77, %78, %79, %80, %81, %82, %83, %84, %85, %86, %87, %88, %89, %90, %91, %92, %93, %94, %95, %96, %97, %98, %99, %100, %101, %102, %103, %104, %105, %106, %107, %108, %109, %110, %111, %112, %113, %114, %115, %116, %117, %118, %119, %120, %121, %122, %123, %124, %125, %126, %127}, {%128,%129,%130,%131}, %132, p, 1, 1, %134;\n}\n"
    : "+f"(d[0]), "+f"(d[1]), "+f"(d[2]), "+f"(d[3]), "+f"(d[4]), "+f"(d[5]), "+f"(d[6]), "+f"(d[7]), "+f"(d[8]), "+f"(d[9]), "+f"(d[10]), "+f"(d[11]), "+f"(d[12]), "+f"(d[13]), "+f"(d[14]), "+f"(d[15]), "+f"(d[16]), "+f"(d[17]), "+f"(d[18]), "+f"(d[19]), "+f"(d[20]), "+f"(d[21]), "+f"(d[22]), "+f"(d[23]), "+f"(d[24]), "+f"(d[25]), "+f"(d[26]), "+f"(d[27]), "+f"(d[28]), "+f"(d[29]), "+f"(d[30]), "+f"(d[31]), "+f"(d[32]), "+f"(d[33]), "+f"(d[34]), "+f"(d[35]), "+f"(d[36]), "+f"(d[37]), "+f"(d[38]), "+f"(d[39]), "+f"(d[40]), "+f"(d[41]), "+f"(d[42]), "+f"(d[43]), "+f"(d[44]), "+f"(d[45]), "+f"(d[46]), "+f"(d[47]), "+f"(d[48]), "+f"(d[49]), "+f"(d[50]), "+f"(d[51]), "+f"(d[52]), "+f"(d[53]), "+f"(d[54]), "+f"(d[55]), "+f"(d[56]), "+f"(d[57]), "+f"(d[58]), "+f"(d[59]), "+f"(d[60]), "+f"(d[61]), "+f"(d[62]), "+f"(d[63]), "+f"(d[64]), "+f"(d[65]), "+f"(d[66]), "+f"(d[67]), "+f"(d[68]), "+f"(d[69]), "+f"(d[70]), "+f"(d[71]), "+f"(d[72]), "+f"(d[73]), "+f"(d[74]), "+f"(d[75]), "+f"(d[76]), "+f"(d[77]), "+f"(d[78]), "+f"(d[79]), "+f"(d[80]), "+f"(d[81]), "+f"(d[82]), "+f"(d[83]), "+f"(d[84]), "+f"(d[85]), "+f"(d[86]), "+f"(d[87]), "+f"(d[88]), "+f"(d[89]), "+f"(d[90]), "+f"(d[91]), "+f"(d[92]), "+f"(d[93]), "+f"(d[94]), "+f"(d[95]), "+f"(d[96]), "+f"(d[97]), "+f"(d[98]), "+f"(d[99]), "+f"(d[100]), "+f"(d[101]), "+f"(d[102]), "+f"(d[103]), "+f"(d[104]), "+f"(d[105]), "+f"(d[106]), "+f"(d[107]), "+f"(d[108]), "+f"(d[109]), "+f"(d[110]), "+f"(d[111]), "+f"(d[112]), "+f"(d[113]), "+f"(d[114]), "+f"(d[115]), "+f"(d[116]), "+f"(d[117]), "+f"(d[118]), "+f"(d[119]), "+f"(d[120]), "+f"(d[121]), "+f"(d[122]), "+f"(d[123]), "+f"(d[124]), "+f"(d[125]), "+f"(d[126]), "+f"(d[127])
    : "r"(a0), "r"(a1), "r"(a2), "r"(a3), "l"(db), "r"(sc), "n"(TB));
}

constexpr uint32_t T_INI = 500;
constexpr uint32_t T_X0 = 450;
constexpr uint32_t T_XD = 600;
constexpr uint32_t T_P0 = 1500;
constexpr uint32_t T_P1 = 3000;
constexpr uint32_t T_W1 = 2800;
constexpr uint32_t T_S0 = 3300;
constexpr uint32_t T_S1 = 5800;
constexpr uint32_t T_WLATE = 4000;
constexpr uint32_t T_REST = 6000;
constexpr uint32_t T_COL = 7000;
constexpr uint32_t T_COL2 = 14000;
constexpr uint32_t T_OSC = 24000;
constexpr uint32_t T_OSD = 800;
constexpr uint32_t KVDLY = 700;
constexpr uint32_t OP0 = 500;
constexpr uint32_t OPS = 400;
constexpr int PFJ = 3;
constexpr int WOJ = 10;
constexpr int CREG = 208;
constexpr int KW = 8;
constexpr int DEP = 2;
constexpr int DNE = 12;
constexpr uint32_t YDLY = 600;
constexpr uint32_t YD2 = 600;
constexpr uint32_t GDLY = 300;
constexpr uint32_t FDLY = 400;
struct Ptrs { const bf16 *x, *c, *wmod, *wr, *wqkv, *wo; bf16* out; Scratch* s; };

#define BAR(i) (sb + OFF_BAR + 8u * (i))

__device__ __forceinline__ int d_block(int hg, int n) {
    const int m = n - (n >= 9 ? 9 : 2);
    return n < 2 ? 2 * hg + n : 2 * (m + (m >= hg)) + (n >= 9);
}
__host__ __device__ constexpr uint32_t bar_count(int i) {
    return ((i >= B_E1 && i < B_E1 + 3) || (i >= B_S0FREE && i < B_PHI + 4) || i == B_OWN || i == B_OWN + 1 || (i >= B_ED && i < B_ED + 16)
            || i == B_STFREE || i == B_X2 || i == B_OUTW || i == B_YP || i == B_RED) ? 8
         : ((i >= B_KVD && i < B_KVD + 2) || i == B_ST2 || i == B_TURN) ? 4 : (i == B_KVF || i == B_KVF + 1) ? 2 : 1;
}
template<int I0, int I1> __device__ __forceinline__ void init_barriers(uint32_t sb) {
    #pragma unroll
    for (int i = I0; i < I1; i++) mbar_init(BAR(i), bar_count(i));
}
__device__ __forceinline__ uint32_t pop_max(uint32_t& k) {
    const uint32_t m = __reduce_max_sync(0xffffffffu, k);
    k = k == m ? 0u : k;
    return m;
}
__device__ __forceinline__ uint32_t cand_row(uint32_t key) { return (key & 126u) * 16 + 31 - ((key >> 7) & 31u); }
__device__ __forceinline__ uint32_t mod_pos(int step, int g) { return step * 64 + (g >> 1) * 16 + (g & 1) * 4; }
__device__ __forceinline__ void fma8(float (&a)[8], uint4 w, float s) {
    a[0] = fmaf(bf_lo(w.x), s, a[0]); a[1] = fmaf(bf_hi(w.x), s, a[1]); a[2] = fmaf(bf_lo(w.y), s, a[2]); a[3] = fmaf(bf_hi(w.y), s, a[3]);
    a[4] = fmaf(bf_lo(w.z), s, a[4]); a[5] = fmaf(bf_hi(w.z), s, a[5]); a[6] = fmaf(bf_lo(w.w), s, a[6]); a[7] = fmaf(bf_hi(w.w), s, a[7]);
}
__device__ __forceinline__ float reduce8(const float (&v)[8], int lane) {
    const bool b3 = lane & 16, b2 = lane & 8, b1 = lane & 4;
    float a[4], b[2];
    #pragma unroll
    for (int i = 0; i < 4; i++) { float keep = b3 ? v[4 + i] : v[i], send = b3 ? v[i] : v[4 + i]; a[i] = keep + shfl_x(send, 16); }
    #pragma unroll
    for (int i = 0; i < 2; i++) { float keep = b2 ? a[2 + i] : a[i], send = b2 ? a[i] : a[2 + i]; b[i] = keep + shfl_x(send, 8); }
    float keep = b1 ? b[1] : b[0], send = b1 ? b[0] : b[1];
    return keep + shfl_x(send, 4);
}
__device__ __forceinline__ bool mod_collect(uint4 w0, uint4 w1, uint4 w2, uint4 w3, uint32_t sb, int jb, int lane, uint32_t tag2) {
    const uint32_t add = lane < 16 ? ONE2 : 0u;
    const uint32_t lo = pack2((__uint_as_float(w0.x) + __uint_as_float(w1.x)) + (__uint_as_float(w2.x) + __uint_as_float(w3.x)),
                              (__uint_as_float(w0.y) + __uint_as_float(w1.y)) + (__uint_as_float(w2.y) + __uint_as_float(w3.y)));
    const uint32_t hi = pack2((__uint_as_float(w0.z) + __uint_as_float(w1.z)) + (__uint_as_float(w2.z) + __uint_as_float(w3.z)),
                              (untag2(w0.w, tag2) + untag2(w1.w, tag2)) + (untag2(w2.w, tag2) + untag2(w3.w, tag2)));
    sts64(sb + OFF_MODS + jb * 256 + (lane & 15) * 16 + (lane >> 4) * 8, hadd2(lo, add), hadd2(hi, add));
    return !(((w0.w ^ tag2) | (w1.w ^ tag2) | (w2.w ^ tag2) | (w3.w ^ tag2)) & 3u);
}
__device__ __forceinline__ void phi_issue(float (&pp)[2][16], const uint32_t* a, uint32_t sb, int pair) {
    const uint64_t dw = mk_desc(sb + OFF_WPHI + pair * 4096, 16, 512, 2);
    wg_fence();
    #pragma unroll
    for (int ks = 0; ks < 2; ks++)
        #pragma unroll
        for (int h = 0; h < 2; h++) wgmma_n32_rs<1>(pp[h], a[8 * h + 4 * ks], a[8 * h + 4 * ks + 1], a[8 * h + 4 * ks + 2], a[8 * h + 4 * ks + 3], desc_add(dw, h * 2048 + ks * 1024), ks);
    wg_commit();
}
__device__ __forceinline__ void phi_transpose(float (&pp)[2][16], uint32_t (&pt)[16], uint32_t wr, uint32_t rd) {
    wg_wait<0>();
    acc_fence(pp[0]); acc_fence(pp[1]);
    #pragma unroll
    for (int q = 0; q < 4; q++) {
        const float (&a)[16] = pp[q >> 1]; const int o = 8 * (q & 1);
        stsm4(wr ^ (q << 5), pack2(a[o], a[o + 1]), pack2(a[o + 2], a[o + 3]), pack2(a[o + 4], a[o + 5]), pack2(a[o + 6], a[o + 7]));
    }
    __syncwarp();
    #pragma unroll
    for (int i = 0; i < 4; i++) { const uint4 v = lds128(rd ^ (i << 4)); pt[4 * i] = v.x; pt[4 * i + 1] = v.y; pt[4 * i + 2] = v.z; pt[4 * i + 3] = v.w; }
    __syncwarp();
}

__global__ void __cluster_dims__(2, 1, 1) __launch_bounds__(NTHREADS, 1)
fused_kernel(const Ptrs p, const __grid_constant__ CUtensorMap tmW, const __grid_constant__ CUtensorMap tmWo, const __grid_constant__ CUtensorMap tmPhi,
             const __grid_constant__ CUtensorMap tmG, const __grid_constant__ CUtensorMap tmU, const __grid_constant__ CUtensorMap tmD,
             const __grid_constant__ CUtensorMap tmX, const __grid_constant__ CUtensorMap tmO, const __grid_constant__ CUtensorMap tmM,
             const __grid_constant__ CUtensorMap tmR, const __grid_constant__ CUtensorMap tmG8, const __grid_constant__ CUtensorMap tmU8,
             const __grid_constant__ CUtensorMap tmD8)
{
    extern __shared__ __align__(1024) uint8_t smem_raw[];
    const uint32_t sb = smem_u32(smem_raw);
    const int tid = threadIdx.x, lane = tid & 31, warp = __shfl_sync(0xffffffffu, tid >> 5, 0);
    const int b = blockIdx.x;
    const int pr = b >> 1, rank = b & 1;
    const int cls = pr < 4 ? 15 : pr < 36 ? 2 * ((pr - 4) & 7) : 2 * ((pr - 36) % 7) + 1, mem = pr < 4 ? pr : pr < 36 ? (pr - 4) >> 3 : (pr - 36) / 7;
    const int hg = (((cls + 1) >> 1) & 1) * 4 + mem, rb = (cls >> 1) * 2 + rank;
    const bool ffn = b < 112;
    const uint32_t cstart = clk32();

    if (warp >= 8) {
        const int t = tid & 127, w4 = warp & 3, g = lane >> 2, c = lane & 3;
        reg_dec<40>();
        if (w4 == 0) { tmap_prefetch(&tmX); tmap_prefetch(&tmW); }
        if (w4 == 3) tmap_prefetch(&tmM);
        if (w4 < 2) while (clk32() - cstart < T_INI) {}
        if (elect_one()) {
            if (w4 & 2) { if (w4 & 1) init_barriers<B_WS, B_COUNT>(sb); else init_barriers<B_XS, B_WS>(sb); }
            else { if (w4 & 1) init_barriers<B_MP, B_XS>(sb); else init_barriers<0, B_MP>(sb); }
        }
        __syncwarp();
        if (w4 == 1) {
            asm volatile("fence.mbarrier_init.release.cluster;" ::: "memory");
            expect_tx_e(BAR(B_PX), 2048); sts32(sb + OFF_SEEN, 0);
        }
        bar_arrive(0, 384);
        if (w4 == 2) {
            #pragma unroll 1
            for (int i = 0; i < 4; i++) {
                while (clk32() - cstart < T_X0 + i * T_XD) {}
                bulk_load_e(sb + OFF_XS + i * 8192u, p.x + (size_t)(b * 16 + i * 4) * 1024, 8192, BAR(B_XS + i));
                expect_tx_e(BAR(B_XS + i), 8192);
            }
        }
        if (w4 == 3 && b < 64) {
            while (b >= 32 && clk32() - cstart < T_W1) {}
            #pragma unroll 1
            for (int i = 0; i < 4; i++) {
                tma2_ef_e(sb + OFF_WST + i * 8192u, &tmM, (((b >> 2) & 1) ? 0 : 1024) + (b >> 3) * 64, (b & 3) * 256 + i * 64, BAR(B_WS + i));
                expect_tx_e(BAR(B_WS + i), 8192);
            }
        }
        cluster_arrive();
        const uint32_t tag = ld_rlx(p.s->done) + 1, tag2 = tag % 3u;
        if (w4 == 0) {
            uint4* clr = p.s->kvp + (hg * 1024 + rb) * 32 + lane;
            #pragma unroll 1
            for (int j = 0; j < 3; j++) {
                while (clk32() - cstart < (j ? T_P1 : T_P0)) {}
                if (lane < 24) asm volatile("prefetch.global.L2 [%0];" :: "l"((const char*)p.wqkv + ((j * 128 + b) * 24 + lane) * 128));
            }
            int s = 0, par = 1;
            #pragma unroll 1
            for (int j = 0; j < 19; j++) {
                if (j >= 2) mbar_wait(BAR(j == 2 ? B_STFREE : B_E1 + s), j == 2 ? 0 : par);
                else while (clk32() - cstart < (j ? T_S1 : T_S0)) {}
                const uint32_t st = sb + OFF_RING + s * 65536u;
                if (j < 16) {
                    tma4_ef_e(st + 16384u, &tmW, j * 64, hg * 2, BAR(B_F1 + s));
                    tma2_e(st, &tmX, j * 64, rb * 128, BAR(B_F1 + s));
                    expect_tx_e(BAR(B_F1 + s), 65536);
                    if (j >= WOJ && j < WOJ + 4) asm volatile("prefetch.global.L2 [%0];" :: "l"((const char*)p.wo + (j - WOJ) * 524288 + (b * 32 + lane) * 128));
                } else if (j == 17) {
                    #pragma unroll 1
                    for (int n = 0; n < 2; n++) {
                        expect_tx_e(BAR(B_FB + 4 + n), 16384);
                        tma3_ef_e(st + n * 16384u, &tmWo, (2 * hg + n) * 64, hg * 2, BAR(B_FB + 4 + n));
                    }
                } else if (j == 18) {
                    expect_tx_e(BAR(B_S0), ffn ? 65536 : 32768);
                    #pragma unroll 1
                    for (int i = 0; i < (ffn ? 4 : 2); i++)
                        tma2_ef_e(st + i * 16384u, i < 2 ? &tmX : i == 2 ? &tmG : &tmU, i < 2 ? hg * 128 + i * 64 : pr * 64, i < 2 ? rb * 128 : rank * 512, BAR(B_S0));
                }
                par ^= s == 1;
                s = s == 0 ? 2 : s - 1;
                if (j >= 2 && j < 18) {
                    #pragma unroll
                    for (int i = 0; i < 4; i++) stg_fill(clr + i * 512, EMPTY);
                    clr += 2048;
                }
                const int piece = j - PFJ;
                if (ffn && piece >= 0 && piece < PND + 2 * PNG) {
                    if (piece < PND) tma3_e(sb + OFF_DUMMY, &tmD8, rank * 8, pr * 64 + piece * PRD, BAR(B_PF));
                    else tma2_e(sb + OFF_DUMMY, (piece & 1) ? &tmU8 : &tmG8, pr * 64, rank * 512 + 512 - PRG - ((piece - PND) >> 1) * PRG, BAR(B_PF));
                }
            }
            expect_tx_e(BAR(B_PF), ffn ? PND * PRD * 128 + 2 * PNG * PRG * 16 : 0);
        } else if (w4 == 1) {
            #pragma unroll 1
            for (int it = 0, jb = 4; it < POLL_MAX && jb < 16; it++) {
                while (clk32() - cstart < (jb < 8 ? T_COL : T_COL2)) {}
                const int n = min(4, (jb < 8 ? 8 : 16) - jb);
                bulk_load_e(sb + OFF_WPHI, p.s->mp + jb * 128, n * 2048, BAR(B_MP));
                expect_tx_e(BAR(B_MP), n * 2048);
                mbar_wait(BAR(B_MP), it & 1);
                #pragma unroll 1
                for (int q = 0; q < n; q++) {
                    const uint32_t a = sb + OFF_WPHI + q * 2048 + (lane >> 4) * 1024 + (lane & 15) * 16;
                    if (!__all_sync(0xffffffffu, mod_collect(lds128(a), lds128(a + 256), lds128(a + 512), lds128(a + 768), sb, jb, lane, tag2))) break;
                    arrive_many(BAR(B_MOD + jb), bar_count(B_MOD));
                    jb++;
                }
            }
            fence_async_smem();
            __syncwarp();
            expect_tx_e(BAR(B_WPHI), 8192);
            tma2_e(sb + OFF_WPHI, &tmPhi, 0, hg * 128, BAR(B_WPHI));
            #pragma unroll 1
            for (int i = 0; i < 4; i++) {
                uint4* rw = p.s->rowh + (rb * 8 + i * 2 + (lane >> 4)) * 128 + hg * 16 + (lane & 15);
                stg_fill(rw, EMPTY); stg_fill(rw + 16384, EMPTY);
                if (lane < 18) stg_fill(p.s->kvf + (hg * 4 + i) * 288 + (lane < 16 ? (rb >> 2) * 64 + (rb & 3) * 8 + (lane >> 3) * 32 + (lane & 7) : 240 + rb * 2 + lane), EMPTY);
            }
            if (hg == 0 && lane < 8) stg_fill(p.s->cand + rb * 8 + lane, 0);
            if (lane < 28) stg_fill(lane < 16 ? p.s->st2 + rb * 128 + hg * 16 + lane : lane < 20 ? p.s->flo + (rb * 16 + hg * 2) * 2 + lane - 16
                                    : p.s->rsc + ((rb * 4 + ((lane - 20) >> 1)) * 8 + hg) * 2 + (lane & 1), 0);
            fence_rel_gpu();
            #pragma unroll 1
            for (int i = 0; i < (ffn ? 9 : 8); i++) {
                while (clk32() - cstart < T_OSC + i * T_OSD) {}
                uint4* d = (i < 8 ? p.s->os + (rb * 16 + 2 * hg) * 1024 + i * 256 : p.s->yp + pr * 512 + rank * 128) + lane;
                #pragma unroll
                for (int q = 0; q < 4; q++) { stg_fill(d + q * 32, EMPTY); stg_fill(d + (i < 8 ? 128 : 256) + q * 32, EMPTY); }
            }
        } else {
            const int hw = w4 & 1;
            const uint32_t fb = BAR(B_RF + 2 * hw);
            if (w4 == 2) {
                if (lane < 8) stg_fill(p.s->rest + b * 8 + lane, 0);
                else if (lane < 24 && b >= 64) stg_fill(p.s->mp + b * 16 + lane - 8, EMPTY);
            }
            bar_sync(3, 320);
            const uint32_t buf = sb + OFF_SP + hw * 8192u;
            #pragma unroll 1
            for (int job = b < 64; job < 2; job++) {
                const int nr = job ? 8 : 4;
                const int c0 = job ? 2048 + b * 32 : (((b >> 2) & 1) ? 0 : 1024) + (b >> 3) * 64 + hw * 32;
                const int row0 = job ? hw * 512 : (b & 3) * 256;
                while (clk32() - cstart < (job ? T_REST : T_WLATE)) __nanosleep(100);
                float macc[8] = {0.f, 0.f, 0.f, 0.f, 0.f, 0.f, 0.f, 0.f};
                #pragma unroll 1
                for (int q = -2; q < nr; q++) {
                    if (q >= 0) {
                        mbar_wait(fb + (q & 1) * 8, (q >> 1) & 1);
                        const uint32_t sv0 = sb + OFF_SILU + (row0 + q * 64 + g) * 2, wa = buf + (q & 1) * 4096u + lane * 16u;
                        #pragma unroll
                        for (int i = 0; i < 8; i += 2) {
                            const uint32_t s0 = lds16(sv0 + i * 16), s1 = lds16(sv0 + i * 16 + 16);
                            const uint4 w0 = lds128(wa + i * 512u), w1 = lds128(wa + i * 512u + 512u);
                            fma8(macc, w0, bf_lo(s0)); fma8(macc, w1, bf_lo(s1));
                        }
                    }
                    __syncwarp();
                    if (q + 2 < nr) {
                        expect_tx_e(fb + (q & 1) * 8, 4096);
                        tma2_ef_e(buf + (q & 1) * 4096u, &tmR, c0, row0 + (q + 2) * 64, fb + (q & 1) * 8);
                    }
                }
                stsf(sb + OFF_RED0 + (job ? hw * 256 + (c * 8 + g) * 4 : mod_pos(hw * 2 + (c >> 1), g) + (c & 1) * 8), reduce8(macc, lane));
                bar_sync(4, 64);
                if (w4 == 2) {
                    const uint4 u0 = lds128(sb + OFF_RED0 + (lane & 15) * 16), u1 = lds128(sb + OFF_RED0 + 256 + (lane & 15) * 16);
                    const float v0 = __uint_as_float(u0.x) + __uint_as_float(u1.x), v1 = __uint_as_float(u0.y) + __uint_as_float(u1.y);
                    const float v2 = __uint_as_float(u0.z) + __uint_as_float(u1.z), v3 = __uint_as_float(u0.w) + __uint_as_float(u1.w);
                    const uint32_t add = (b >> 5) == 2 ? ONE2 : 0u;
                    if (job == 0) { if (lane < 16) st_ll(p.s->mp + b * 16 + lane, u0.x, u0.y, u0.z, low_bits(__uint_as_float(u0.w), tag2)); }
                    else { if (lane < 8) st_ll(p.s->rest + b * 8 + lane, hadd2(pack2(v0, v1), add), hadd2(pack2(v2, v3), add), tag, tag); }
                }
                bar_sync(4, 64);
            }
            tmap_prefetch(hw ? &tmWo : &tmG); tmap_prefetch(hw ? &tmU : &tmD); tmap_prefetch(hw ? &tmPhi : &tmO);
        }
        __syncwarp();
        cluster_wait();
        bar_sync(2, 128);
        reg_inc<504 - 2 * CREG>();
        #pragma unroll 1
        for (int pp = 0; pp < 2; pp++) {
            mbar_wait(BAR(B_PHI + pp), 0);
            fence_async_smem();
            float o[2][20];
            const uint32_t vb = OFF_V + pp * 16384u;
            const uint64_t dp = mk_desc(sb + (pp ? OFF_PHI1 : OFF_PHI0), 16, 1024, 1), dv = mk_desc(sb + vb, OFF_ONES - vb, 512, 2);
            wg_fence();
            #pragma unroll
            for (int hh = 0; hh < 2; hh++) {
                #pragma unroll
                for (int ks = 0; ks < 8; ks++)
                    wgmma_n40_ss<1, 1>(o[hh], desc_add(dp, hh * 16384 + ks * 2048), desc_raw(dv, (hh * 8 + ks) * (64 - (64 << 16))), ks);
                wg_commit();
            }
            #pragma unroll
            for (int hh = 0; hh < 2; hh++) {
                if (hh) wg_wait<0>(); else wg_wait<1>();
                acc_fence(o[hh]);
                if (hh) arrive_one(BAR(B_KVD + pp));
                if (hh == 0 && pp && w4 < 2) {
                    mbar_wait(BAR(B_KVD), 0);
                    bulk_load_e(sb + OFF_KVS + w4 * 8192u, p.s->kvp + ((hg * 4 + w4) * 16 + rb) * 512, 8192, BAR(B_KVS + w4));
                    expect_tx_e(BAR(B_KVS + w4), 8192);
                }
                uint4* dst = p.s->kvp + (((hg * 4 + 2 * pp + hh) * 16 + (t >> 3)) * 16 + rb) * 32 + (t & 7);
                const float (&a)[20] = o[hh];
                #pragma unroll
                for (int k = 0; k < 2; k++) {
                    const uint32_t z = __float_as_uint(a[16 + 2 * k]);
                    st_ll(dst + k * 8, low_byte<1>(a[4 * k], z), low_byte<2>(a[4 * k + 1], z), low_byte<3>(a[4 * k + 2], z), low_bits(a[4 * k + 3], tag2));
                    st_ll(dst + 16 + k * 8, __float_as_uint(a[8 + 4 * k]), __float_as_uint(a[9 + 4 * k]), __float_as_uint(a[10 + 4 * k]), low_bits(a[11 + 4 * k], tag2));
                }
            }
        }
        {
            uint4* const fin = p.s->kvf + (hg * 4 + w4) * 288;
            {
                const uint4* src = p.s->kvp + ((hg * 4 + w4) * 16 + rb) * 512 + lane;
                uint4 w[16];
                if (w4 < 2) {
                    mbar_wait(BAR(B_KVS + w4), 0);
                    #pragma unroll
                    for (int i = 0; i < 16; i++) w[i] = lds128(sb + OFF_KVS + w4 * 8192u + i * 512u + lane * 16u);
                } else {
                    pause(KVDLY);
                    #pragma unroll
                    for (int i = 0; i < 16; i++) w[i].w = EMPTY;
                }
                #pragma unroll 1
                for (int it = 0; it < POLL_MAX; it++) {
                    uint32_t bad = 0;
                    #pragma unroll
                    for (int i = 0; i < 16; i++) bad |= w[i].w ^ tag2;
                    if (__all_sync(0xffffffffu, !(bad & 3))) break;
                    #pragma unroll
                    for (int i = 0; i < 16; i++) ld_ll_if(w[i], src + i * 32, !tagged2(w[i].w, tag2));
                }
                float s[5], s2[5];
                #pragma unroll
                for (int i = 0; i < 16; i++) {
                    const float z = __uint_as_float(__byte_perm(__byte_perm(w[i].x, w[i].y, 0x0400), w[i].z, 0x4210));
                    float (&a)[5] = (i & 1) ? s2 : s;
                    if (i < 2) { a[0] = __uint_as_float(w[i].x); a[1] = __uint_as_float(w[i].y); a[2] = __uint_as_float(w[i].z); a[3] = untag2(w[i].w, tag2); a[4] = z; }
                    else { a[0] += __uint_as_float(w[i].x); a[1] += __uint_as_float(w[i].y); a[2] += __uint_as_float(w[i].z); a[3] += untag2(w[i].w, tag2); a[4] += z; }
                }
                #pragma unroll
                for (int i = 0; i < 5; i++) s[i] += s2[i];
                char* d = (char*)fin + ((rb >> 2) * 16 + (rb & 3) * 2 + (g & 1)) * 64 + (((lane >> 3) ^ (rb & 3)) << 4) + c * 4;
                st_ll4(d, pack2(s[0], s[1]));
                st_ll4(d + 512, pack2(s[2], s[3]));
                st_ll4_if((char*)fin + 4096 + rb * 32 + (g * 2 + c) * 4, pack2(s[4], s[4]), lane < 16 && c < 2);
            }
            mbar_wait(BAR(B_PF), 1);
            fence_acq_gpu();
            uint4 v[9];
            pause(GDLY);
            #pragma unroll 1
            for (int it = 0; it < POLL_MAX; it++) {
                uint32_t m = 0;
                #pragma unroll
                for (int k = 0; k < 9; k++) v[k] = ld_ll(fin + k * 32 + lane);
                #pragma unroll
                for (int k = 0; k < 9; k++) m = max(m, umax4(v[k]));
                if (__all_sync(0xffffffffu, m != EMPTY)) break;
            }
            #pragma unroll
            for (int k = 0; k < 8; k++) sts128(sb + OFF_SP + w4 * 4096u + k * 512u + lane * 16u, v[k]);
            const uint32_t za = sb + OFF_Z + ((lane >> 3) * 16 + ((lane >> 1) & 3) * 2 + (lane & 1) * 8) * 64u + ((w4 ^ ((lane >> 1) & 3)) << 4);
            sts128(za, make_uint4(v[8].x, v[8].x, v[8].x, v[8].x)); sts128(za + 64, make_uint4(v[8].z, v[8].z, v[8].z, v[8].z));
            __syncwarp();
            arrive_one(BAR(B_KVF + (w4 >> 1)));
        }
        if (w4 == 0) {
            const unsigned* f = (const unsigned*)(p.s->flo + (rb * 16 + d_block(hg, lane & 15)) * 2);
            const uint4* const a0 = p.s->os + rb * 16384;
            uint32_t seen = 0;
            uint32_t kb = hg ? 0 : 2, s = 4, freeb = BAR(B_OWN), par = 0;
            mbar_wait(BAR(B_OWN), 0);
            fence_async_smem();
            bulk_store_e(p.s->os + (rb * 16 + 2 * hg) * 1024, sb + OFF_OWN, 16384);
            bulk_commit();
            mbar_wait(BAR(B_REL), 0);
            bulk_wait();
            st_flag_e(p.s->flo + (rb * 16 + 2 * hg) * 2, tag);
            pause(FDLY);
            #pragma unroll 1
            for (int n = 2; n < 16; n++) {
                if (!((seen >> n) & 1)) {
                    if (n >= 8) asm volatile("ld.acquire.cta.shared.u32 %0, [%1];" : "=r"(seen) : "r"(sb + OFF_SEEN) : "memory");
                    #pragma unroll 1
                    for (int it = 0; it < POLL_MAX && !((seen >> n) & 1); it++) { seen = __ballot_sync(0xffffffffu, ld_rlx(f) == tag); fence_acq_gpu(); }
                }
                mbar_wait(freeb, par);
                bulk_load_e(sb + OFF_DA + s * 16384u, a0 + kb * 1024, 16384, BAR(B_FA + s));
                expect_tx_e(BAR(B_FA + s), 16384);
                if (n == 6) mbar_wait(BAR(B_PUB), 0);
                kb = n == 8 ? 1 : kb + 2;
                if ((kb >> 1) == hg) kb += 2;
                s = (SLOT_A >> (4 * n + 4)) & 7;
                if (n >= 5) { freeb = BAR(B_ED + n - 5); par = 1; } else if (n == 3) freeb = BAR(B_OWN + 1);
            }
        } else if (w4 == 1) {
            if (ffn) { expect_tx_e(BAR(B_GU), 98304); expect_tx_e(BAR(B_WD), 65536); }
            fence_rel_gpu();
            arrive_one(BAR(B_REL));
            mbar_wait(BAR(B_S0FREE), 0);
            #pragma unroll 1
            for (int n = 2; n < (ffn ? 20 : 16); n++) {
                if (n >= 6) mbar_wait(BAR(B_ED + n - 6), 1);
                if (n < 16) {
                    const uint32_t s = (SLOT_B >> (4 * n)) & 7, bar = BAR(B_FB + s), dst = sb + OFF_DB + s * 16384u;
                    expect_tx_e(bar, 16384);
                    tma3_ef_e(dst, &tmWo, d_block(hg, n) * 64, hg * 2, bar);
                    if (ffn && (n == 6 || n == 7)) tma2_ef_e(sb + OFF_GB + (n & 1) * 16384u, (n & 1) ? &tmU : &tmG, pr * 64, rank * 512 + 128, BAR(B_GU));
                } else if (n < 18) {
                    tma2_ef_e(sb + OFF_UP0 + (n & 1) * 16384u, (n & 1) ? &tmU : &tmG, pr * 64, rank * 512 + 256, BAR(B_GU));
                    tma2_ef_e(sb + OFF_UP1 + (n & 1) * 16384u, (n & 1) ? &tmU : &tmG, pr * 64, rank * 512 + 384, BAR(B_GU));
                } else {
                    tma3_ef_e(sb + OFF_DN0 + (n & 1) * 16384u, &tmD, pr * 64, rank * 8 + (n & 1) * 2, BAR(B_WD));
                    tma3_ef_e(sb + OFF_DN1 + (n & 1) * 16384u, &tmD, pr * 64, rank * 8 + 4 + (n & 1) * 2, BAR(B_WD));
                }
            }
        } else if (w4 == 3) {
            const unsigned* f = (const unsigned*)(p.s->flo + (rb * 16 + d_block(hg, lane & 15)) * 2);
            uint32_t seen = 0xffff0003u;
            mbar_wait(BAR(B_PUB), 0);
            #pragma unroll 1
            for (int it = 0; it < POLL_MAX && seen != 0xffffffffu; it++) {
                const uint32_t m = seen | __ballot_sync(0xffffffffu, !((seen >> lane) & 1) && ld_rlx(f) == tag);
                if (m != seen) {
                    seen = m;
                    fence_acq_gpu();
                    __syncwarp();
                    asm volatile(EL "st.release.cta.shared.u32 [%0], %1;\n}" :: "r"(sb + OFF_SEEN), "r"(seen) : "memory");
                }
            }
        } else {
            mbar_wait(BAR(B_OWN + 1), 0);
            fence_async_smem();
            #pragma unroll 1
            for (uint32_t i = 0, due = clk32() + OP0; i < 4; i++, due += OPS) {
                while ((int)(clk32() - due) < 0) {}
                bulk_store_e(p.s->os + (rb * 16 + 2 * hg + 1) * 1024 + i * 256, sb + OFF_OWN + 16384u + i * 4096u, 4096);
            }
            bulk_commit();
            mbar_wait(BAR(B_REL), 0);
            bulk_wait();
            st_flag_e(p.s->flo + (rb * 16 + 2 * hg + 1) * 2, tag);
            arrive_one(BAR(B_PUB));
            {
                uint4 w[4];
                poll_words<4>(w, p.s->rest + hg * 32 + lane, 256, tag);
                sts64(sb + OFF_PAR + lane * 8, w[2].x, w[2].y); sts64(sb + OFF_PAR + 256 + lane * 8, w[1].x, w[1].y);
                sts64(sb + OFF_PAR + 512 + lane * 8, w[3].x, w[3].y); sts64(sb + OFF_PAR + 768 + lane * 8, w[0].x, w[0].y);
                const uint2 wr = ldg64(p.wr + hg * 128 + lane * 4);
                sts64(sb + OFF_BQ + lane * 8, hmul2(w[2].x, wr.x), hmul2(w[2].y, wr.y));
            }
            float s = 0.f;
            #pragma unroll 1
            for (int i = 0; i < 2; i++) {
                uint4 w[4]; uint2 wr[4];
                #pragma unroll
                for (int q = 0; q < 4; q++) wr[q] = ldg64(p.wr + (lane + 32 * q + 128 * i) * 4);
                poll_words<4>(w, p.s->rest + 512 + i * 128 + lane, 32, tag);
                #pragma unroll
                for (int q = 0; q < 4; q++) { const uint32_t r0 = hmul2(w[q].x, wr[q].x), r1 = hmul2(w[q].y, wr[q].y); s += (bf_lo(r0) + bf_hi(r0)) + (bf_lo(r1) + bf_hi(r1)); }
            }
            __syncwarp();
            #pragma unroll
            for (int m = 16; m >= 1; m >>= 1) s += shfl_x(s, m);
            if (lane == 0) { stsf(sb + OFF_ATOT, s); sts128(sb + OFF_BQ + 272, make_uint4(ONE2, ONE2, ONE2, ONE2)); }
            __syncwarp();
            arrive_one(BAR(B_PAR));
        }
        __syncwarp();
        {
            mbar_wait(BAR(B_PAR), 0);
            const uint4 pa = lds128(sb + OFF_PAR + (lane & 15) * 16), ps = lds128(sb + OFF_PAR + 256 + (lane & 15) * 16);
            const uint4 wr = ldg128(p.wr + hg * 128 + (lane & 15) * 8);
            const float atot = ldsf(sb + OFF_ATOT);
            mbar_wait(BAR(B_RED), 0);
            uint4 w;
            #pragma unroll 1
            for (int it = 0; it < POLL_MAX; it++) {
                w = ld_ll(p.s->st2 + rb * 128 + t);
                if (__all_sync(0xffffffffu, __uint_as_float(w.w) == 8.0f)) break;
            }
            uint32_t m2; float rinv;
            ln_final(__uint_as_float(w.x), __uint_as_float(w.y), m2, rinv);
            const uint32_t grp = rb * 4 + w4;
            uint32_t k = (f2key(fmaf(-bf_lo(m2), atot, __uint_as_float(w.z)) * rinv) & ~0xfffu) | ((31 - lane) << 7) | (grp * 2);
            const uint32_t best0 = pop_max(k), best1 = pop_max(k) | 1u;
            st_ll_if(p.s->cand + grp * 2 + lane, best0, best1, tag, tag, hg == 0 && lane < 2);
            const uint32_t row = w4 * 32 + 31 - (((lane < 16 ? best0 : best1) >> 7) & 31u);
            mbar_wait(BAR(B_X2), 0);
            const uint4 xv = lds128(sb + OFF_OUT + (row >> 3) * 2048u + ((lane >> 3) & 1) * 1024u + (row & 7) * 128u + (((lane ^ row) & 7) << 4));
            sts64(sb + OFF_ST2 + t * 8, m2, __float_as_uint(rinv));
            __syncwarp();
            arrive_one(BAR(B_ST2));
            pause(1);
            const uint32_t rm = __shfl_sync(0xffffffffu, m2, row & 31);
            const Recip rr = split_recip(__shfl_sync(0xffffffffu, rinv, row & 31));
            const uint32_t h0 = ln_pair(xv.x, rm, rr, pa.x, ps.x), h1 = ln_pair(xv.y, rm, rr, pa.y, ps.y);
            const uint32_t h2 = ln_pair(xv.z, rm, rr, pa.z, ps.z), h3 = ln_pair(xv.w, rm, rr, pa.w, ps.w);
            uint4* d = p.s->rowh + (grp * 2 + (lane >> 4)) * 128 + hg * 16 + (lane & 15);
            st_ll(d, h0, h1, h2, h3);
            st_ll(d + 16384, xv.x, xv.y, xv.z, xv.w);
            float r = (fmaf(bf_lo(h0), bf_lo(wr.x), bf_hi(h0) * bf_hi(wr.x)) + fmaf(bf_lo(h1), bf_lo(wr.y), bf_hi(h1) * bf_hi(wr.y)))
                    + (fmaf(bf_lo(h2), bf_lo(wr.z), bf_hi(h2) * bf_hi(wr.z)) + fmaf(bf_lo(h3), bf_lo(wr.w), bf_hi(h3) * bf_hi(wr.w)));
            #pragma unroll
            for (int m = 8; m >= 1; m >>= 1) r += shfl_x(r, m);
            st_ll_if(p.s->rsc + (grp * 8 + hg) * 2 + (lane >> 4), __float_as_uint(r), __float_as_uint(r), tag, tag, !(lane & 15));
        }
        if (w4 == 0) {
            uint4 cv[2];
            poll_words<2>(cv, p.s->cand + lane * 2, 64, tag);
            const uint32_t ka = min(cv[0].x, cv[1].x), kb = max(cv[0].y, cv[1].y);
            uint32_t k0 = max(cv[0].x, cv[1].x), k1 = max(ka, kb), k2 = min(ka, kb), k3 = min(cv[0].y, cv[1].y), m[4];
            uint4 hv[4][2];
            const uint4* const h0 = p.s->rowh + rank * 64 + lane;
            #pragma unroll
            for (int i = 0; i < 4; i++) {
                m[i] = __reduce_max_sync(0xffffffffu, k0);
                if (k0 == m[i]) { k0 = k1; k1 = k2; k2 = k3; }
                hv[i][0] = ld_ll(h0 + (m[i] & 127u) * 128); hv[i][1] = ld_ll(h0 + (m[i] & 127u) * 128 + 32);
            }
            sts128(sb + OFF_SEL + 32, make_uint4(m[0], m[1], m[2], m[3]));
            __syncwarp();
            arrive_one(BAR(B_CAND));
            #pragma unroll 1
            for (int it = 0; it < POLL_MAX; it++) {
                uint32_t mx = 0;
                #pragma unroll
                for (int i = 0; i < 4; i++) mx = max(mx, max(hv[i][0].x, hv[i][1].x));
                if (__all_sync(0xffffffffu, mx != EMPTY)) break;
                #pragma unroll
                for (int i = 0; i < 4; i++) { hv[i][0] = ld_ll(h0 + (m[i] & 127u) * 128); hv[i][1] = ld_ll(h0 + (m[i] & 127u) * 128 + 32); }
            }
            #pragma unroll
            for (int i = 0; i < 4; i++) { sts128(sb + OFF_ROWS + i * 1056u + lane * 16u, hv[i][0]); sts128(sb + OFF_ROWS + i * 1056u + 528u + lane * 16u, hv[i][1]); }
            __syncwarp();
            arrive_one(BAR(B_ROWS));
        } else if (w4 == 3) {
            mbar_wait(BAR(B_CAND), 0);
            const uint32_t m = lds32(sb + OFF_SEL + 32 + (lane >> 3) * 4), slot = m & 127u, row = cand_row(m);
            uint4 sc[1];
            poll_words<1>(sc, p.s->rsc + ((slot >> 1) * 8 + (lane & 7)) * 2 + (slot & 1), 0, tag);
            float r = __uint_as_float(sc[0].x & sc[0].y);
            r += shfl_x(r, 1); r += shfl_x(r, 2); r += shfl_x(r, 4);
            r = rbf(r);
            const uint32_t key = (f2key(r) & 0xffff0000u) | (0xffffu - row);
            uint32_t kq = key;
            const uint32_t best0 = pop_max(kq), best1 = pop_max(kq), tok = key == best0 ? 0 : key == best1 ? 1 : 2;
            sts32(sb + OFF_SEL + 48 + (lane >> 3) * 4, tok);
            if (tok < 2) sts128(sb + OFF_SEL + tok * 16, make_uint4(row, slot, __float_as_uint(r), 0));
            __syncwarp();
            arrive_one(BAR(B_SEL));
        } else if (w4 == 1) {
            mbar_wait(BAR(B_SEL), 0);
            const uint4 sel = lds128(sb + OFF_SEL + rank * 16);
            const int col = pr * 16 + c * 2 + (lane >> 4) + (lane & 8);
            uint32_t xs, hs; uint4 gw;
            #pragma unroll 1
            for (int it = 0; it < POLL_MAX; it++) {
                const char* a = (const char*)(p.s->rowh + sel.y * 128) + (col >> 1) * 4;
                hs = ld_rlx(a); xs = ld_rlx(a + 262144); gw = ld_ll(p.s->rest + 768 + (col >> 2));
                if (__all_sync(0xffffffffu, hs != EMPTY && xs != EMPTY && gw.z == tag && gw.w == tag)) break;
            }
            const uint32_t gq = (col & 2) ? gw.y : gw.x;
            const float fx = (col & 1) ? bf_hi(xs) : bf_lo(xs), fh = (col & 1) ? bf_hi(hs) : bf_lo(hs), fg = (col & 1) ? bf_hi(gq) : bf_lo(gq);
            const float sg = rbf(sigmoidf(__uint_as_float(sel.z)));
            const uint4* src = p.s->yp + g * 512 + rank * 256 + pr * 4 + c;
            bf16* optr = p.out + (size_t)sel.x * 1024 + col;
            asm volatile("" : "+l"(optr));
            uint4 w[7];
            if (ffn) mbar_wait(BAR(B_YP), 0);
            pause(ffn ? YDLY : YDLY + YD2);
            #pragma unroll
            for (int i = 0; i < 7; i++) w[i] = ld_ll(src + i * 4096);
            #pragma unroll 1
            for (int it = 0; it < POLL_MAX; it++) {
                uint32_t m[7];
                #pragma unroll
                for (int i = 0; i < 7; i++) m[i] = max(w[i].x, w[i].z);
                if (__all_sync(0xffffffffu, max(max(max(m[0], m[1]), max(m[2], m[3])), max(max(m[4], m[5]), m[6])) != EMPTY)) break;
                #pragma unroll
                for (int i = 0; i < 7; i++) ld_ll_if(w[i], src + i * 4096, m[i] == EMPTY);
            }
            float y0, y1, y2, y3;
            {
                auto sum7 = [](uint32_t a, uint32_t b, uint32_t c, uint32_t d, uint32_t e, uint32_t f, uint32_t g) {
                    return ((__uint_as_float(a) + __uint_as_float(b)) + (__uint_as_float(c) + __uint_as_float(d))) + ((__uint_as_float(e) + __uint_as_float(f)) + __uint_as_float(g)); };
                y0 = sum7(w[0].x, w[1].x, w[2].x, w[3].x, w[4].x, w[5].x, w[6].x); y1 = sum7(w[0].y, w[1].y, w[2].y, w[3].y, w[4].y, w[5].y, w[6].y);
                y2 = sum7(w[0].z, w[1].z, w[2].z, w[3].z, w[4].z, w[5].z, w[6].z); y3 = sum7(w[0].w, w[1].w, w[2].w, w[3].w, w[4].w, w[5].w, w[6].w);
            }
            const bool b4 = lane & 16, b3 = lane & 8;
            const float a0 = (b4 ? y2 : y0) + shfl_x(b4 ? y0 : y2, 16), a1 = (b4 ? y3 : y1) + shfl_x(b4 ? y1 : y3, 16);
            float y = (b3 ? a1 : a0) + shfl_x(b3 ? a0 : a1, 8);
            y += shfl_x(y, 4);
            const float upd = rbf(rbf(y) * sg);
            asm volatile("st.global.b16 [%0], %1;" :: "l"(optr), "h"((uint16_t)pack2(fx + rbf(fg * rbf(fh + upd)), 0.f)) : "memory");
            if (b == 0 && lane == 0) p.s->done[0] = tag;
        } else {
            mbar_wait(BAR(B_CAND), 0);
            const uint32_t cg = (cand_row(lds32(sb + OFF_SEL + 32 + c * 4)) >> 3) - rb * 16;
            uint32_t late = __reduce_or_sync(0xffffffffu, cg < 16 ? 1u << cg : 0u);
            mbar_wait(BAR(B_OUTW), 0);
            fence_async_smem();
            #pragma unroll 1
            for (uint32_t i = 0; i < 16; i++)
                if (!((late >> i) & 1))
                    asm volatile(EL "cp.async.bulk.tensor.3d.global.shared::cta.bulk_group [%0, {0, %2, %3}], [%1];\n}"
                        :: "l"(&tmO), "r"(sb + OFF_OUT + i * 2048u), "r"(rb * 128 + i * 8), "r"(hg * 2) : "memory");
            bulk_commit();
            mbar_wait(BAR(B_SEL), 0);
            const uint32_t row0 = lds32(sb + OFF_SEL) - rb * 128, row1 = lds32(sb + OFF_SEL + 16) - rb * 128;
            #pragma unroll 1
            for (; late; late &= late - 1) {
                const uint32_t i = __ffs(late) - 1;
                #pragma unroll 1
                for (uint32_t q = 0; q < 4; q++) {
                    const uint32_t r = q * 2 + (lane >> 4), ch = lane & 15;
                    const uint4 v = lds128(sb + OFF_OUT + i * 2048u + (ch >> 3) * 1024u + r * 128u + (((ch ^ r) & 7) << 4));
                    if (i * 8 + r != row0 && i * 8 + r != row1) stg128(p.out + (size_t)(rb * 128 + i * 8 + r) * 1024 + hg * 128 + ch * 8, v);
                }
            }
            bulk_wait();
        }
    } else {
        const int w4 = warp & 3, wgi = warp >> 2;
        uint32_t m2[2], r[4]; Recip ri0, ri1;
        {
            const int g = lane >> 2, c = lane & 3, xrow = b * 16 + warp * 2;
            if (b < 32)
                asm volatile("prefetch.global.L2 [%0];" :: "l"(p.wmod + (size_t)((b & 3) * 256 + tid) * 6144 + (((b >> 2) & 1) ? 0 : 1024) + (b >> 3) * 64));
            const uint2 cv = ldg64(p.c + tid * 4);
            const uint32_t tag = ld_rlx(p.s->done) + 1;
            if (lane < 2) stg_fill(p.s->st1 + xrow + lane, 0);
            if (warp == 0 && lane < 16 && b < 64) stg_fill(p.s->mp + b * 16 + lane, EMPTY);
            if (tid < 64) { int s = tid >> 2; sts128(sb + OFF_ONES + tid * 16, make_uint4(((tid & 3) == ((s >> 1) & 3)) ? 0x3F80u : 0u, 0, 0, 0)); }
            cluster_arrive();
            reg_inc<232>();
            {
                const float c0 = bf_lo(cv.x), c1 = bf_hi(cv.x), c2 = bf_lo(cv.y), c3 = bf_hi(cv.y);
                sts64(sb + OFF_SILU + tid * 8, pack2(c0 * sigmoidf(c0), c1 * sigmoidf(c1)), pack2(c2 * sigmoidf(c2), c3 * sigmoidf(c3)));
            }
            const uint32_t tag2 = tag % 3u;
            bar_sync(0, 384);
            bar_arrive(3, 320);
            #pragma unroll 1
            for (int part = 0; part < 2; part++)
            if (part == (b < 32)) {
                mbar_wait(BAR(B_XS + (warp >> 1)), 0);
                float sd[2][4], q1[2][4], q2[2][4];
                #pragma unroll
                for (int e = 0; e < 4; e++) { sd[0][e] = sd[1][e] = q1[0][e] = q1[1][e] = q2[0][e] = q2[1][e] = 0.f; }
                #pragma unroll
                for (int i = 0; i < 8; i++) {
                    uint32_t a0, a1, a2, a3;
                    ldsm4(a0, a1, a2, a3, sb + OFF_XS + warp * 4096u + ((lane >> 3) & 1) * 2048u + i * 256u + (lane >> 4) * 128u + (lane & 7) * 16u);
                    mma16816(sd[i & 1], a0, a1, a2, a3, ONE2, ONE2);
                    mma1688(q1[0], a0, a1, a0); mma1688(q2[0], a0, a1, a1); mma1688(q1[1], a2, a3, a2); mma1688(q2[1], a2, a3, a3);
                }
                const float d0 = __shfl_sync(0xffffffffu, (g & 1) ? q1[0][1] + q1[1][1] : q1[0][0] + q1[1][0], g * 4 + (g >> 1));
                const float d1 = __shfl_sync(0xffffffffu, (g & 1) ? q2[0][3] + q2[1][3] : q2[0][2] + q2[1][2], g * 4 + (g >> 1));
                float sk = (c & 1) ? sd[0][2] + sd[1][2] : sd[0][0] + sd[1][0], qk = (c & 1) ? d1 : d0;
                #pragma unroll
                for (int m = 4; m <= 16; m <<= 1) { sk += shfl_x(sk, m); qk += shfl_x(qk, m); }
                uint32_t mm; float ri;
                ln_final(sk, qk, mm, ri);
                const Recip rr = split_recip(ri);
                st_ll_if(p.s->st1 + xrow + lane, mm, rr.hi, rr.lo, tag, lane < 2);
            } else if (b < 64) {
                float m[4][4];
                uint32_t sv[4];
                ldsm4(sv[0], sv[1], sv[2], sv[3], sb + OFF_SILU + ((b & 3) * 256 + warp * 32) * 2 + (lane >> 3) * 16);
                mbar_wait(BAR(B_WS + (warp >> 1)), 0);
                #pragma unroll
                for (int tt = 0; tt < 4; tt++) {
                    m[tt][0] = m[tt][1] = m[tt][2] = m[tt][3] = 0.f;
                    #pragma unroll
                    for (int e = 0; e < 2; e++) {
                        uint32_t a0, a1, a2, a3;
                        ldsm4t(a0, a1, a2, a3, sb + OFF_WST + warp * 4096u + (e * 16 + (lane & 7) + ((lane >> 4) << 3)) * 128u + (((2 * tt + ((lane >> 3) & 1)) ^ (lane & 7)) << 4));
                        mma16816(m[tt], a0, a1, a2, a3, sv[2 * e], sv[2 * e + 1]);
                    }
                }
                const uint32_t ra = sb + OFF_RED0 + warp * 256 + mod_pos(c, g);
                stsf(ra, (c & 2) ? ((c & 1) ? m[3][0] : m[2][0]) : ((c & 1) ? m[1][0] : m[0][0]));
                stsf(ra + 8, (c & 2) ? ((c & 1) ? m[3][2] : m[2][2]) : ((c & 1) ? m[1][2] : m[0][2]));
                if (warp != 7) bar_arrive(5, 256);
                else {
                    bar_sync(5, 256);
                    float v0 = 0.f, v1 = 0.f, v2 = 0.f, v3 = 0.f;
                    #pragma unroll
                    for (int w = 0; w < 4; w++) {
                        const uint4 u = lds128(sb + OFF_RED0 + w * 512 + lane * 16);
                        v0 += __uint_as_float(u.x); v1 += __uint_as_float(u.y); v2 += __uint_as_float(u.z); v3 += __uint_as_float(u.w);
                    }
                    v0 += shfl_x(v0, 16); v1 += shfl_x(v1, 16); v2 += shfl_x(v2, 16); v3 += shfl_x(v3, 16);
                    st_ll_if(p.s->mp + b * 16 + lane, __float_as_uint(v0), __float_as_uint(v1), __float_as_uint(v2), low_bits(v3, tag2), lane < 16);
                }
            }
            cluster_wait();
            uint4 st[2];
            bool need = warp < 4;
            #pragma unroll 1
            for (int it = 0; it < POLL_MAX; it++) {
                st[0] = ld_ll(p.s->st1 + rb * 128 + warp * 16 + g); st[1] = ld_ll(p.s->st1 + rb * 128 + warp * 16 + g + 8);
                if (need) {
                    const uint4* src = p.s->mp + (warp * 8 + (lane >> 4) * 4) * 16 + (lane & 15);
                    const uint4 w0 = ld_ll(src), w1 = ld_ll(src + 16), w2 = ld_ll(src + 32), w3 = ld_ll(src + 48);
                    if (__all_sync(0xffffffffu, mod_collect(w0, w1, w2, w3, sb, warp, lane, tag2))) {
                        need = false;
                        arrive_many(BAR(B_MOD + warp), bar_count(B_MOD));
                    }
                }
                if (it == 0) {
                    mbar_wait(BAR(B_F1), 0);
                    ldsm4(r[0], r[1], r[2], r[3], sb + OFF_RING + (warp * 16 + (lane & 15)) * 128u + ((((lane >> 4) ^ lane) & 7) << 4));
                }
                if (__all_sync(0xffffffffu, st[0].w == tag && st[1].w == tag) && !need) break;
            }
            m2[0] = st[0].x; ri0.hi = st[0].y; ri0.lo = st[0].z; m2[1] = st[1].x; ri1.hi = st[1].y; ri1.lo = st[1].z;
            arrive_one(BAR(B_STFREE));
        }
        const int lane = lane_id(), g = lane >> 2, c = lane & 3;
        const int srow = warp * 16 + (lane & 15);
        const uint32_t aoff = srow * 128u + ((((lane >> 4) ^ srow) & 7) << 4);
        uint32_t pt[16], qf[32];
        float pp[2][16];
        const uint32_t roff = srow * 128u + ((lane & 7) << 4);
        {
            float accKV[128], accQ[64];
            {
                uint32_t f[2][4];
                mbar_wait(BAR(B_MOD), 0);
                uint4 md = lds128(sb + OFF_MODS + c * 16);
                int s = 0, sp = 1, par = 0;
                #pragma unroll 1
                for (int j = 0; j < 16; j++) {
                    const int sn = s == 0 ? 2 : s - 1;
                    par ^= s == 1;
                    const uint32_t modb = (wgi && j == 15) ? BAR(B_TURN) : BAR(B_MOD + ((j + 1) & 15));
                    const uint64_t db = mk_desc(sb + OFF_RING + s * 65536u + 16384u, 8192, 1024, 1);
                    #pragma unroll
                    for (int ks = 0; ks < 4; ks++) {
                        uint32_t (&ff)[4] = f[ks & 1];
                        ff[0] = ln_pair(r[0], m2[0], ri0, md.x, md.z); ff[1] = ln_pair(r[1], m2[1], ri1, md.x, md.z);
                        ff[2] = ln_pair(r[2], m2[0], ri0, md.y, md.w); ff[3] = ln_pair(r[3], m2[1], ri1, md.y, md.w);
                        const int kn = (ks + 1) & 3;
                        ldsm4(r[0], r[1], r[2], r[3], sb + OFF_RING + (ks == 3 ? sn : s) * 65536u + (aoff ^ (kn << 5)));
                        md = lds128(sb + OFF_MODS + ((ks == 3 ? j + 1 : j) * 4 + kn) * 64 + c * 16);
                        wg_fence();
                        wgmma_n256_rs<1>(accKV, ff[0], ff[1], ff[2], ff[3], desc_add(db, 16384 + ks * 2048), ks ? 1 : j);
                        wgmma_n128_rs<1>(accQ, ff[0], ff[1], ff[2], ff[3], desc_add(db, ks * 2048), ks ? 1 : j);
                        wg_commit();
                        if (ks == 3) arrive_if(BAR(B_TURN), j == 15 && !wgi);
                        if (ks == 1) mbar_wait(modb, 0);
                        if (ks == 2) mbar_wait(BAR(j < 15 ? B_F1 + sn : B_WPHI), j < 15 ? par : 0);
                        wg_wait<1>();
                        if (ks == 0) arrive_if(BAR(B_E1 + sp), j);
                    }
                    sp = s; s = sn;
                }
            }
            mbar_wait(BAR(B_E1 + 2), 0);
            wg_wait<0>();
            acc_fence(accKV); acc_fence(accQ);
            arrive_one(BAR(B_E1));
            uint32_t kf[32];
            #pragma unroll
            for (int h = 0; h < 4; h++) {
                if (h == 1) {
                    #pragma unroll
                    for (int i = 0; i < 16; i++) kf[i] = pack2(accKV[2 * i], accKV[2 * i + 1]);
                    phi_issue(pp, kf, sb, 0);
                }
                #pragma unroll
                for (int q = 0; q < 2; q++) {
                    const int o = 64 + 16 * h + 8 * q;
                    stsm4(sb + OFF_V + h * 8192u + srow * 64u + (((2 * q + (lane >> 4)) ^ ((srow >> 1) & 3)) << 4),
                          pack2(accKV[o], accKV[o + 1]), pack2(accKV[o + 2], accKV[o + 3]), pack2(accKV[o + 4], accKV[o + 5]), pack2(accKV[o + 6], accKV[o + 7]));
                }
            }
            #pragma unroll
            for (int i = 16; i < 32; i++) kf[i] = pack2(accKV[2 * i], accKV[2 * i + 1]);
            phi_transpose(pp, pt, sb + OFF_PHI0 + aoff, sb + OFF_PHI0 + (roff ^ ((lane >> 4) << 6)));
            phi_issue(pp, kf + 16, sb, 1);
            #pragma unroll
            for (int i = 0; i < 32; i++) qf[i] = pack2(accQ[2 * i], accQ[2 * i + 1]);
        }
        reg_dec<CREG>();
        {
            float cp, cn;
            fm_extrema(pt, cp, cn);
            #pragma unroll 1
            for (int u = 0; u < 4; u++) {
                const uint32_t cur = sb + ((u & 1) ? OFF_PHI1 : OFF_PHI0);
                float e[64], s[4];
                uint32_t pn[16];
                #pragma unroll
                for (int k = 0; k < 16; k++) {
                    if (k == KW) {
                        stsf(cur + aoff, e[31 + 2 * k]);
                        phi_transpose(pp, pn, cur + aoff, cur + (roff ^ ((lane >> 4) << 6)));
                    }
                    const float dep = k >= DEP ? e[33 + 2 * (k >= DEP ? k - DEP : 0)] : 0.f, f0 = bf_lo_after(pt[k], dep), f1 = bf_hi_after(pt[k], dep);
                    e[2 * k] = ex2(fmaf(f0, LOG2E, cp)); e[2 * k + 1] = ex2(fmaf(f1, LOG2E, cp));
                    e[32 + 2 * k] = ex2(fmaf(f0, -LOG2E, cn)); e[33 + 2 * k] = ex2(fmaf(f1, -LOG2E, cn));
                    if (k == 0) { s[0] = e[0]; s[1] = e[1]; s[2] = e[32]; s[3] = e[33]; }
                    else { s[0] += e[2 * k]; s[1] += e[2 * k + 1]; s[2] += e[32 + 2 * k]; s[3] += e[33 + 2 * k]; }
                }
                fm_extrema(pn, cp, cn);
                #pragma unroll
                for (int i = 0; i < 16; i++) pt[i] = pn[i];
                const float sp = s[0] + s[1], sn = s[2] + s[3], r = rcp(sp * sn), rp = r * sn, rn = r * sp;
                #pragma unroll
                for (int i = 0; i < 8; i++) {
                    const float q = i < 4 ? rp : rn;
                    sts128((cur + (lane >> 4) * 16384u + roff) ^ (i << 4), make_uint4(pack2(e[8 * i] * q, e[8 * i + 1] * q), pack2(e[8 * i + 2] * q, e[8 * i + 3] * q),
                                                                                   pack2(e[8 * i + 4] * q, e[8 * i + 5] * q), pack2(e[8 * i + 6] * q, e[8 * i + 7] * q)));
                }
                __syncwarp();
                arrive_one(BAR(B_PHI + u));
                if (u == 0) { mbar_wait(BAR(B_E1 + 1), 0); phi_issue(pp, qf, sb, 0); }
                else {
                    mbar_wait(BAR(B_KVD + (u != 1)), 0);
                    if (u == 1) phi_issue(pp, qf + 16, sb, 1);
                }
            }
            wg_wait<0>();
        }
        uint32_t x2[16][2], wf[32][4];
        const uint32_t woff = ((lane >> 3) & 1) * 16384u + ((lane & 7) + ((lane >> 4) << 3)) * 128u + (((warp ^ lane) & 7) << 4);
        mbar_wait(BAR(B_S0), 0);
        #pragma unroll
        for (int q = 0; q < 8; q++) {
            ldsm4(x2[2 * q][0], x2[2 * q][1], x2[2 * q + 1][0], x2[2 * q + 1][1], sb + OFF_XT + (q >> 2) * 16384u + (aoff ^ ((q & 3) << 5)));
            ldsm4t(wf[q][0], wf[q][1], wf[q][2], wf[q][3], sb + OFF_GA + q * 2048u + woff);
        }
        __syncwarp();
        arrive_one(BAR(B_S0FREE));
        float acc[64];
        const uint64_t da0 = mk_desc(sb + OFF_DA + wgi * 8192u, 16, 1024, 1), db0 = mk_desc(sb + OFF_DB, 8192, 1024, 1);
        #pragma unroll 1
        for (int pp = 0; pp < 2; pp++) {
            float o0[20], o1[20];
            const uint64_t dk = mk_desc(sb + OFF_SP + pp * 8192u, OFF_Z - OFF_SP - pp * 8160u, 512, 2);
            const uint64_t dq = mk_desc(sb + (pp ? OFF_PHI1 : OFF_PHI0) + wgi * 8192u, 16, 1024, 1);
            mbar_wait(BAR(B_FB + 4 + pp), 0);
            mbar_wait(BAR(B_PHI + 2 + pp), 0);
            mbar_wait(BAR(B_KVF + pp), 0);
            fence_async_smem();
            wg_fence();
            #pragma unroll
            for (int ks = 0; ks < 4; ks++) {
                wgmma_n40_ss<0, 1>(o0, desc_add(dq, ks * 32), desc_add(dk, ks * 1024), ks);
                wgmma_n40_ss<0, 1>(o1, desc_add(dq, 16384 + ks * 32), desc_raw(dk, 256 + ks * 64 - (255 << 16)), ks);
            }
            wg_commit();
            wg_wait<0>();
            acc_fence(o0); acc_fence(o1);
            arrive_if(BAR(B_ED), pp);
            uint32_t op[16];
            #pragma unroll
            for (int hh = 0; hh < 2; hh++) {
                const float (&o)[20] = hh ? o1 : o0;
                const Recip rd0 = split_recip(rcp(rbf(rbf(o[16]) + 1e-6f)));
                const Recip rd1 = split_recip(rcp(rbf(rbf(o[18]) + 1e-6f)));
                #pragma unroll
                for (int j = 0; j < 4; j++) { op[8 * hh + 2 * j] = hdiv2(pack2(o[4 * j], o[4 * j + 1]), rd0); op[8 * hh + 2 * j + 1] = hdiv2(pack2(o[4 * j + 2], o[4 * j + 3]), rd1); }
                #pragma unroll
                for (int q = 2 * hh; q < 2 * hh + 2; q++) stsm4(sb + OFF_OWN + pp * 16384u + (aoff ^ (q << 5)), op[4 * q], op[4 * q + 1], op[4 * q + 2], op[4 * q + 3]);
            }
            __syncwarp();
            arrive_one(BAR(B_OWN + pp));
            wg_fence();
            #pragma unroll
            for (int ks = 0; ks < 4; ks++) wgmma_n128_rs<1>(acc, op[4 * ks], op[4 * ks + 1], op[4 * ks + 2], op[4 * ks + 3], desc_add(db0, (4 + pp) * 16384u + ks * 2048), ks ? 1 : pp);
            wg_commit();
        }
        const uint32_t ooff = sb + OFF_OUT + (srow >> 3) * 1024u + aoff;
        {
            const uint32_t vchk = lane * 32u + g * 4u;
            #pragma unroll 1
            for (int n = 2; n < 16; n++) {
                const uint32_t s = (SLOT_A >> (4 * n)) & 7, sB = (SLOT_B >> (4 * n)) & 7;
                mbar_wait(BAR(B_FB + sB), (PAR_B >> n) & 1);
                mbar_wait(BAR(B_FA + s), (PAR_A >> n) & 1);
                {
                    const uint32_t ra = sb + OFF_DA + s * 16384u + warp * 2048u;
                    if (__any_sync(0xffffffffu, max(lds32(ra + vchk), lds32(ra + vchk + 1024)) == EMPTY)) {
                        #pragma unroll 1
                        for (int i = 0; i < 4; i++) {
                            uint4 v;
                            #pragma unroll 1
                            for (int it = 0; it < POLL_MAX; it++) {
                                v = ld_ll(p.s->os + (rb * 16 + d_block(hg, n)) * 1024 + warp * 128 + i * 32 + lane);
                                if (umax4(v) != EMPTY) break;
                            }
                            sts128(ra + i * 512 + lane * 16, v);
                        }
                        fence_async_smem();
                        __syncwarp();
                    }
                }
                const uint64_t da = desc_add(da0, s * 16384u), db = desc_add(db0, sB * 16384u);
                wg_fence();
                #pragma unroll
                for (int ks = 0; ks < 4; ks++) wgmma_n128_ss<0, 1>(acc, desc_add(da, ks * 32), desc_add(db, ks * 2048), 1);
                wg_commit();
                wg_wait<1>();
                arrive_one(BAR(B_ED - 1 + n));
            }
            mbar_wait(BAR(B_PAR), 0);
            uint32_t gar[16], bfr[16];
            #pragma unroll
            for (int j = 0; j < 16; j += 4) {
                ldsm4(gar[j], gar[j + 1], gar[j + 2], gar[j + 3], sb + OFF_PAR + 768 + (j + (lane >> 3)) * 16);
                ldsm4(bfr[j], bfr[j + 1], bfr[j + 2], bfr[j + 3], sb + OFF_BQ + ((lane & 1) ? (j + (lane >> 3)) * 16 : 272));
            }
            wg_wait<0>();
            acc_fence(acc);
            bar_arrive(6 + wgi, 256);
            float sd[2][4], q1[2][4], q2[2][4];
            #pragma unroll
            for (int e = 0; e < 4; e++) { sd[0][e] = sd[1][e] = q1[0][e] = q1[1][e] = q2[0][e] = q2[1][e] = 0.f; }
            #pragma unroll
            for (int s = 0; s < 8; s++) {
                #pragma unroll
                for (int e = 0; e < 4; e++) { const int j = 2 * s + (e >> 1), h = e & 1; x2[j][h] = hadd2(x2[j][h], hmul2(gar[j], pack2(acc[4 * j + 2 * h], acc[4 * j + 2 * h + 1]))); }
                mma16816(sd[s & 1], x2[2 * s][0], x2[2 * s][1], x2[2 * s + 1][0], x2[2 * s + 1][1], bfr[2 * s], bfr[2 * s + 1]);
                #pragma unroll
                for (int e = 0; e < 2; e++) { mma1688(q1[e], x2[2 * s + e][0], x2[2 * s + e][1], x2[2 * s + e][0]); mma1688(q2[e], x2[2 * s + e][0], x2[2 * s + e][1], x2[2 * s + e][1]); }
            }
            uint4* d = p.s->st2 + rb * 128 + warp * 16 + g;
            red_add4_if(d, sd[0][0] + sd[1][0], (g & 1) ? q1[0][1] + q1[1][1] : q1[0][0] + q1[1][0], sd[0][1] + sd[1][1], 1.0f, c == (g >> 1));
            red_add4_if(d + 8, sd[0][2] + sd[1][2], (g & 1) ? q2[0][3] + q2[1][3] : q2[0][2] + q2[1][2], sd[0][3] + sd[1][3], 1.0f, c == (g >> 1));
            arrive_one(BAR(B_RED));
            bar_sync(7 - wgi, 256);
            #pragma unroll
            for (int q = 0; q < 8; q++) stsm4((ooff + (q >> 2) * 1024u) ^ ((q & 3) << 5), x2[2 * q][0], x2[2 * q][1], x2[2 * q + 1][0], x2[2 * q + 1][1]);
            __syncwarp();
            arrive_one(BAR(B_X2));
        }
        const uint32_t xa = sb + OFF_OUT + warp * 4096u + ((lane >> 3) & 1) * 1024u + (lane >> 4) * 128u + (((lane ^ (lane >> 4)) & 7) << 4);
        const uint4 pa = lds128(sb + OFF_PAR + (lane & 15) * 16), ps = lds128(sb + OFF_PAR + 256 + (lane & 15) * 16), pg = lds128(sb + OFF_PAR + 512 + (lane & 15) * 16);
        if (ffn) mbar_wait(BAR(B_GU), 0);
        #pragma unroll
        for (int q = 8; q < 32; q++) ldsm4t(wf[q][0], wf[q][1], wf[q][2], wf[q][3], sb + (q < 16 ? OFF_GB : q < 24 ? OFF_UP0 : OFF_UP1) + (q & 7) * 2048u + woff);
        {
            mbar_wait(BAR(B_ST2), 0);
            #pragma unroll 1
            for (int q0 = 0; q0 < 2; q0++) {
                uint4 x[4]; uint2 st[4];
                const uint32_t a = xa + q0 * 2048u;
                #pragma unroll
                for (int q = 0; q < 4; q++) { x[q] = lds128((a + q * 256u) ^ (q << 5)); st[q] = lds64(sb + OFF_ST2 + (warp * 16 + q0 * 8 + q * 2 + (lane >> 4)) * 8); }
                #pragma unroll
                for (int q = 0; q < 4; q++) {
                    const Recip r = split_recip(__uint_as_float(st[q].y));
                    sts128((a + q * 256u) ^ (q << 5), make_uint4(
                        hadd2(x[q].x, hmul2(pg.x, ln_pair(x[q].x, st[q].x, r, pa.x, ps.x))), hadd2(x[q].y, hmul2(pg.y, ln_pair(x[q].y, st[q].x, r, pa.y, ps.y))),
                        hadd2(x[q].z, hmul2(pg.z, ln_pair(x[q].z, st[q].x, r, pa.z, ps.z))), hadd2(x[q].w, hmul2(pg.w, ln_pair(x[q].w, st[q].x, r, pa.w, ps.w)))));
                }
            }
            __syncwarp();
            arrive_one(BAR(B_OUTW));
        }
        if (ffn) {
            float acc[4][4];
            uint32_t df[4][4][4];
            {
                #pragma unroll
                for (int i = 0; i < 4; i++) { acc[i][0] = acc[i][1] = acc[i][2] = acc[i][3] = 0.f; }
                const uint32_t da = sb + (wgi ? OFF_DN1 : OFF_DN0) + w4 * 8192u + ((lane & 7) + ((lane >> 4) << 3)) * 128u;
                mbar_wait(BAR(B_WD), 0);
                #pragma unroll
                for (int q = 0; q < DNE; q++)
                    ldsm4t(df[q >> 2][q & 3][0], df[q >> 2][q & 3][1], df[q >> 2][q & 3][2], df[q >> 2][q & 3][3], da + (q & 3) * 2048u + (((2 * (q >> 2) + ((lane >> 3) & 1)) ^ (lane & 7)) << 4));
                mbar_wait(BAR(B_ROWS), 0);
                #pragma unroll
                for (int q = 0; q < 8; q++) {
                    uint32_t b0, b1, b2, b3;
                    ldsm4(b0, b1, b2, b3, sb + OFF_ROWS + (lane & 7) * 528u + (lane >> 3) * 16u + q * 64u);
                    #pragma unroll
                    for (int hf = 0; hf < 2; hf++) {
                        const int k = 16 * hf + 2 * q;
                        mma16816(acc[2 * hf], wf[k][0], wf[k][1], wf[k][2], wf[k][3], b0, b1);
                        mma16816(acc[2 * hf + 1], wf[k + 1][0], wf[k + 1][1], wf[k + 1][2], wf[k + 1][3], b2, b3);
                    }
                }
                const float gs = (acc[0][0] + acc[1][0]) + (acc[2][1] + acc[3][1]), us = (acc[0][2] + acc[1][2]) + (acc[2][3] + acc[3][3]);
                st_partner64(sb + OFF_PX + warp * 256 + lane * 8, BAR(B_PX), rank ^ 1, gs, us);
                #pragma unroll
                for (int q = DNE; q < 16; q++)
                    ldsm4t(df[q >> 2][q & 3][0], df[q >> 2][q & 3][1], df[q >> 2][q & 3][2], df[q >> 2][q & 3][3], da + (q & 3) * 2048u + (((2 * (q >> 2) + ((lane >> 3) & 1)) ^ (lane & 7)) << 4));
                mbar_wait(BAR(B_SEL), 0);
                const uint32_t tok = lds32(sb + OFF_SEL + 48 + c * 4);
                mbar_wait(BAR(B_PX), 0);
                const uint2 q = lds64(sb + OFF_PX + warp * 256 + lane * 8);
                float gt = rbf(gs + __uint_as_float(q.x));
                gt = rbf(gt * sigmoidf(gt));
                sts16(sb + OFF_HID + tok * 144 + (warp * 8 + g) * 2, pack2(gt * rbf(us + __uint_as_float(q.y)), 0.f));
            }
            bar_sync(1, 256);
            uint32_t bh[8];
            ldsm4(bh[0], bh[1], bh[2], bh[3], sb + OFF_HID + (lane & 1) * 144u + (lane >> 3) * 16u);
            ldsm4(bh[4], bh[5], bh[6], bh[7], sb + OFF_HID + (lane & 1) * 144u + (lane >> 3) * 16u + 64u);
            float y[4][4];
            #pragma unroll
            for (int tt = 0; tt < 4; tt++) { y[tt][0] = y[tt][1] = y[tt][2] = y[tt][3] = 0.f; }
            #pragma unroll
            for (int ks = 0; ks < 4; ks++)
                #pragma unroll
                for (int tt = 0; tt < 4; tt++) mma16816(y[tt], df[tt][ks][0], df[tt][ks][1], df[tt][ks][2], df[tt][ks][3], bh[2 * ks], bh[2 * ks + 1]);
            float e[4];
            #pragma unroll
            for (int i = 0; i < 4; i++) e[i] = (c & 2) ? ((c & 1) ? y[3][i] : y[2][i]) : ((c & 1) ? y[1][i] : y[0][i]);
            char* d = (char*)(p.s->yp + pr * 512 + rank * 128 + (warp * 4 + c) * 4) + g * 8;
            st_ll8(d, __float_as_uint(e[0]), __float_as_uint(e[2]));
            st_ll8(d + 4096, __float_as_uint(e[1]), __float_as_uint(e[3]));
            arrive_one(BAR(B_YP));
        }
    }
}

typedef CUresult (*EncodeFn)(CUtensorMap*, CUtensorMapDataType, cuuint32_t, void*, const cuuint64_t*, const cuuint64_t*, const cuuint32_t*,
                             const cuuint32_t*, CUtensorMapInterleave, CUtensorMapSwizzle, CUtensorMapL2promotion, CUtensorMapFloatOOBfill);

CUtensorMap make_map(EncodeFn enc, const void* ptr, uint64_t cols, uint64_t rows, uint32_t bc, uint32_t br, CUtensorMapSwizzle swz, CUtensorMapL2promotion promo) {
    CUtensorMap m;
    cuuint64_t dims[2] = {cols, rows}, strides[1] = {cols * 2};
    cuuint32_t box[2] = {bc, br}, es[2] = {1, 1};
    enc(&m, CU_TENSOR_MAP_DATA_TYPE_BFLOAT16, 2, const_cast<void*>(ptr), dims, strides, box, es, CU_TENSOR_MAP_INTERLEAVE_NONE, swz, promo,
        CU_TENSOR_MAP_FLOAT_OOB_FILL_NONE);
    return m;
}
CUtensorMap make_block_map(EncodeFn enc, const void* ptr, uint32_t sections, uint64_t rows, uint32_t br, CUtensorMapL2promotion promo) {
    CUtensorMap m;
    cuuint64_t dims[4] = {64, rows, 16, sections}, strides[3] = {sections * 2048ull, 128, 2048};
    cuuint32_t box[4] = {64, br, 2, sections}, es[4] = {1, 1, 1, 1};
    enc(&m, CU_TENSOR_MAP_DATA_TYPE_BFLOAT16, sections > 1 ? 4 : 3, const_cast<void*>(ptr), dims, strides, box, es, CU_TENSOR_MAP_INTERLEAVE_NONE,
        CU_TENSOR_MAP_SWIZZLE_128B, promo, CU_TENSOR_MAP_FLOAT_OOB_FILL_NONE);
    return m;
}

}

extern "C" void kernel_launch(void* const* d_in, const int* in_sizes, int n_in, void* d_out, int out_size) {
    (void)in_sizes; (void)n_in; (void)out_size;
    void* fn = nullptr; cudaDriverEntryPointQueryResult qr;
    cudaGetDriverEntryPoint("cuTensorMapEncodeTiled", &fn, cudaEnableDefault, &qr);
    EncodeFn enc = (EncodeFn)fn;
    void* hs = nullptr;
    cudaGetSymbolAddress(&hs, g_scratch);
    const CUtensorMapL2promotion P256 = CU_TENSOR_MAP_L2_PROMOTION_L2_256B, P128 = CU_TENSOR_MAP_L2_PROMOTION_L2_128B;
    CUtensorMap tmW = make_block_map(enc, d_in[1], 3, 1024, 64, P256);
    CUtensorMap tmWo = make_block_map(enc, d_in[3], 1, 1024, 64, P256);
    CUtensorMap tmPhi = make_map(enc, d_in[2], 32, 1024, 32, 128, CU_TENSOR_MAP_SWIZZLE_64B, P128);
    CUtensorMap tmG = make_map(enc, d_in[6], 3584, 1024, 64, 128, CU_TENSOR_MAP_SWIZZLE_128B, P128);
    CUtensorMap tmU = make_map(enc, d_in[7], 3584, 1024, 64, 128, CU_TENSOR_MAP_SWIZZLE_128B, P128);
    CUtensorMap tmD = make_block_map(enc, d_in[8], 1, 3584, 64, P128);
    CUtensorMap tmX = make_map(enc, d_in[0], 1024, 2048, 64, 128, CU_TENSOR_MAP_SWIZZLE_128B, P128);
    CUtensorMap tmO = make_block_map(enc, d_out, 1, 2048, 8, P128);
    CUtensorMap tmM = make_map(enc, d_in[10], 6144, 1024, 64, 64, CU_TENSOR_MAP_SWIZZLE_128B, P128);
    CUtensorMap tmR = make_map(enc, d_in[10], 6144, 1024, 32, 64, CU_TENSOR_MAP_SWIZZLE_NONE, P128);
    CUtensorMap tmG8 = make_map(enc, d_in[6], 3584, 1024, 8, PRG, CU_TENSOR_MAP_SWIZZLE_NONE, P128);
    CUtensorMap tmU8 = make_map(enc, d_in[7], 3584, 1024, 8, PRG, CU_TENSOR_MAP_SWIZZLE_NONE, P128);
    CUtensorMap tmD8;
    {
        cuuint64_t dims[3] = {64, 16, 3584}, strides[2] = {128, 2048};
        cuuint32_t box[3] = {8, 8, PRD}, es[3] = {1, 1, 1};
        enc(&tmD8, CU_TENSOR_MAP_DATA_TYPE_BFLOAT16, 3, d_in[8], dims, strides, box, es, CU_TENSOR_MAP_INTERLEAVE_NONE, CU_TENSOR_MAP_SWIZZLE_NONE, P128,
            CU_TENSOR_MAP_FLOAT_OOB_FILL_NONE);
    }
    Ptrs p;
    p.x = (const bf16*)d_in[0]; p.c = (const bf16*)d_in[9]; p.wmod = (const bf16*)d_in[10]; p.wr = (const bf16*)d_in[5];
    p.out = (bf16*)d_out; p.s = (Scratch*)hs;
    p.wqkv = (const bf16*)d_in[1]; p.wo = (const bf16*)d_in[3];
    cudaFuncSetAttribute(fused_kernel, cudaFuncAttributeMaxDynamicSharedMemorySize, SMEM_BYTES);
    fused_kernel<<<128, NTHREADS, SMEM_BYTES, cudaStreamPerThread>>>(p, tmW, tmWo, tmPhi, tmG, tmU, tmD, tmX, tmO, tmM, tmR, tmG8, tmU8, tmD8);
}
```
